```python
import torch

def _softmax(x, axis=-1):
    return torch.softmax(x, dim=axis)
def _gelu(x):
    return torch.nn.functional.gelu(x, approximate="tanh")
def _silu(x):
    return torch.nn.functional.silu(x)
def _sigmoid(x):
    return torch.sigmoid(x)
def _layernorm(x, axis=-1, eps=1e-5):
    m = x.mean(dim=axis, keepdim=True)
    v = x.var(dim=axis, keepdim=True, unbiased=False)
    return (x - m) / torch.sqrt(v + eps)
def _scatter_add(tgt, idx, src, axis=0):
    return tgt.clone().index_add_(axis, idx, src)
def _segment_sum(src, seg, n):
    out = torch.zeros((n,) + src.shape[1:], dtype=src.dtype)
    return out.index_add_(0, seg, src)
def _pad(x, pw):
    flat = tuple(v for pair in reversed(pw) for v in pair)
    return torch.nn.functional.pad(x, flat)

kernel_name = 'standalone__molecular_angular_gemnet__graph'

def setup_inputs():

    _w = (lambda a: (lambda t: t.to(torch.bfloat16) if t.is_floating_point() else t)(torch.as_tensor(a)))
    N, deg, De, L = 12500, 64, 4, 1
    E = N * deg
    T = E * deg
    NR = 8
    dist = torch.rand(E).to(float)
    angle = (torch.rand(T) * torch.pi).to(float)
    centers = torch.linspace(0.0, 1.0, NR).to(float)
    ang_freq = torch.arange(1, L + 1).to(float)
    return {
        "m": _w((lambda *s: torch.randn(*s, dtype=torch.bfloat16) * 0.05)(E, De)),
        "idx_in": _w((lambda lo, hi, *s: torch.randint(lo, hi, s))(0, E, T).to(torch.int64)),
        "idx_out": _w((lambda lo, hi, *s: torch.randint(lo, hi, s))(0, E, T).to(torch.int64)),
        "dist": _w(dist),
        "angle": _w(angle),
        "centers": _w(centers),
        "ang_freq": _w(ang_freq),
        "w_rbf": _w((lambda *s: torch.randn(*s, dtype=torch.bfloat16) * 0.2)(NR, De)),
        "w_sbf": _w((lambda *s: torch.randn(*s, dtype=torch.bfloat16) * 0.2)(NR * L, De)),
        "w_down": _w((lambda *s: torch.randn(*s, dtype=torch.bfloat16) * 0.2)(De, De)),
        "w_up": _w((lambda *s: torch.randn(*s, dtype=torch.bfloat16) * 0.2)(De, De)),
    }

def reference(m, idx_in, idx_out, dist, angle, centers, ang_freq, w_rbf, w_sbf, w_down, w_up):
    E, De = m.shape[0], m.shape[1]
    NR = centers.shape[0]
    L = ang_freq.shape[0]
    rbf = torch.exp(-10.0 * (dist[:, None] - centers[None, :]) ** 2)
    cbf = torch.cos(ang_freq[None, :] * angle[:, None])
    rbf_t = rbf[idx_out]
    sbf = torch.reshape(rbf_t[:, :, None] * cbf[:, None, :], (-1, NR * L))
    x = (m[idx_in] @ w_down) * (sbf @ w_sbf)
    agg = _segment_sum(x, idx_out, E)
    return m + (agg @ w_up) * (rbf @ w_rbf)
```

```cpp
#include <cuda_runtime.h>
#include <cuda_bf16.h>
#include <stdint.h>

namespace {

constexpr int NB = 132, NG = 66;
constexpr int R2MAX = 6062, R1MAX = 12124;
constexpr int EMAX = NB * R2MAX;
constexpr int NTHR = 1024;
constexpr int NS1 = 8, NC = 11, J = 6;
#define TILES 15
constexpr int NPR = TILES * 64;
#define RING_DEPTH 3
constexpr int D = RING_DEPTH;
constexpr int NPAIR = 7, PAIR = 8192, SLOT = NPAIR * PAIR;
constexpr int WIN = 16896;
constexpr int NDUM = 16;
constexpr int PROW = 160;

constexpr int OFF_ACC0 = WIN, OFF_ACC1 = OFF_ACC0 + R2MAX * 4, OFF_BAR = OFF_ACC1 + R2MAX * 4;
constexpr int OFF_H1 = 0x10000 + WIN, OFF_M = OFF_H1 + WIN, OFF_WSM = OFF_M + R1MAX * 8;
constexpr int OFF_CNT1 = OFF_H1 + 0x20000 + WIN, OFF_CNT2 = OFF_CNT1 + (NG + NDUM + 2) * 4, OFF_MAP = OFF_CNT2 + (NB + NDUM) * 4;
constexpr int OFF_HIST = 0x30000;
constexpr int OFF_CADR = OFF_WSM + 128;
constexpr int SMEM_BYTES = OFF_MAP + NB * 8;
static_assert(SMEM_BYTES <= 232448 && OFF_BAR + 64 <= 0x10000 && OFF_CADR + 96 <= 0x30000, "smem");
static_assert(OFF_BAR % 8 == 0 && OFF_MAP % 8 == 0 && OFF_WSM % 16 == 0 && OFF_CNT2 % 16 == 0, "align");
static_assert(NC * J == NG && D == 3 && PROW % 32 == 0, "shape");

template <int HOP> struct H {
    static constexpr int S = HOP == 1 ? 32 : 16, NBIN = HOP == 1 ? NG : NB, CAP = HOP == 1 ? 48 : 32, PRE = HOP == 1 ? 16 : 4, SH = HOP == 1 ? 11 : 12;
    static constexpr int TB = HOP == 1 ? 20 : 28, CNT = HOP == 1 ? OFF_CNT1 : OFF_CNT2, STG = HOP == 1 ? OFF_H1 : 0;
    static constexpr uint32_t INC = (1u << SH) + 8u, PM = (S - 1) * 8;
    static __device__ __forceinline__ uint32_t init(int slot, uint32_t gen) { return 0x30000u | gen << TB | (slot == D - 1 ? (1u << TB) - (1u << 18) : 0u); }
    static __device__ __forceinline__ uint32_t win(int r) { return HOP == 1 ? (r & 1) << 17 : (0x310u >> (r % 3 * 4) & 3u) << 16; }
};

__device__ __align__(256) unsigned char g_ring[(size_t)(NB * D * NPAIR + 2) * PAIR];
__device__ __align__(128) uint2 g_pub[NB];
__device__ __align__(128) uint32_t g_first[2 * PROW];
__device__ __align__(128) uint32_t g_done[PROW];
constexpr int DROW = 192;
__device__ uint8_t g_dirty[NB * DROW];
__device__ uint32_t g_base = 2;
__device__ float4 g_ovf[EMAX];

struct Params {
    const uint2* m; const uint2* idx_in; const uint2* idx_out; const __nv_bfloat16* dist; const uint32_t* angle;
    const __nv_bfloat16* centers; const __nv_bfloat16* ang_freq; const __nv_bfloat16* w_rbf; const __nv_bfloat16* w_sbf;
    const __nv_bfloat16* w_down; const __nv_bfloat16* w_up; uint2* out; unsigned char* ring;
    int E, T, T2, R1, R2, rounds, lastn; uint32_t mg1, mg2, k1, k2, zero;
};

__device__ __forceinline__ float bf16r(float x) { return __bfloat162float(__float2bfloat16_rn(x)); }
__device__ __forceinline__ float bf_lo(uint32_t v) { return __uint_as_float(v << 16); }
__device__ __forceinline__ float bf_hi(uint32_t v) { return __uint_as_float(v & 0xffff0000u); }
__device__ __forceinline__ void red4(float4* a, float x, float y, float z, float w) {
    asm volatile("red.global.add.v4.f32 [%0], {%1,%2,%3,%4};" ::"l"(a), "f"(x), "f"(y), "f"(z), "f"(w) : "memory");
}
__device__ __forceinline__ void bar_sync(int id, int n) { __syncwarp(); asm volatile("bar.sync %0, %1;" ::"r"(id), "r"(n) : "memory"); }
__device__ __forceinline__ void bar_arrive(int id, int n) { __syncwarp(); asm volatile("bar.arrive %0, %1;" ::"r"(id), "r"(n) : "memory"); }
template <int OFF> __device__ __forceinline__ uint32_t atoms_add(uint32_t addr, uint32_t v) {
    uint32_t r; asm volatile("atom.shared.add.u32 %0, [%1+%3], %2;" : "=r"(r) : "r"(addr), "r"(v), "n"(OFF) : "memory"); return r;
}
__device__ __forceinline__ void sts64(uint32_t addr, uint32_t x, uint32_t y) {
    asm volatile("st.shared.v2.u32 [%0], {%1,%2};" ::"r"(addr), "r"(x), "r"(y) : "memory");
}
__device__ __forceinline__ void sts32(uint32_t addr, uint32_t x) { asm volatile("st.shared.u32 [%0], %1;" ::"r"(addr), "r"(x) : "memory"); }
template <int OFF = 0> __device__ __forceinline__ uint2 lds64(uint32_t addr) {
    uint2 v; asm volatile("ld.shared.v2.u32 {%0,%1}, [%2+%3];" : "=r"(v.x), "=r"(v.y) : "r"(addr), "n"(OFF) : "memory"); return v;
}
__device__ __forceinline__ uint32_t lds32(uint32_t addr) {
    uint32_t v; asm volatile("ld.shared.u32 %0, [%1];" : "=r"(v) : "r"(addr) : "memory"); return v;
}
__device__ __forceinline__ uint32_t ld_rlx32(const uint32_t* p) {
    uint32_t v; asm volatile("ld.relaxed.gpu.global.u32 %0, [%1];" : "=r"(v) : "l"(p) : "memory"); return v;
}
__device__ __forceinline__ uint2 ld_rlx64(const void* p) {
    uint2 v; asm volatile("ld.relaxed.gpu.global.v2.u32 {%0,%1}, [%2];" : "=r"(v.x), "=r"(v.y) : "l"(p) : "memory"); return v;
}
__device__ __forceinline__ float4 ld_rlx128f(const float4* p) {
    float4 v; asm volatile("ld.relaxed.gpu.global.v4.f32 {%0,%1,%2,%3}, [%4];" : "=f"(v.x), "=f"(v.y), "=f"(v.z), "=f"(v.w) : "l"(p) : "memory"); return v;
}
__device__ __forceinline__ void st_rlx32(uint32_t* p, uint32_t v) { asm volatile("st.relaxed.gpu.global.u32 [%0], %1;" ::"l"(p), "r"(v) : "memory"); }
__device__ __forceinline__ uint32_t hmul_bf2(uint32_t a, uint32_t b) {
    uint32_t r; asm("mul.rn.bf16x2 %0, %1, %2;" : "=r"(r) : "r"(a), "r"(b)); return r;
}
__device__ __forceinline__ uint32_t hsub_bf2(uint32_t a, uint32_t b) {
    uint32_t r; asm("sub.rn.bf16x2 %0, %1, %2;" : "=r"(r) : "r"(a), "r"(b)); return r;
}
constexpr int SPIN_LIMIT = 1 << 22;

__constant__ uint32_t c_inv2pi[8] = {0u, 0x28be60dbu, 0x9391054au, 0x7f09d5f4u, 0x7d4d3770u, 0x36d8a566u, 0x4f10e410u, 0x7f9458eau};
constexpr uint32_t BIGX = 0x4280u;
__device__ __forceinline__ float cos_big(uint32_t xb) {
    uint32_t e = (xb >> 7) & 0xffu, M = (xb & 0x7fu) | 0x80u;
    uint32_t pp = e - 102u;
    uint32_t wi = pp >> 5;
    uint32_t t0 = c_inv2pi[wi], t1 = c_inv2pi[wi + 1], t2 = c_inv2pi[wi + 2];
    uint32_t f = M * __funnelshift_l(t1, t0, pp) + __umulhi(M, __funnelshift_l(t2, t1, pp));
    float c = __cosf((float)(int)f * 1.4629180792671596e-9f);
    return e == 255u ? __uint_as_float(0x7fc00000u) : c;
}
__device__ __forceinline__ float cos_bf(uint32_t xb) {
    return (xb & 0x7fffu) > BIGX ? cos_big(xb) : __cosf(__uint_as_float(xb << 16));
}
__device__ __forceinline__ uint32_t pack_bf2(float lo, float hi) {
    uint32_t r; asm("cvt.rn.bf16x2.f32 %0, %1, %2;" : "=r"(r) : "f"(hi), "f"(lo)); return r;
}
template <int N> __device__ __forceinline__ uint32_t pick(int k, const uint32_t (&a)[N]) {
    uint32_t v = a[0];
#pragma unroll
    for (int i = 1; i < N; i++) if (k == i) v = a[i];
    return v;
}
template <int N> __device__ __forceinline__ uint2 pick(int k, const uint2 (&a)[N]) {
    uint2 v = a[0];
#pragma unroll
    for (int i = 1; i < N; i++) if (k == i) v = a[i];
    return v;
}
__device__ __forceinline__ void side_add(uint32_t bin, uint32_t row, int R2, float a, float b, float c, float d) {
    red4(&g_ovf[bin * R2 + row], a, b, c, d);
    g_dirty[bin * DROW + (row >> 5)] = 1;
}
__device__ __forceinline__ void slow_triplet(const Params& p, uint32_t ii, uint32_t oo, float c) {
    const uint2 v = __ldg(p.m + ii);
    const uint32_t bo = __umulhi(oo, p.mg2);
    side_add(bo, oo - bo * p.R2, p.R2, c * bf_lo(v.x), c * bf_hi(v.x), c * bf_lo(v.y), c * bf_hi(v.y));
}
__device__ __forceinline__ void slow_rec1(const Params& p, uint32_t x, uint32_t y, uint32_t bin) {
    const uint2 v = __ldg(p.m + bin * p.R1 + (y & 0xffffu));
    const float c = bf_hi(y);
    side_add(x & 0xffu, __byte_perm(x, 0u, 0x4413) >> 2, p.R2, c * bf_lo(v.x), c * bf_hi(v.x), c * bf_lo(v.y), c * bf_hi(v.y));
}
__device__ __forceinline__ uint32_t aux_of(uint32_t w0, uint32_t w1) {
    uint32_t u; asm("lop3.b32 %0, %1, %2, 0xf000f000, 0xe4;" : "=r"(u) : "r"(w0), "r"(w1 >> 4));
    return __byte_perm(u, 0u, 0x4413);
}
__device__ __forceinline__ void slow_rec2(const Params& p, uint32_t w0, uint32_t w1, uint32_t bin, float unit) {
    side_add(bin, aux_of(w0, w1) >> 2, p.R2, (float)((int)(w0 & 0xfffu) - 2048) * unit, (float)((int)(w0 >> 16 & 0xfffu) - 2048) * unit,
             (float)((int)(w1 & 0xfffu) - 2048) * unit, (float)((int)(w1 >> 16 & 0xfffu) - 2048) * unit);
}
template <uint32_t M> __device__ __forceinline__ uint32_t and_or(uint32_t a, uint32_t c) {
    uint32_t r; asm("lop3.b32 %0, %1, %2, %3, 0xea;" : "=r"(r) : "r"(a), "n"(M), "r"(c)); return r;
}
__device__ __forceinline__ uint32_t and_xor(uint32_t a, uint32_t m, uint32_t c) {
    uint32_t r; asm("lop3.b32 %0, %1, %2, %3, 0x6a;" : "=r"(r) : "r"(a), "r"(m), "r"(c)); return r;
}
__device__ __forceinline__ uint2 ld_in(const uint2* a) {
    uint2 v; asm volatile("ld.global.nc.L1::no_allocate.v2.u32 {%0,%1}, [%2];" : "=r"(v.x), "=r"(v.y) : "l"(a)); return v;
}
__device__ __forceinline__ uint32_t ld_in(const uint32_t* a) {
    uint32_t v; asm volatile("ld.global.nc.L1::no_allocate.u32 %0, [%1];" : "=r"(v) : "l"(a)); return v;
}
template <int OFF> __device__ __forceinline__ void put_rec(uint32_t ret, uint32_t lim, uint32_t addr, uint32_t x, uint32_t y) {
    asm volatile("{ .reg .pred q; setp.lt.u32 q, %0, %1; @q st.shared.v2.u32 [%2+%5], {%3,%4}; }" ::"r"(ret), "r"(lim), "r"(addr), "r"(x), "r"(y), "n"(OFF) : "memory");
}
__device__ __forceinline__ uint32_t mbar_try(uint32_t mb, uint32_t parity) {
    uint32_t ok;
    asm volatile("{ .reg .pred q; mbarrier.try_wait.parity.shared::cta.b64 q, [%1], %2; selp.u32 %0, 1, 0, q; }" : "=r"(ok) : "r"(mb), "r"(parity) : "memory");
    return ok;
}
__device__ __forceinline__ void mbar_wait(uint32_t mb, uint32_t parity) {
    if (!mbar_try(mb, parity)) {
        int it = 0;
        while (!mbar_try(mb, parity)) if (++it > SPIN_LIMIT) __trap();
    }
}
__device__ __forceinline__ void mbar_arrive(uint32_t mb) { asm volatile("mbarrier.arrive.shared::cta.b64 _, [%0];" ::"r"(mb) : "memory"); }
constexpr int B_FULL = OFF_BAR, B_OPEN = OFF_BAR + 16, B_FREE = OFF_BAR + 32, W_PROBE = OFF_BAR + 48, W_ROLE = OFF_BAR + 52, W_EXP = OFF_BAR + 56, W_UNIT = OFF_BAR + 60;
enum { BAR_PROBE = 1, BAR_ROLE, BAR_TABLE, BAR_DONE };

extern __shared__ __align__(1024) unsigned char smem[];
#define TK_DECL
#define TK(i)
#define TK_CNT(i)
#define TK_OUT
#define TK_ARG
#define TK_PASS

constexpr int NR = (R2MAX + NTHR - 1) / NTHR;
template <int U0, int NH>
__device__ __forceinline__ void gates(const Params& p, int i0, int row0, uint4 (&gh)[NR]) {
    uint32_t dd[NH];
    float g[NH][4], h[NH][4];
#pragma unroll
    for (int u = 0; u < NH; u++) {
        dd[u] = reinterpret_cast<const uint16_t*>(p.dist)[min(row0 + i0 + (U0 + u) * NTHR, p.E - 1)] * 0x10001u;
#pragma unroll
        for (int k = 0; k < 4; k++) { g[u][k] = 0.f; h[u][k] = 0.f; }
    }
#pragma unroll 1
    for (int r2 = 0; r2 < 4; r2++) {
        const uint32_t cen = __ldg(reinterpret_cast<const uint32_t*>(p.centers) + r2);
        const uint4 s4 = __ldg(reinterpret_cast<const uint4*>(p.w_sbf) + r2), r4 = __ldg(reinterpret_cast<const uint4*>(p.w_rbf) + r2);
        const uint32_t sw[4] = {s4.x, s4.y, s4.z, s4.w}, rw[4] = {r4.x, r4.y, r4.z, r4.w};
        uint32_t rb[NH];
#pragma unroll
        for (int u = 0; u < NH; u++) {
            const uint32_t df = hsub_bf2(dd[u], cen);
            const uint32_t ar = hmul_bf2(hmul_bf2(df, df), 0xc120c120u);
            rb[u] = pack_bf2(__expf(bf_lo(ar)), __expf(bf_hi(ar)));
        }
#pragma unroll
        for (int i = 0; i < 8; i++) {
            const float ws = i & 1 ? bf_hi(sw[i >> 1]) : bf_lo(sw[i >> 1]), wr = i & 1 ? bf_hi(rw[i >> 1]) : bf_lo(rw[i >> 1]);
#pragma unroll
            for (int u = 0; u < NH; u++) {
                const float x = i < 4 ? bf_lo(rb[u]) : bf_hi(rb[u]);
                g[u][i & 3] += x * ws;
                h[u][i & 3] += x * wr;
            }
        }
    }
#pragma unroll
    for (int u = 0; u < NH; u++)
        gh[U0 + u] = make_uint4(pack_bf2(g[u][0], g[u][1]), pack_bf2(g[u][2], g[u][3]), pack_bf2(h[u][0], h[u][1]), pack_bf2(h[u][2], h[u][3]));
}
__device__ __forceinline__ void epilogue(const Params& p, int tid, int role, uint32_t next_base, const uint4 (&gh)[NR]) {
    const int row0 = role * p.R2, nrows = min(p.R2, p.E - row0);
    uint2 mn = __ldg(p.m + min(row0 + tid, p.E - 1));
    bar_sync(0, NTHR);
    uint32_t dirty = 0;
#pragma unroll
    for (int it = 0; it < NR; it++) {
        uint32_t f;
        asm volatile("ld.relaxed.gpu.global.u8 %0, [%1];" : "=r"(f) : "l"(g_dirty + role * DROW + min((tid + it * NTHR) >> 5, DROW - 1)) : "memory");
        dirty |= (f ? 1u : 0u) << it;
    }
    if (tid == 0 && blockIdx.x == 0) g_base = next_base;
    const float unit = *reinterpret_cast<const float*>(smem + W_UNIT);
    const float4* w4 = reinterpret_cast<const float4*>(smem + OFF_WSM);
#pragma unroll
    for (int it = 0; it < NR; it++) {
        const int i = tid + it * NTHR;
        const uint2 mv = mn;
        mn = __ldg(p.m + min(row0 + i + NTHR, p.E - 1));
        asm volatile("" ::: "memory");
        if (i < nrows) {
            const int e = row0 + i;
            const uint32_t u0 = reinterpret_cast<const uint32_t*>(smem + OFF_ACC0)[i] + 0x40004000u, u1 = reinterpret_cast<const uint32_t*>(smem + OFF_ACC1)[i] + 0x40004000u;
            float a[4] = {(float)((int)(u0 & 0xffffu) - 0x8000) * unit, (float)((int)(u0 >> 16) - 0x8000) * unit,
                          (float)((int)(u1 & 0xffffu) - 0x8000) * unit, (float)((int)(u1 >> 16) - 0x8000) * unit};
            if (dirty >> it & 1) {
                const float4 o = ld_rlx128f(&g_ovf[e]);
                a[0] += o.x; a[1] += o.y; a[2] += o.z; a[3] += o.w;
                if (__float_as_uint(o.x) | __float_as_uint(o.y) | __float_as_uint(o.z) | __float_as_uint(o.w)) g_ovf[e] = make_float4(0.f, 0.f, 0.f, 0.f);
                if ((tid & 31) == 0) g_dirty[role * DROW + (i >> 5)] = 0;
            }
            float sd[4] = {0, 0, 0, 0}, uu[4] = {0, 0, 0, 0};
#pragma unroll
            for (int j = 0; j < 4; j++) {
                float4 w = w4[j];
                sd[0] += a[j] * w.x; sd[1] += a[j] * w.y; sd[2] += a[j] * w.z; sd[3] += a[j] * w.w;
            }
            const uint32_t a01 = pack_bf2(sd[0] * bf_lo(gh[it].x), sd[1] * bf_hi(gh[it].x)), a23 = pack_bf2(sd[2] * bf_lo(gh[it].y), sd[3] * bf_hi(gh[it].y));
            const float ag[4] = {bf_lo(a01), bf_hi(a01), bf_lo(a23), bf_hi(a23)};
#pragma unroll
            for (int j = 0; j < 4; j++) {
                float4 w = w4[4 + j];
                uu[0] += ag[j] * w.x; uu[1] += ag[j] * w.y; uu[2] += ag[j] * w.z; uu[3] += ag[j] * w.w;
            }
            const uint32_t t01 = hmul_bf2(pack_bf2(uu[0], uu[1]), gh[it].z);
            const uint32_t t23 = hmul_bf2(pack_bf2(uu[2], uu[3]), gh[it].w);
            uint2 o;
            asm("add.rn.bf16x2 %0, %1, %2;" : "=r"(o.x) : "r"(mv.x), "r"(t01));
            asm("add.rn.bf16x2 %0, %1, %2;" : "=r"(o.y) : "r"(mv.y), "r"(t23));
            p.out[e] = o;
        }
    }
}

template <int HOP> __device__ __forceinline__ uint32_t mailbox(uint32_t sb, int lead) {
    const uint2 mp = lds64(sb + OFF_MAP + lead * 8);
    return (mp.y * (D * NPAIR) + 6) * PAIR + (((mp.x >> 6 & 1u) ^ (lead >= NG)) << 12) + 1024 + HOP * 1024;
}
template <int HOP> __device__ __forceinline__ uint4 nulls(int lane) {
    const uint32_t i = lane & 7;
    if (HOP == 1) {
        const uint32_t x = NB + 2 * i, y = (OFF_CNT2 - OFF_M) / 8 + 2 * i;
        return make_uint4(x, y, x + 1, y + 1);
    }
    const uint32_t x = 0x08000800u | (i & 2u) << 28 | blockIdx.x << 30, y = 0x08000800u | i << 31;
    return make_uint4(x, y, x | 1u << 28, y | 1u << 30);
}
template <int OFF> __device__ __forceinline__ void sts128(uint32_t a, const uint4& v) {
    asm volatile("st.shared.v4.u32 [%0+%5], {%1,%2,%3,%4};" ::"r"(a), "r"(v.x), "r"(v.y), "r"(v.z), "r"(v.w), "n"(OFF) : "memory");
}
template <int HOP> struct Prefill {
    uint32_t a0, a1;
    __device__ __forceinline__ Prefill(int lane) {
        const uint32_t q = lane >> 3, i = lane & 7, b = q + (i & 4), c = (q & 1) + (q & 2) * 4 + (i & 6);
        a0 = HOP == 1 ? q * 256 + ((8 + q + i) & 15) * 16 : b * 128 + ((4 + b + (i & 3)) & 7) * 16;
        a1 = HOP == 1 ? q * 256 + 1024 + ((12 + q + i) & 15) * 16 : c * 128 + ((2 + c + (i & 1)) & 7) * 16;
    }
    __device__ __forceinline__ void run(uint32_t win, const uint4& v) const {
#pragma unroll 1
        for (uint32_t w = win; w < win + 16384; w += 8192) {
            sts128<0>(w + a0, v); sts128<2048>(w + a0, v); sts128<4096>(w + a0, v); sts128<6144>(w + a0, v);
            sts128<0>(w + a1, v); sts128<2048>(w + a1, v); sts128<4096>(w + a1, v); sts128<6144>(w + a1, v);
            if (HOP == 2) { sts128<1024>(w + a0, v); sts128<3072>(w + a0, v); sts128<5120>(w + a0, v); sts128<7168>(w + a0, v); }
        }
        if (a0 < 512) sts128<16384>(win + a0, v);
        if (HOP == 2 && a1 < 512) sts128<16384>(win + a1, v);
    }
};
__device__ __forceinline__ bool elect() {
    uint32_t q; asm volatile("{ .reg .pred q; elect.sync _|q, 0xffffffff; selp.u32 %0, 1, 0, q; }" : "=r"(q)); return q;
}
template <int HOP>
__device__ __forceinline__ void manager(const Params& p, uint32_t sb, int lane, int role, uint32_t base) {
    typedef H<HOP> h;
    constexpr int V = h::NBIN / 32, PB = h::S * 8;
    const int RT = p.rounds, grp = role >= NG;
    unsigned char* dst = p.ring + (uint32_t)(blockIdx.x * D * SLOT);
    uint32_t halves = __reduce_or_sync(0xffffffffu, lds64(sb + OFF_MAP + role * 8).x ^ (HOP == 1 && grp ? ~0u : 0u)) & ((1u << D * NPAIR) - 1u);
    const unsigned char* cr = p.ring + mailbox<HOP>(sb, HOP == 1 ? role / J * J : max(role / (2 * J) * (2 * J), grp * NG));
    const unsigned char* cr0 = cr + lane * V * 4, *cr1 = cr + (32 * V + min(lane, V - 1)) * 4;
    const uint32_t ca0 = sb + h::CNT + lane * V * 4, ca1 = sb + h::CNT + (32 * V + min(lane, V + NDUM - 1)) * 4;
    const uint32_t rot0 = (lane * V & 7) * 16, rot1 = lane < V ? lane * 16 : 0x80000000u;
    const Prefill<HOP> pf(lane);
    uint4 nul = nulls<HOP>(lane);
    int slot = 0;
    uint32_t init = h::init(0, 0), prim = sb + h::STG;
    uint32_t cs[5];
    auto sample = [&]() {
        if (V == 2) asm volatile("ld.relaxed.gpu.global.v2.u32 {%0,%1}, [%2];" : "=r"(cs[0]), "=r"(cs[1]) : "l"(cr0) : "memory");
        else asm volatile("ld.relaxed.gpu.global.v4.u32 {%0,%1,%2,%3}, [%4];" : "=r"(cs[0]), "=r"(cs[1]), "=r"(cs[2]), "=r"(cs[3]) : "l"(cr0) : "memory");
        cs[V] = ld_rlx32(reinterpret_cast<const uint32_t*>(cr1));
    };
    sample();
    uint32_t c[5];
    TK_DECL
#pragma unroll 1
    for (int r = 0; r < RT; r++) {
        const int nslot = slot == D - 1 ? 0 : slot + 1;
        const uint32_t ninit = h::init(nslot, (init + 0x10000u) >> h::TB & 1u);
        TK(5)
        mbar_wait(sb + B_FULL + (HOP - 1) * 8, r & 1);
        TK(0)
        if (V == 2) asm volatile("ld.shared.v2.u32 {%0,%1}, [%2];" : "=r"(c[0]), "=r"(c[1]) : "r"(ca0) : "memory");
        else asm volatile("ld.shared.v4.u32 {%0,%1,%2,%3}, [%4];" : "=r"(c[0]), "=r"(c[1]), "=r"(c[2]), "=r"(c[3]) : "r"(ca0) : "memory");
        c[V] = lds32(ca1);
        uint32_t nc[5], lo = c[V];
#pragma unroll
        for (int k = 0; k <= V; k++) {
            const uint32_t z = ninit + (k < V ? rot0 + k * 16 : rot1);
            nc[k] = min(max(c[k] + (ninit - init - h::S * h::INC), z), z + (h::CAP - h::S) * h::INC);
            lo = min(lo, c[k]);
        }
        if (V == 2) sts64(ca0, nc[0], nc[1]); else sts128<0>(ca0, make_uint4(nc[0], nc[1], nc[2], nc[3]));
        sts32(ca1, nc[V]);
        __syncwarp();
        if (lane == 0) mbar_arrive(sb + B_OPEN + (HOP - 1) * 8);
        TK(1)
        if (lo < init + (h::PRE << h::SH)) {
            const uint32_t gb = init & 1u << h::TB, vx = HOP == 1 ? NB | gb : 0x08000800u, vy = HOP == 1 ? nul.y : 0x08000800u | gb;
#pragma unroll 1
            for (int k = 0; k <= V; k++) {
                const uint32_t bin = k < V ? lane * V + k : 32 * V + lane;
#pragma unroll 1
                for (uint32_t x = pick(k, c); x < init + (h::PRE << h::SH); x += h::INC) sts64(prim + bin * PB + (x & h::PM), vx, vy);
            }
        }
        __syncwarp();
        TK(2)
        asm volatile("fence.proxy.async.shared::cta;" ::: "memory");
        TK(6)
        if (r >= D) {
            int it = 0;
            while (true) {
                uint32_t bad = 0;
#pragma unroll
                for (int k = 0; k <= V; k++) bad |= cs[k] - (base + r - D + 1);
                if (!__any_sync(0xffffffffu, bad >> 20)) break;
                if (++it > SPIN_LIMIT) __trap();
                if (it > 1) __nanosleep(100);
                sample();
            }
        }
        TK(3)
        if (elect()) {
#pragma unroll
            for (int i = 0; i < (HOP == 1 ? 5 : 6); i++) {
                const int k = HOP == 1 ? i : i % 3, pg = HOP == 1 ? 0 : i / 3, pair = HOP == 1 ? (k < 4 ? k : 6) : 4 + k;
                const uint32_t o = (((pg ? ~halves : halves) << (12 - pair)) & 4096u) | (pair * PAIR + (HOP == 1 && pair == 6 ? 1024 : 0));
                asm volatile("cp.async.bulk.global.shared::cta.bulk_group [%0], [%1], %2;"
                             ::"l"(dst + o), "r"(prim + pg * NG * PB + k * 4096), "r"(pair < 6 ? 4096 : 2 * PB) : "memory");
            }
            asm volatile("cp.async.bulk.commit_group;" ::: "memory");
            if (r < D) {
                asm volatile("cp.async.bulk.wait_group 0;" ::: "memory");
                __threadfence();
                st_rlx32(g_first + (HOP - 1) * PROW + blockIdx.x, base + r + 1);
            } else asm volatile("cp.async.bulk.wait_group.read 0;" ::: "memory");
            if (HOP == 1) mbar_arrive(sb + B_FREE);
        }
        __syncwarp();
        TK(4)
        sample();
        if (slot == (HOP == 1 ? 1 : 0)) {
            if (HOP == 1) { nul.x ^= 1u << h::TB; nul.z ^= 1u << h::TB; }
            else { nul.y ^= 1u << h::TB; nul.w ^= 1u << h::TB; }
        }
        pf.run(prim, nul);
        dst += slot == D - 1 ? -(D - 1) * SLOT : SLOT;
        halves = (halves >> NPAIR | halves << (D - 1) * NPAIR) & ((1u << D * NPAIR) - 1u);
        prim = HOP == 1 ? prim ^ 0x20000u : sb + ((0x310u >> (nslot * 4) & 3u) << 16);
        slot = nslot;
        if (r < RT - 1) init = ninit;
    }
#pragma unroll 1
    for (int k = 0; k <= V; k++) {
        const uint32_t bin = k < V ? lane * V + k : 32 * V + lane, n = bin < h::NBIN ? min((pick(k, c) - init) >> h::SH, (uint32_t)h::CAP) : 0u;
#pragma unroll 1
        for (uint32_t x = h::S; x < n; x++) {
            const uint2 w = lds64(prim + bin * PB + ((x + (bin & 7) * 2) & (h::S - 1)) * 8);
            if (HOP == 1) slow_rec1(p, w.x, w.y, bin);
            else slow_rec2(p, w.x, w.y, bin, __uint_as_float(lds32(sb + W_UNIT)));
        }
    }
    asm volatile("cp.async.bulk.wait_group 0;" ::: "memory");
    TK_OUT
}

#define POLL_NS 200
template <int HOP> struct Reader {
    uint32_t cur[J];
    uint32_t st;
    uint32_t want;
    __device__ __forceinline__ bool wrap() const { return st & 0x80u; }
    static __device__ __forceinline__ int source(int w, int j, int lane, int role) { return HOP == 1 ? (role >= NG ? NG : 0) + w * J + j : (w * J + j) * 2 + (lane >> 4); }
    __device__ __forceinline__ void init(const Params& p, uint32_t sb, int w, int lane, int role) {
        const int grp = role >= NG, l = role - grp * NG;
        const int pair = HOP == 1 ? (l < 64 ? l >> 4 : 6) : 4 + (l >> 5);
        const uint32_t in = HOP == 1 ? (l & 15) * 256 + (l < 64 ? 0 : 1024) + lane * 8 : (l & 31) * 128 + (lane & 15) * 8;
        st = 0xc04000u;
        if (lane == 0) sts32(sb + OFF_CADR + ((HOP - 1) * NC + w) * 4, mailbox<HOP>(sb, source(w, 0, 0, role)) + (HOP == 1 ? l : role) * 4);
        if (HOP == 2 && w == NC / 2 && lane == 0) sts32(sb + OFF_CADR + 2 * NC * 4, mailbox<HOP>(sb, NG) + role * 4);
        __syncwarp();
#pragma unroll
        for (int j = 0; j < J; j++) {
            const uint2 mp = lds64(sb + OFF_MAP + source(w, j, lane, role) * 8);
            const uint32_t hv = mp.x >> pair;
            cur[j] = (mp.y * (D * NPAIR) + pair) * PAIR + in + (((hv & 1u) ^ grp) << 12);
#pragma unroll
            for (int s = 0; s < D; s++) st |= ((hv >> (s * NPAIR) ^ hv >> ((s + 1) % D * NPAIR)) & 1u) << (s * 8 + j);
        }
        want = 0;
    }
    __device__ __forceinline__ void first(uint32_t need) const {
#pragma unroll 1
        for (int j = 0; j < J; j++) {
            const uint32_t* f = g_first + (HOP - 1) * PROW + pick(j, cur) / (D * SLOT);
            int it = 0;
            while ((int)(ld_rlx32(f) - need) < 0) { __nanosleep(100); if (++it > SPIN_LIMIT) __trap(); }
        }
        __syncwarp();
        __threadfence();
    }
    __device__ __forceinline__ void load(const Params& p, uint2 (&rec)[J]) const {
#pragma unroll
        for (int j = 0; j < J; j++) rec[j] = ld_rlx64(p.ring + cur[j]);
    }
    __device__ __forceinline__ void check(const Params& p, uint32_t sb, uint2 (&rec)[J], uint32_t done TK_ARG) const {
        constexpr uint32_t BIT = 1u << H<HOP>::TB;
        int it = 0;
        uint32_t bad;
        while (true) {
            bad = 0;
#pragma unroll
            for (int j = 0; j < J; j++) bad |= (HOP == 1 ? rec[j].x : rec[j].y) ^ want;
            if (!__any_sync(0xffffffffu, bad & BIT)) break;
            if (++it > SPIN_LIMIT) __trap();
            __nanosleep(POLL_NS);
            TK_CNT(7)
#pragma unroll
            for (int j = 0; j < J; j++)
                asm volatile("{ .reg .pred q; .reg .u32 t; .reg .u64 a; xor.b32 t, %5, %4; and.b32 t, t, %6; setp.ne.u32 q, t, 0;\n"
                             "cvt.u64.u32 a, %3; add.u64 a, a, %2; @q ld.relaxed.gpu.global.v2.u32 {%0,%1}, [a]; }"
                             : "+r"(rec[j].x), "+r"(rec[j].y) : "l"(p.ring), "r"(cur[j]), "r"(want), "r"(HOP == 1 ? rec[j].x : rec[j].y), "n"(BIT) : "memory");
        }
        uint32_t t;
        asm volatile("mov.u32 %0, %%tid.x;" : "=r"(t));
        const bool extra = HOP == 2 && t == (NS1 + NC + 1 + NC / 2) * 32 + 1;
        if ((t & 31u) == 0 || extra)
            st_rlx32(reinterpret_cast<uint32_t*>(p.ring + lds32(sb + OFF_CADR + (extra ? 2 * NC * 4 : (t >> 3) - (NS1 + HOP - 1) * 4))), done);
    }
    __device__ __forceinline__ void advance() {
        const uint32_t ds = wrap() ? -(D - 1) * SLOT : SLOT;
#pragma unroll
        for (int j = 0; j < J; j++) cur[j] = (cur[j] ^ (st << (12 - j) & 4096u)) + ds;
        want ^= (st & 0x80u) << (H<HOP>::TB - 7);
        st = __byte_perm(st, 0u, 0x3021);
    }
};

#define NPROBE 7
__device__ __forceinline__ uint32_t near_half(unsigned char* pair, uint32_t zero) {
#pragma unroll
    for (int i = 0; i < 4; i++) *reinterpret_cast<uint4*>(pair + (i >> 1) * 4096 + (i & 1) * 16) = make_uint4(0u, 0u, 0u, 0u);
    uint32_t best[2] = {~0u, ~0u}, v = 0, prev = 0;
#pragma unroll
    for (int t = 0; t <= NPROBE; t++) {
        uint32_t now;
        asm volatile("atom.relaxed.gpu.global.add.u32 %0, [%1], 1;" : "=r"(v) : "l"(pair + (t & 1) * 4096 + (v & zero)) : "memory");
        asm volatile("mov.u32 %0, %%clock;" : "=r"(now) :: "memory");
        if (t > 1) best[(t - 1) & 1] = min(best[(t - 1) & 1], now - prev);
        prev = now;
    }
    return (best[1] < best[0] ? 1u : 0u) | (v & zero);
}
template <bool B> struct BoolC { static constexpr bool value = B; };

template <int NP>
__device__ __forceinline__ void stage1(const Params& p, uint32_t sb, const int pos0, int lane) {
    typedef H<1> h;
    const int RT = p.rounds;
    const uint32_t ff = *reinterpret_cast<const uint16_t*>(p.ang_freq) * 0x10001u;
    auto pair_of = [&](int r, int pos) {
        const int q = r < RT - 1 ? (r * NB + blockIdx.x) * NPR + pos : (RT - 1) * NB * NPR + blockIdx.x * p.lastn + pos;
        return (r < RT - 1 || (r == RT - 1 && pos < p.lastn)) && q < p.T2 ? q : -1;
    };
    uint2 vi[NP], vo[NP]; uint32_t va[NP];
    auto load_edge = [&](int r) {
#pragma unroll
        for (int u = 0; u < NP; u++) {
            const int q = max(pair_of(r, pos0 + u * 32), 0);
            vi[u] = ld_in(p.idx_in + q); vo[u] = ld_in(p.idx_out + q); va[u] = ld_in(p.angle + q);
        }
    };
    load_edge(0);
    if (blockIdx.x == 0 && pos0 == 0 && (p.T & 1)) {
        const int t = p.T - 1;
        slow_triplet(p, reinterpret_cast<const uint32_t*>(p.idx_in)[t], reinterpret_cast<const uint32_t*>(p.idx_out)[t],
                     bf16r(cos_bf(hmul_bf2(reinterpret_cast<const uint16_t*>(p.angle)[t], ff) & 0xffffu)));
    }
    uint32_t init = h::init(0, 0);
    int slot = 0;
    TK_DECL
    auto step = [&](const int r, auto edge) {
        constexpr bool EDGE = decltype(edge)::value;
        uint32_t cc[NP], big = 0;
#pragma unroll
        for (int u = 0; u < NP; u++) {
            va[u] = hmul_bf2(va[u], ff);
            cc[u] = pack_bf2(__cosf(bf_lo(va[u])), __cosf(bf_hi(va[u])));
            big = __vmaxu2(big, va[u] & 0x7fff7fffu);
        }
        if ((big + (0x7fffu - BIGX) * 0x10001u) & 0x80008000u) {
#pragma unroll 1
            for (int u = 0; u < NP; u++) {
                const uint32_t a = pick(u, va);
                float c0 = cos_bf(a & 0xffffu), c1 = cos_bf(a >> 16);
                if ((c0 != c0 || c1 != c1) && (!EDGE || pair_of(r, pos0 + u * 32) >= 0)) {
                    const uint2 i2 = pick(u, vi), o2 = pick(u, vo);
                    if (c0 != c0) slow_triplet(p, i2.x, o2.x, c0);
                    if (c1 != c1) slow_triplet(p, i2.y, o2.y, c1);
                }
                const uint32_t v = pack_bf2(c0 != c0 ? 0.f : c0, c1 != c1 ? 0.f : c1);
#pragma unroll
                for (int k = 0; k < NP; k++) if (k == u) cc[k] = v;
            }
        }
        uint32_t bin[2 * NP], x[2 * NP], y[2 * NP];
#pragma unroll
        for (int j = 0; j < 2 * NP; j++) {
            const uint32_t ii = j & 1 ? vi[j >> 1].y : vi[j >> 1].x, oo = j & 1 ? vo[j >> 1].y : vo[j >> 1].x;
            bin[j] = __umulhi(ii, p.mg1);
            y[j] = __byte_perm(bin[j] * p.k1 + ii, cc[j >> 1], j & 1 ? 0x7610 : 0x5410);
            const uint32_t bo = __umulhi(oo, p.mg2);
            x[j] = __byte_perm(bo * p.k2 + oo * 4u, bo, 0x0514);
            if (EDGE && pair_of(r, pos0 + (j >> 1) * 32) < 0) bin[j] = NG + (lane & (NDUM - 1));
        }
        if (EDGE) load_edge(r + 1);
        else {
            uint32_t dep = 0;
#pragma unroll
            for (int j = 0; j < 2 * NP; j++) dep |= x[j] | y[j];
            const int q = ((r + 1) * NB + blockIdx.x) * NPR + pos0 + (dep & p.zero);
#pragma unroll
            for (int u = 0; u < NP; u++) { vi[u] = ld_in(p.idx_in + q + u * 32); vo[u] = ld_in(p.idx_out + q + u * 32); va[u] = ld_in(p.angle + q + u * 32); }
        }
        const uint32_t kb = sb + h::win(r + 1), lim = init + (h::CAP << h::SH);
        TK(0)
        mbar_wait(sb + B_OPEN, (r - 1) & 1);
        TK(1)
        bool freed = false;
        uint32_t over = 0;
#pragma unroll
        for (int g = 0; g < 2 * NP; g += 4) {
            uint32_t ret[4];
#pragma unroll
            for (int j = 0; j < 4; j++) ret[j] = atoms_add<h::CNT>(sb + bin[g + j] * 4, h::INC);
            const int mx = max(max((int)ret[0], (int)ret[1]), max((int)ret[2], (int)ret[3]));
            if (!freed && __any_sync(0xffffffffu, mx >= (int)(init + 0x10000u))) { TK(2) mbar_wait(sb + B_FREE, (r - 1) & 1); freed = true; TK(3) }
            TK(2)
#pragma unroll
            for (int j = 0; j < 4; j++) {
                x[g + j] = and_or<1u << h::TB>(ret[j], x[g + j]);
                put_rec<h::STG>(ret[j], lim, and_xor(ret[j], 0x20000u | h::PM, bin[g + j] * 256 + kb), x[g + j], y[g + j]);
            }
            if (mx >= (int)lim) {
#pragma unroll
                for (int j = 0; j < 4; j++) if ((int)ret[j] >= (int)lim) over |= 1u << (g + j);
            }
        }
        __syncwarp();
        if (lane == 0) mbar_arrive(sb + B_FULL);
        TK(4)
#pragma unroll 1
        while (over) {
            TK_CNT(7)
            const int j = __ffs(over) - 1;
            over &= over - 1;
            slow_rec1(p, pick(j, x), pick(j, y), pick(j, bin));
        }
        slot = slot == D - 1 ? 0 : slot + 1;
        init = h::init(slot, (init + 0x10000u) >> h::TB & 1u);
    };
    int r = 0;
    const int nfast = p.T2 / (NB * NPR) - 1;
#pragma unroll 1
    for (; r < nfast; r++) step(r, BoolC<false>());
#pragma unroll 1
    for (; r < RT; r++) step(r, BoolC<true>());
    TK_OUT
}

__device__ __forceinline__ void stage2(const Params& p, uint32_t sb, int w, int lane, int role, uint32_t base) {
    typedef H<2> h;
    const int RT = p.rounds;
    Reader<1> rd;
    rd.init(p, sb, w, lane, role);
    uint2 rec[J];
    rd.first(base + 1);
    rd.load(p, rec);
    bar_sync(BAR_TABLE, (2 * NC + 1) * 32);
    TK_DECL
#pragma unroll 1
    for (int r = 0; r < RT; r++) {
        rd.check(p, sb, rec, base + r + 1 TK_PASS);
        TK(0)
        uint2 mv[J];
#pragma unroll
        for (int j = 0; j < J; j++) mv[j] = lds64<OFF_M>(sb + (rec[j].y & 0xffffu) * 8);
        uint32_t fl = 0;
#pragma unroll
        for (int j = 0; j < J; j++) fl |= mv[j].y;
        if (fl & 0x40000000u) {
#pragma unroll 1
            for (int j = 0; j < J; j++) {
                const uint2 v = pick(j, mv), w = pick(j, rec);
                if ((v.y & 0x40000000u) && (w.x & 0xffu) < NB) {
                    if (v.x & 0x40000000u) slow_rec1(p, w.x, w.y, lds32(sb + W_ROLE) % NG);
                    else {
                        const float c = bf_hi(w.y), s = __uint_as_float(lds32(sb + W_UNIT)) * 1024.f;
                        side_add(w.x & 0xffu, __byte_perm(w.x, 0u, 0x4413) >> 2, p.R2, c * (bf_lo(v.x) * s), c * (bf_hi(v.x) * s),
                                 c * (bf_lo(v.y) * s), c * (bf_hi(v.y & 0xbfffffffu) * s));
                    }
                }
            }
#pragma unroll
            for (int j = 0; j < J; j++) if (mv[j].y & 0x40000000u) rec[j].x = NB;
        }
        uint32_t w0[J], w1[J], bin[J], ret[J];
#pragma unroll
        for (int j = 0; j < J; j++) {
            const float c = bf_hi(rec[j].y), MG = 8194.0f;
            const uint32_t x = rec[j].x;
            w0[j] = and_or<0xf000f000u>(x, __byte_perm(__float_as_uint(fmaf(c, bf_lo(mv[j].x), MG)), __float_as_uint(fmaf(c, bf_hi(mv[j].x), MG)), 0x5410));
            w1[j] = and_or<0xf000f000u>(x << 4, __byte_perm(__float_as_uint(fmaf(c, bf_lo(mv[j].y), MG)), __float_as_uint(fmaf(c, bf_hi(mv[j].y), MG)), 0x5410));
            bin[j] = x & 0xffu;
        }
        const uint32_t lim = h::init(rd.wrap() ? D - 1 : 0, rd.want >> H<1>::TB) + 0x20000u;
        rd.advance();
        if (r + 1 < D) rd.first(base + r + 2);
        rd.load(p, rec);
        TK(1)
        mbar_wait(sb + B_OPEN + 8, (r - 1) & 1);
        TK(2)
#pragma unroll
        for (int j = 0; j < J; j++) ret[j] = atoms_add<h::CNT>(sb + bin[j] * 4, h::INC);
        const uint32_t am = and_or<0x30000u>(rd.st << 10 ^ rd.st >> 6, h::PM), kb = and_or<0x30000u>(rd.st << 10, sb);
        int mx = -1;
#pragma unroll
        for (int j = 0; j < J; j++) {
            w1[j] = and_or<1u << h::TB>(ret[j], w1[j]);
            put_rec<0>(ret[j], lim, and_xor(ret[j], am, bin[j] * 128 + kb), w0[j], w1[j]);
            mx = max(mx, (int)ret[j]);
        }
        __syncwarp();
        if (lane == 0) mbar_arrive(sb + B_FULL + 8);
        TK(3)
        if (mx >= (int)lim) {
#pragma unroll 1
            for (int j = 0; j < J; j++)
                if ((int)pick(j, ret) >= (int)lim) slow_rec2(p, pick(j, w0), pick(j, w1), pick(j, bin), __uint_as_float(lds32(sb + W_UNIT)));
        }
        __syncwarp();
        TK(4)
    }
    TK_OUT
}

__device__ __forceinline__ float2 acc_fix(uint32_t old, uint32_t q) {
    const uint32_t u = old + 0x40004000u, n = u + q - 0x08000800u;
    return make_float2((float)((int)(u & 0xffffu) + (int)(q & 0xffffu) - 2048 - (int)(n & 0xffffu)), (float)((int)(u >> 16) + (int)(q >> 16) - 2048 - (int)(n >> 16)));
}
__device__ __forceinline__ void stage3(const Params& p, uint32_t sb, int w, int lane, int role, uint32_t base) {
    const int RT = p.rounds;
    Reader<2> rd;
    rd.init(p, sb, w, lane, role);
    uint2 rec[J];
    rd.first(base + 1);
    rd.load(p, rec);
    TK_DECL
#pragma unroll 1
    for (int r = 0; r < RT; r++) {
        rd.check(p, sb, rec, base + r + 1 TK_PASS);
        TK(0)
        uint32_t o0[J], o1[J];
        const uint32_t ab = sb - (rd.want >> H<2>::TB);
#pragma unroll
        for (int j = 0; j < J; j++) {
            const uint32_t ad = ab + aux_of(rec[j].x, rec[j].y);
            o0[j] = atoms_add<OFF_ACC0>(ad, (rec[j].x & 0x0fff0fffu) - 0x08000800u);
            o1[j] = atoms_add<OFF_ACC1>(ad, (rec[j].y & 0x0fff0fffu) - 0x08000800u);
        }
        rd.advance();
        uint32_t g = 0;
#pragma unroll
        for (int j = 0; j < J; j++) g |= o0[j] | o1[j];
        if (g & 0x80008000u) {
#pragma unroll 1
            for (int j = 0; j < J; j++) {
                const uint2 w = pick(j, rec);
                const float2 a = acc_fix(pick(j, o0), w.x & 0x0fff0fffu), b = acc_fix(pick(j, o1), w.y & 0x0fff0fffu);
                const float unit = __uint_as_float(lds32(sb + W_UNIT));
                if (a.x != 0.f || a.y != 0.f || b.x != 0.f || b.y != 0.f)
                    side_add(lds32(sb + W_ROLE), aux_of(w.x, w.y) >> 2, p.R2, a.x * unit, a.y * unit, b.x * unit, b.y * unit);
            }
        }
        if (r + 1 < D) rd.first(base + r + 2);
        rd.load(p, rec);
        TK(1)
    }
    TK_OUT
}

__device__ __forceinline__ uint32_t row_max(uint32_t x, uint32_t y) {
    const uint32_t mx = __vmaxu2(x & 0x7fff7fffu, y & 0x7fff7fffu);
    return max(mx & 0xffffu, mx >> 16);
}
constexpr int EWIN = 5;

__global__ void __launch_bounds__(NTHR, 1) fused_kernel(const Params p) {
    const int tid = threadIdx.x, lane = tid & 31;
    const int hw = __reduce_max_sync(0xffffffffu, tid >> 5);
    const uint32_t sb = __reduce_or_sync(0xffffffffu, (uint32_t)__cvta_generic_to_shared(smem));
    const uint32_t base = __reduce_or_sync(0xffffffffu, ld_rlx32(&g_base));
    if (tid < NB + NDUM) sts32(sb + OFF_CNT2 + tid * 4, H<2>::init(0, 0) + (tid < NB ? (tid & 7) * 16 : 0x80000000u));
    else if (tid >= 160 && tid < 160 + NG + NDUM) sts32(sb + OFF_CNT1 + (tid - 160) * 4, H<1>::init(0, 0) + (tid < 160 + NG ? (tid & 7) * 16 : 0x80000000u));
    else if (tid >= 256 && tid < 512) sts32(sb + OFF_HIST + (tid - 256) * 4, 0u);
    else if (tid >= 512 && tid < 544) reinterpret_cast<float*>(smem + OFF_WSM)[tid - 512] = __bfloat162float(tid < 528 ? p.w_down[tid - 512] : p.w_up[tid - 528]);
    else if (tid == 544) {
        if (sb & 255u) __trap();
        asm volatile("mbarrier.init.shared::cta.b64 [%0], %1;" ::"r"(sb + B_FULL), "n"(NS1) : "memory");
        asm volatile("mbarrier.init.shared::cta.b64 [%0], %1;" ::"r"(sb + B_FULL + 8), "n"(NC) : "memory");
        for (int i = 0; i < 3; i++) asm volatile("mbarrier.init.shared::cta.b64 [%0], 1;" ::"r"(sb + B_OPEN + i * 8) : "memory");
        sts32(sb + W_PROBE, 0u);
    } else if (tid >= 576 && (tid - 576) * 16 < p.R2 && (blockIdx.x * p.R2 + (tid - 576) * 16) < p.E)
        asm volatile("prefetch.global.L2 [%0];" ::"l"(p.m + blockIdx.x * p.R2 + (tid - 576) * 16));
    if (hw >= 30) Prefill<1>(lane).run(sb + OFF_H1 + H<1>::win(hw), nulls<1>(lane));
    __syncthreads();

    constexpr int W_M1 = NS1 + NC, W_M2 = 31;
    if (hw < NS1) {
        if (hw < NS1 - 1) stage1<4>(p, sb, hw * 128 + lane, lane);
        else stage1<NPR / 32 - (NS1 - 1) * 4>(p, sb, hw * 128 + lane, lane);
        __threadfence();
        bar_arrive(BAR_DONE, (NS1 + NC + 2) * 32);
    } else if (hw == W_M1) {
        bar_sync(BAR_PROBE, (2 * NC + 1) * 32);
        {
            const uint32_t raw = lds32(sb + W_PROBE), side = raw >> (D * NPAIR);
            if (lane == 0) asm volatile("st.relaxed.gpu.global.v2.u32 [%0], {%1,%2};" ::"l"(g_pub + blockIdx.x), "r"(base), "r"(side ? ~raw | 0x80000000u : raw) : "memory");
            uint32_t best = 0;
#pragma unroll 1
            for (int e = 11 + lane; e <= 230; e += 32) {
                uint32_t c = 0;
#pragma unroll
                for (int i = 0; i < EWIN; i++) c += lds32(sb + OFF_HIST + (e - i) * 4);
                best = max(best, c << 8 | (255 - e));
            }
            const uint32_t e = 255 - (__reduce_max_sync(0xffffffffu, best) & 255u);
            if (lane == 0) { sts32(sb + W_EXP, e); sts32(sb + W_UNIT, (e - 10) << 23); }
            uint2 pb[5];
            int it = 0;
            while (true) {
                bool ok = true;
#pragma unroll
                for (int j = 0; j < 5; j++) { pb[j] = ld_rlx64(g_pub + min(lane + 32 * j, NB - 1)); ok = ok && pb[j].x == base; }
                if (__all_sync(0xffffffffu, ok)) break;
                __nanosleep(100);
                if (++it > SPIN_LIMIT) __trap();
            }
            uint32_t bal[5], n1 = 0;
#pragma unroll
            for (int j = 0; j < 5; j++) { bal[j] = __ballot_sync(0xffffffffu, lane + 32 * j < NB && (int)pb[j].y < 0); n1 += __popc(bal[j]); }
            uint32_t before = 0;
#pragma unroll
            for (int j = 0; j < 5; j++) {
                const uint32_t b = lane + 32 * j, k = before + __popc(bal[j] & ((1u << lane) - 1u)), ro = (int)pb[j].y < 0 ? NB - n1 + k : b - k;
                if (b < NB) sts64(sb + OFF_MAP + ro * 8, pb[j].y, b);
                if (b == blockIdx.x) sts32(sb + W_ROLE, ro);
                before += __popc(bal[j]);
            }
        }
        bar_sync(BAR_ROLE, (2 * NC + 2) * 32);
        manager<1>(p, sb, lane, __reduce_max_sync(0xffffffffu, lds32(sb + W_ROLE)), base);
        __threadfence();
        bar_arrive(BAR_DONE, (NS1 + NC + 2) * 32);
    } else if (hw == W_M2) {
        bar_sync(BAR_ROLE, (2 * NC + 2) * 32);
#pragma unroll 1
        for (int i = 0; i < 3; i++) Prefill<2>(lane).run(sb + H<2>::win(i), nulls<2>(lane));
        bar_arrive(BAR_TABLE, (2 * NC + 1) * 32);
        manager<2>(p, sb, lane, __reduce_max_sync(0xffffffffu, lds32(sb + W_ROLE)), base);
        __threadfence();
        bar_sync(BAR_DONE, (NS1 + NC + 2) * 32);
        if (lane == 0) { __threadfence(); st_rlx32(g_done + blockIdx.x, base); }
    } else {
        const int pw = __reduce_max_sync(0xffffffffu, hw < W_M1 ? hw - NS1 : hw - NS1 - 1), ct = pw * 32 + lane;
        constexpr int CT = 2 * NC * 32;
        uint2 sm3[3];
#pragma unroll
        for (int u = 0; u < 3; u++) sm3[u] = __ldg(p.m + (uint32_t)(ct * 3 + u) * (uint32_t)p.E / (3 * CT));
        if (lane == 0) {
#pragma unroll 1
            for (int i = pw; i <= D * NPAIR; i += 2 * NC) {
                const uint32_t v = near_half(p.ring + (uint32_t)(i < D * NPAIR ? (blockIdx.x * D * NPAIR + i) * PAIR : NB * D * NPAIR * PAIR + (blockIdx.x & 127) * 32), p.zero);
                asm volatile("red.shared.or.b32 [%0], %1;" ::"r"(sb + W_PROBE), "r"(v << i) : "memory");
            }
        }
        __syncwarp();
#pragma unroll
        for (int u = 0; u < 3; u++) {
            const uint32_t mx = row_max(sm3[u].x, sm3[u].y);
            if (mx) atoms_add<OFF_HIST>(sb + (mx >> 7) * 4, 1u);
        }
        bar_arrive(BAR_PROBE, (2 * NC + 1) * 32);
        for (int i = ct; i < R2MAX / 2; i += CT) reinterpret_cast<uint4*>(smem + OFF_ACC0)[i] = make_uint4(0x40004000u, 0x40004000u, 0x40004000u, 0x40004000u);
        bar_sync(BAR_ROLE, (2 * NC + 2) * 32);
        const int role = __reduce_max_sync(0xffffffffu, lds32(sb + W_ROLE));
        {
            const int e = lds32(sb + W_EXP), r0 = (role >= NG ? role - NG : role) * p.R1, nr = min(p.R1, p.E - r0);
            const uint32_t sc = (uint32_t)(254 - e) * 0x800080u;
            constexpr int CH = 9;
#pragma unroll 1
            for (int i0 = ct; i0 < R1MAX; i0 += CH * CT) {
                uint2 v[CH];
#pragma unroll
                for (int u = 0; u < CH; u++) v[u] = __ldg(p.m + min(r0 + i0 + u * CT, p.E - 1));
#pragma unroll
                for (int u = 0; u < CH; u++) {
                    const int i = i0 + u * CT;
                    const uint32_t mx = i < nr ? row_max(v[u].x, v[u].y) : 0u;
                    const int d = e - (int)(mx >> 7);
                    uint32_t x = hmul_bf2(v[u].x, sc), y = hmul_bf2(v[u].y, sc);
                    if (d >= EWIN) y |= 0x40000000u;
                    if (d < 0 || (d >= EWIN && e > 127)) { x = 0x40000000u; y = x; }
                    if (mx == 0) { x = 0; y = 0; }
                    if (i < R1MAX) sts64(sb + OFF_M + i * 8, x, y);
                }
            }
        }
        if (hw < W_M1) {
            stage2(p, sb, pw, lane, role, base);
            __threadfence();
            bar_arrive(BAR_DONE, (NS1 + NC + 2) * 32);
        } else {
            bar_arrive(BAR_TABLE, (2 * NC + 1) * 32);
            stage3(p, sb, pw - NC, lane, role, base);
            __threadfence();
        }
    }
    const int role = lds32(sb + W_ROLE);
    int t2;
    asm volatile("mov.u32 %0, %%tid.x;" : "=r"(t2));
    uint4 gh[NR];
    gates<3, 3>(p, t2, role * p.R2, gh);
    gates<0, 3>(p, t2, role * p.R2, gh);
    if (t2 >= W_M2 * 32) {
        int it = 0;
        while (true) {
            bool ok = true;
#pragma unroll
            for (int j = 0; j < 5; j++) ok = ok && ld_rlx32(g_done + min((t2 & 31) + 32 * j, NB - 1)) == base;
            if (__all_sync(0xffffffffu, ok)) break;
            __nanosleep(100);
            if (++it > SPIN_LIMIT) __trap();
        }
        __threadfence();
    }
    epilogue(p, t2, role, base + p.rounds + 8, gh);
}

__global__ void fb_scatter(const uint2* __restrict__ m, const int* __restrict__ idx_in, const int* __restrict__ idx_out,
                           const uint16_t* __restrict__ angle, const __nv_bfloat16* __restrict__ ang_freq, int T, int e0, int e1) {
    const uint32_t fb = *reinterpret_cast<const uint16_t*>(ang_freq);
    for (long long t = blockIdx.x * (long long)blockDim.x + threadIdx.x; t < T; t += (long long)gridDim.x * blockDim.x) {
        int o = idx_out[t];
        if (o < e0 || o >= e1) continue;
        float c = bf16r(cos_bf(hmul_bf2(angle[t], fb) & 0xffffu));
        uint2 v = __ldg(m + idx_in[t]);
        red4(&g_ovf[o - e0], c * bf_lo(v.x), c * bf_hi(v.x), c * bf_lo(v.y), c * bf_hi(v.y));
    }
}
__global__ void fb_final(const Params p, int e0, int e1) {
    int e = e0 + blockIdx.x * blockDim.x + threadIdx.x;
    if (e >= e1) return;
    float4 a4 = g_ovf[e - e0];
    g_ovf[e - e0] = make_float4(0.f, 0.f, 0.f, 0.f);
    float a[4] = {a4.x, a4.y, a4.z, a4.w};
    float d = __bfloat162float(p.dist[e]);
    float g[4] = {0, 0, 0, 0}, h[4] = {0, 0, 0, 0};
    for (int r = 0; r < 8; r++) {
        float df = bf16r(d - __bfloat162float(p.centers[r]));
        float rb = bf16r(expf(bf16r(-10.0f * bf16r(df * df))));
        for (int k = 0; k < 4; k++) {
            g[k] += rb * __bfloat162float(p.w_sbf[r * 4 + k]);
            h[k] += rb * __bfloat162float(p.w_rbf[r * 4 + k]);
        }
    }
    float ag[4];
    for (int k = 0; k < 4; k++) {
        float s = 0.f;
        for (int j = 0; j < 4; j++) s += a[j] * __bfloat162float(p.w_down[j * 4 + k]);
        ag[k] = bf16r(s * g[k]);
    }
    uint2 mv = p.m[e];
    float mm[4] = {bf_lo(mv.x), bf_hi(mv.x), bf_lo(mv.y), bf_hi(mv.y)};
    __nv_bfloat16 o[4];
    for (int k = 0; k < 4; k++) {
        float u = 0.f;
        for (int j = 0; j < 4; j++) u += ag[j] * __bfloat162float(p.w_up[j * 4 + k]);
        o[k] = __float2bfloat16_rn(mm[k] + bf16r(bf16r(u) * bf16r(h[k])));
    }
    p.out[e] = *reinterpret_cast<uint2*>(o);
}

}

static bool exact_div(int E, int lo, int hi, int* R, uint32_t* magic) {
    for (int r = lo; r <= hi; r++) {
        unsigned long long mg = ((1ull << 32) + r - 1) / r, err = mg * r - (1ull << 32);
        if (err * (unsigned long long)E < (1ull << 32)) { *R = r; *magic = (uint32_t)mg; return true; }
    }
    return false;
}

extern "C" void kernel_launch(void* const* d_in, const int* in_sizes, int n_in, void* d_out, int out_size) {
    typedef const __nv_bfloat16* B;
    Params p;
    p.m = (const uint2*)d_in[0]; p.idx_in = (const uint2*)d_in[1]; p.idx_out = (const uint2*)d_in[2]; p.dist = (B)d_in[3];
    p.angle = (const uint32_t*)d_in[4]; p.centers = (B)d_in[5]; p.ang_freq = (B)d_in[6]; p.w_rbf = (B)d_in[7]; p.w_sbf = (B)d_in[8];
    p.w_down = (B)d_in[9]; p.w_up = (B)d_in[10]; p.out = (uint2*)d_out;
    p.E = in_sizes[3]; p.T = in_sizes[1]; p.T2 = p.T >> 1; p.zero = 0;
    p.R1 = p.R2 = p.rounds = p.lastn = 0; p.mg1 = p.mg2 = p.k1 = p.k2 = 0;
    static int ok = -1;
    static unsigned char* ring = nullptr;
    if (ok < 0) {
        void* ra = nullptr;
        cudaGetSymbolAddress(&ra, g_ring);
        ring = reinterpret_cast<unsigned char*>(((uintptr_t)ra + PAIR - 1) & ~(uintptr_t)(PAIR - 1));
        int dev = 0, sms = 0, occ = 0;
        cudaGetDevice(&dev);
        cudaDeviceGetAttribute(&sms, cudaDevAttrMultiProcessorCount, dev);
        cudaError_t e = cudaFuncSetAttribute(fused_kernel, cudaFuncAttributeMaxDynamicSharedMemorySize, SMEM_BYTES);
        if (e == cudaSuccess) e = cudaOccupancyMaxActiveBlocksPerMultiprocessor(&occ, fused_kernel, NTHR, SMEM_BYTES);
        ok = (e == cudaSuccess && occ >= 1 && sms >= NB) ? 1 : 0;
        (void)cudaGetLastError();
    }
    p.ring = ring;
    const bool fused = ok == 1 && p.E <= EMAX && p.E >= 2 * NB && p.T >= 2 && exact_div(p.E, (p.E + NG - 1) / NG, R1MAX, &p.R1, &p.mg1) &&
                       exact_div(p.E, (p.E + NB - 1) / NB, R2MAX, &p.R2, &p.mg2);
    if (fused) {
        p.k1 = 0u - (uint32_t)p.R1; p.k2 = 0u - 4u * (uint32_t)p.R2;
        const int per = NB * NPR;
        int full = p.T2 / per, rest = p.T2 - full * per;
        p.lastn = (rest + NB - 1) / NB;
        if (p.lastn > NPR / 2) { full++; p.lastn = 0; }
        if (full < D) { full = D; p.lastn = 0; }
        p.rounds = full + 1;
        fused_kernel<<<NB, NTHR, SMEM_BYTES>>>(p);
    } else {
        for (int e0 = 0; e0 < p.E; e0 += EMAX) {
            int e1 = p.E - e0 < EMAX ? p.E : e0 + EMAX;
            fb_scatter<<<1056, 256>>>(p.m, (const int*)d_in[1], (const int*)d_in[2], (const uint16_t*)d_in[4], p.ang_freq, p.T, e0, e1);
            fb_final<<<(e1 - e0 + 255) / 256, 256>>>(p, e0, e1);
        }
    }
}
```

```cpp
#include <cuda_runtime.h>
#include <cuda_bf16.h>
#include <stdint.h>

namespace {

constexpr int NB = 132, NG = 66;
constexpr int R2MAX = 6062, R1MAX = 12124;
constexpr int EMAX = NB * R2MAX;
constexpr int NTHR = 1024;
constexpr int NS1 = 8, NC = 11, J = 6;
#define TILES 15
constexpr int NPR = TILES * 64;
#define RING_DEPTH 3
constexpr int D = RING_DEPTH;
constexpr int NPAIR = 7, PAIR = 8192, SLOT = NPAIR * PAIR;
constexpr int WIN = 16896;
constexpr int NDUM = 16;

constexpr int OFF_ACC0 = WIN, OFF_ACC1 = OFF_ACC0 + R2MAX * 4, OFF_BAR = OFF_ACC1 + R2MAX * 4;
constexpr int OFF_H1 = 0x10000 + WIN, OFF_M = OFF_H1 + WIN, OFF_WSM = OFF_M + R1MAX * 8;
constexpr int OFF_CNT1 = OFF_H1 + 0x20000 + WIN, OFF_CNT2 = OFF_CNT1 + (NG + NDUM + 2) * 4, OFF_MAP = OFF_CNT2 + (NB + NDUM) * 4;
constexpr int OFF_HIST = 0x30000, OFF_ZERO = 0x10000;
constexpr int OFF_CADR = OFF_WSM + 128;
constexpr int SMEM_BYTES = OFF_MAP + NB * 8;
static_assert(SMEM_BYTES <= 232448 && OFF_BAR + 64 <= 0x10000 && OFF_CADR + 96 <= 0x30000, "smem");
static_assert(OFF_BAR % 8 == 0 && OFF_MAP % 8 == 0 && OFF_WSM % 16 == 0 && OFF_CNT2 % 16 == 0, "align");
static_assert(NC * J == NG && D == 3 && D * NPAIR + 1 == 2 * NC && NC * 32 * 6 * 16 == 2 * WIN, "shape");

template <int HOP> struct H {
    static constexpr int S = HOP == 1 ? 32 : 16, NBIN = HOP == 1 ? NG : NB, CAP = HOP == 1 ? 48 : 32, PRE = HOP == 1 ? 16 : 4, SH = HOP == 1 ? 11 : 12;
    static constexpr int TB = HOP == 1 ? 20 : 28, CNT = HOP == 1 ? OFF_CNT1 : OFF_CNT2, STG = HOP == 1 ? OFF_H1 : 0;
    static constexpr uint32_t INC = (1u << SH) + 8u, PM = (S - 1) * 8;
    static __device__ __forceinline__ uint32_t init(int slot, uint32_t gen) { return 0x30000u | gen << TB | (slot == D - 1 ? (1u << TB) - (1u << 18) : 0u); }
    static __device__ __forceinline__ uint32_t win(int r) { return HOP == 1 ? (r & 1) << 17 : (0x310u >> (r % 3 * 4) & 3u) << 16; }
};

__device__ __align__(256) unsigned char g_ring[(size_t)(NB * D * NPAIR + 2) * PAIR];
constexpr int REF = NB * D * SLOT;
constexpr int REF_PUB = 2048;
constexpr int REF_FLAG = 3136;
constexpr int RPAD = 6064, DROW = 6144;
__device__ __align__(128) uint8_t g_dirty[NB * DROW];
__device__ uint32_t g_base = 2;
__device__ __align__(128) float4 g_ovf[NB * RPAD];

struct Params {
    const uint2* m; const uint2* idx_in; const uint2* idx_out; const __nv_bfloat16* dist; const uint32_t* angle;
    const __nv_bfloat16* centers; const __nv_bfloat16* ang_freq; const __nv_bfloat16* w_rbf; const __nv_bfloat16* w_sbf;
    const __nv_bfloat16* w_down; const __nv_bfloat16* w_up; uint2* out; unsigned char* ring;
    int E, T, T2, R1, R2, rounds, lastn; uint32_t mg1, mg2, k1, k2, zero;
};

__device__ __forceinline__ float bf16r(float x) { return __bfloat162float(__float2bfloat16_rn(x)); }
__device__ __forceinline__ float bf_lo(uint32_t v) { return __uint_as_float(v << 16); }
__device__ __forceinline__ float bf_hi(uint32_t v) { return __uint_as_float(v & 0xffff0000u); }
__device__ __forceinline__ void red4(float4* a, float x, float y, float z, float w) {
    asm volatile("red.global.add.v4.f32 [%0], {%1,%2,%3,%4};" ::"l"(a), "f"(x), "f"(y), "f"(z), "f"(w) : "memory");
}
__device__ __forceinline__ void bar_sync(int id, int n) { __syncwarp(); asm volatile("bar.sync %0, %1;" ::"r"(id), "r"(n) : "memory"); }
__device__ __forceinline__ void bar_arrive(int id, int n) { __syncwarp(); asm volatile("bar.arrive %0, %1;" ::"r"(id), "r"(n) : "memory"); }
template <int OFF> __device__ __forceinline__ uint32_t atoms_add(uint32_t addr, uint32_t v) {
    uint32_t r; asm volatile("atom.shared.add.u32 %0, [%1+%3], %2;" : "=r"(r) : "r"(addr), "r"(v), "n"(OFF) : "memory"); return r;
}
__device__ __forceinline__ void sts64(uint32_t addr, uint32_t x, uint32_t y) {
    asm volatile("st.shared.v2.u32 [%0], {%1,%2};" ::"r"(addr), "r"(x), "r"(y) : "memory");
}
__device__ __forceinline__ void sts32(uint32_t addr, uint32_t x) { asm volatile("st.shared.u32 [%0], %1;" ::"r"(addr), "r"(x) : "memory"); }
template <int OFF = 0> __device__ __forceinline__ uint2 lds64(uint32_t addr) {
    uint2 v; asm volatile("ld.shared.v2.u32 {%0,%1}, [%2+%3];" : "=r"(v.x), "=r"(v.y) : "r"(addr), "n"(OFF) : "memory"); return v;
}
__device__ __forceinline__ uint32_t lds32(uint32_t addr) {
    uint32_t v; asm volatile("ld.shared.u32 %0, [%1];" : "=r"(v) : "r"(addr) : "memory"); return v;
}
__device__ __forceinline__ uint32_t ld_rlx32(const uint32_t* p) {
    uint32_t v; asm volatile("ld.relaxed.gpu.global.u32 %0, [%1];" : "=r"(v) : "l"(p) : "memory"); return v;
}
__device__ __forceinline__ uint2 ld_rlx64(const void* p) {
    uint2 v; asm volatile("ld.relaxed.gpu.global.v2.u32 {%0,%1}, [%2];" : "=r"(v.x), "=r"(v.y) : "l"(p) : "memory"); return v;
}
__device__ __forceinline__ float4 ld_rlx128f(const float4* p) {
    float4 v; asm volatile("ld.relaxed.gpu.global.v4.f32 {%0,%1,%2,%3}, [%4];" : "=f"(v.x), "=f"(v.y), "=f"(v.z), "=f"(v.w) : "l"(p) : "memory"); return v;
}
__device__ __forceinline__ void st_rlx32(uint32_t* p, uint32_t v) { asm volatile("st.relaxed.gpu.global.u32 [%0], %1;" ::"l"(p), "r"(v) : "memory"); }
__device__ __forceinline__ uint32_t hmul_bf2(uint32_t a, uint32_t b) {
    uint32_t r; asm("mul.rn.bf16x2 %0, %1, %2;" : "=r"(r) : "r"(a), "r"(b)); return r;
}
__device__ __forceinline__ uint32_t hsub_bf2(uint32_t a, uint32_t b) {
    uint32_t r; asm("sub.rn.bf16x2 %0, %1, %2;" : "=r"(r) : "r"(a), "r"(b)); return r;
}
constexpr int SPIN_LIMIT = 1 << 22;

__constant__ uint32_t c_inv2pi[8] = {0u, 0x28be60dbu, 0x9391054au, 0x7f09d5f4u, 0x7d4d3770u, 0x36d8a566u, 0x4f10e410u, 0x7f9458eau};
constexpr uint32_t BIGX = 0x4280u;
__device__ __forceinline__ float cos_big(uint32_t xb) {
    uint32_t e = (xb >> 7) & 0xffu, M = (xb & 0x7fu) | 0x80u;
    uint32_t pp = e - 102u;
    uint32_t wi = pp >> 5;
    uint32_t t0 = c_inv2pi[wi], t1 = c_inv2pi[wi + 1], t2 = c_inv2pi[wi + 2];
    uint32_t f = M * __funnelshift_l(t1, t0, pp) + __umulhi(M, __funnelshift_l(t2, t1, pp));
    float c = __cosf((float)(int)f * 1.4629180792671596e-9f);
    return e == 255u ? __uint_as_float(0x7fc00000u) : c;
}
__device__ __forceinline__ float cos_bf(uint32_t xb) {
    return (xb & 0x7fffu) > BIGX ? cos_big(xb) : __cosf(__uint_as_float(xb << 16));
}
__device__ __forceinline__ uint32_t pack_bf2(float lo, float hi) {
    uint32_t r; asm("cvt.rn.bf16x2.f32 %0, %1, %2;" : "=r"(r) : "f"(hi), "f"(lo)); return r;
}
template <int N> __device__ __forceinline__ uint32_t pick(int k, const uint32_t (&a)[N]) {
    uint32_t v = a[0];
#pragma unroll
    for (int i = 1; i < N; i++) if (k == i) v = a[i];
    return v;
}
template <int N> __device__ __forceinline__ uint2 pick(int k, const uint2 (&a)[N]) {
    uint2 v = a[0];
#pragma unroll
    for (int i = 1; i < N; i++) if (k == i) v = a[i];
    return v;
}
__device__ __forceinline__ void side_add(uint32_t bin, uint32_t row, float a, float b, float c, float d) {
    red4(&g_ovf[bin * RPAD + row], a, b, c, d);
    g_dirty[bin * DROW + row] = 1;
}
__device__ __forceinline__ void slow_triplet(const Params& p, uint32_t ii, uint32_t oo, float c) {
    const uint2 v = __ldg(p.m + ii);
    const uint32_t bo = __umulhi(oo, p.mg2);
    side_add(bo, oo - bo * p.R2, c * bf_lo(v.x), c * bf_hi(v.x), c * bf_lo(v.y), c * bf_hi(v.y));
}
__device__ __forceinline__ void slow_rec1(const Params& p, uint32_t x, uint32_t y, uint32_t bin) {
    const uint2 v = __ldg(p.m + bin * p.R1 + (y & 0xffffu));
    const float c = bf_hi(y);
    side_add(x & 0xffu, __byte_perm(x, 0u, 0x4413) >> 2, c * bf_lo(v.x), c * bf_hi(v.x), c * bf_lo(v.y), c * bf_hi(v.y));
}
__device__ __forceinline__ uint32_t aux_of(uint32_t w0, uint32_t w1) {
    uint32_t u; asm("lop3.b32 %0, %1, %2, 0xf000f000, 0xe4;" : "=r"(u) : "r"(w0), "r"(w1 >> 4));
    return __byte_perm(u, 0u, 0x4413);
}
__device__ __forceinline__ void slow_rec2(const Params& p, uint32_t w0, uint32_t w1, uint32_t bin, float unit) {
    side_add(bin, aux_of(w0, w1) >> 2, (float)((int)(w0 & 0xfffu) - 2048) * unit, (float)((int)(w0 >> 16 & 0xfffu) - 2048) * unit,
             (float)((int)(w1 & 0xfffu) - 2048) * unit, (float)((int)(w1 >> 16 & 0xfffu) - 2048) * unit);
}
template <uint32_t M> __device__ __forceinline__ uint32_t and_or(uint32_t a, uint32_t c) {
    uint32_t r; asm("lop3.b32 %0, %1, %2, %3, 0xea;" : "=r"(r) : "r"(a), "n"(M), "r"(c)); return r;
}
__device__ __forceinline__ uint32_t and_xor(uint32_t a, uint32_t m, uint32_t c) {
    uint32_t r; asm("lop3.b32 %0, %1, %2, %3, 0x6a;" : "=r"(r) : "r"(a), "r"(m), "r"(c)); return r;
}
__device__ __forceinline__ uint2 ld_in(const uint2* a) {
    uint2 v; asm volatile("ld.global.nc.L1::no_allocate.v2.u32 {%0,%1}, [%2];" : "=r"(v.x), "=r"(v.y) : "l"(a)); return v;
}
__device__ __forceinline__ uint32_t ld_in(const uint32_t* a) {
    uint32_t v; asm volatile("ld.global.nc.L1::no_allocate.u32 %0, [%1];" : "=r"(v) : "l"(a)); return v;
}
template <int OFF> __device__ __forceinline__ void put_rec(uint32_t ret, uint32_t lim, uint32_t addr, uint32_t x, uint32_t y) {
    asm volatile("{ .reg .pred q; setp.lt.u32 q, %0, %1; @q st.shared.v2.u32 [%2+%5], {%3,%4}; }" ::"r"(ret), "r"(lim), "r"(addr), "r"(x), "r"(y), "n"(OFF) : "memory");
}
__device__ __forceinline__ uint32_t mbar_try(uint32_t mb, uint32_t parity) {
    uint32_t ok;
    asm volatile("{ .reg .pred q; mbarrier.try_wait.parity.shared::cta.b64 q, [%1], %2; selp.u32 %0, 1, 0, q; }" : "=r"(ok) : "r"(mb), "r"(parity) : "memory");
    return ok;
}
__device__ __forceinline__ void mbar_wait(uint32_t mb, uint32_t parity) {
    if (!mbar_try(mb, parity)) {
        int it = 0;
        while (!mbar_try(mb, parity)) if (++it > SPIN_LIMIT) __trap();
    }
}
__device__ __forceinline__ void mbar_arrive(uint32_t mb) { asm volatile("mbarrier.arrive.shared::cta.b64 _, [%0];" ::"r"(mb) : "memory"); }
constexpr int B_FULL = OFF_BAR, B_OPEN = OFF_BAR + 16, B_FREE = OFF_BAR + 32, W_PROBE = OFF_BAR + 48, W_ROLE = OFF_BAR + 52, W_EXP = OFF_BAR + 56, W_UNIT = OFF_BAR + 60;
enum { BAR_PROBE = 1, BAR_ROLE, BAR_CLEAR, BAR_TABLE, BAR_H1, BAR_DONE };
constexpr int W_M1 = NS1 + NC, W_M2 = 31;

extern __shared__ __align__(1024) unsigned char smem[];
#define TK_DECL
#define TK(i)
#define TK_CNT(i)
#define TK_OUT
#define TK_ARG
#define TK_PASS
#define TKX(i)

constexpr int NR = (R2MAX + NTHR - 1) / NTHR;
__device__ __forceinline__ void gates(const Params& p, int e0, int e1, int e2, uint4* gh) {
    constexpr int NH = 3;
    const int e[NH] = {e0, e1, e2};
    uint32_t dd[NH];
    float g[NH][4], h[NH][4];
#pragma unroll
    for (int u = 0; u < NH; u++) {
        dd[u] = reinterpret_cast<const uint16_t*>(p.dist)[min(e[u], p.E - 1)] * 0x10001u;
#pragma unroll
        for (int k = 0; k < 4; k++) { g[u][k] = 0.f; h[u][k] = 0.f; }
    }
#pragma unroll 1
    for (int r2 = 0; r2 < 4; r2++) {
        const uint32_t cen = __ldg(reinterpret_cast<const uint32_t*>(p.centers) + r2);
        const uint4 s4 = __ldg(reinterpret_cast<const uint4*>(p.w_sbf) + r2), r4 = __ldg(reinterpret_cast<const uint4*>(p.w_rbf) + r2);
        const uint32_t sw[4] = {s4.x, s4.y, s4.z, s4.w}, rw[4] = {r4.x, r4.y, r4.z, r4.w};
        uint32_t rb[NH];
#pragma unroll
        for (int u = 0; u < NH; u++) {
            const uint32_t df = hsub_bf2(dd[u], cen);
            const uint32_t ar = hmul_bf2(hmul_bf2(df, df), 0xc120c120u);
            rb[u] = pack_bf2(__expf(bf_lo(ar)), __expf(bf_hi(ar)));
        }
#pragma unroll
        for (int i = 0; i < 8; i++) {
            const float ws = i & 1 ? bf_hi(sw[i >> 1]) : bf_lo(sw[i >> 1]), wr = i & 1 ? bf_hi(rw[i >> 1]) : bf_lo(rw[i >> 1]);
#pragma unroll
            for (int u = 0; u < NH; u++) {
                const float x = i < 4 ? bf_lo(rb[u]) : bf_hi(rb[u]);
                g[u][i & 3] += x * ws;
                h[u][i & 3] += x * wr;
            }
        }
    }
#pragma unroll
    for (int u = 0; u < NH; u++)
        gh[u] = make_uint4(pack_bf2(g[u][0], g[u][1]), pack_bf2(g[u][2], g[u][3]), pack_bf2(h[u][0], h[u][1]), pack_bf2(h[u][2], h[u][3]));
}
__device__ __forceinline__ void prefetch_l2(const void* a) { asm volatile("prefetch.global.L2 [%0];" ::"l"(a)); }
__device__ __forceinline__ uint4* gate_slot(int k) { return reinterpret_cast<uint4*>(smem + OFF_H1 + (k >= WIN / 16 ? 0x20000 - WIN : 0)) + k; }
__device__ __forceinline__ void wait_flags(const Params& p, uint32_t sb, int lane, uint32_t need, uint32_t span) {
    const unsigned char* f = p.ring + REF + REF_FLAG + (lds32(sb + W_PROBE) >> (D * NPAIR) << 12);
    int it = 0;
    while (true) {
        const float4 a = ld_rlx128f(reinterpret_cast<const float4*>(f) + lane);
        const uint32_t b = ld_rlx32(reinterpret_cast<const uint32_t*>(f) + 128 + (lane & 3));
        const uint32_t d = max(max(max(__float_as_uint(a.x) - need, __float_as_uint(a.y) - need), max(__float_as_uint(a.z) - need, __float_as_uint(a.w) - need)), b - need);
        if (__all_sync(0xffffffffu, d <= span)) break;
        __nanosleep(50);
        if (++it > SPIN_LIMIT) __trap();
    }
    __threadfence();
}
__device__ __forceinline__ void epilogue(const Params& p, uint32_t sb, uint32_t base) {
    int tid;
    asm volatile("mov.u32 %0, %%tid.x;" : "=r"(tid));
    const int role = lds32(sb + W_ROLE), row0 = role * p.R2, nrows = min(p.R2, p.E - row0), hw = tid >> 5;
    const bool s3 = hw > W_M1 && hw < W_M2;
    constexpr int T3 = (W_M1 + 1) * 32, N3 = NC * 32;
    uint4 gh[NR];
    if (hw < NS1) {
        if (tid * 64 < nrows) prefetch_l2(p.dist + row0 + tid * 64);
        for (int i = tid * 16; i < nrows; i += NS1 * 32 * 16) prefetch_l2(p.m + row0 + i);
    }
    if (!s3) gates(p, row0 + tid + 3 * NTHR, row0 + tid + 4 * NTHR, row0 + tid + 5 * NTHR, gh + 3);
    if (hw < NS1) {
        bar_sync(BAR_H1, (NS1 + 1) * 32);
#pragma unroll 1
        for (int k0 = tid; k0 < NR * N3; k0 += 3 * NS1 * 32) {
            int k[3], e[3];
#pragma unroll
            for (int u = 0; u < 3; u++) { k[u] = k0 + u * NS1 * 32; e[u] = row0 + T3 + k[u] + k[u] / N3 * (NTHR - N3); }
            gates(p, e[0], e[1], e[2], gh);
#pragma unroll
            for (int u = 0; u < 3; u++) if (k[u] < NR * N3) *gate_slot(k[u]) = gh[u];
        }
#pragma unroll
        for (int i = tid; i < DROW / 8; i += NS1 * 32) {
            const uint2 f = ld_rlx64(g_dirty + role * DROW + i * 8);
            if (f.x | f.y) prefetch_l2(g_ovf + role * RPAD + i * 8);
        }
    }
    if (!s3) gates(p, row0 + tid, row0 + tid + NTHR, row0 + tid + 2 * NTHR, gh);
    if (hw == W_M1) {
        reinterpret_cast<float*>(smem + OFF_WSM)[tid & 31] = __bfloat162float(tid & 16 ? p.w_up[tid & 15] : p.w_down[tid & 15]);
        wait_flags(p, sb, tid & 31, base + 2, 0);
    }
    TKX(5)
    bar_sync(0, NTHR);
    TKX(6)
    uint32_t dirty = 0;
#pragma unroll
    for (int it = 0; it < NR; it++) {
        uint32_t f;
        asm volatile("ld.relaxed.gpu.global.u8 %0, [%1];" : "=r"(f) : "l"(g_dirty + role * DROW + tid + it * NTHR) : "memory");
        dirty |= f << it;
    }
    if (s3) {
#pragma unroll
        for (int it = 0; it < NR; it++) gh[it] = *gate_slot(tid - T3 + it * N3);
    }
    if (tid == W_M1 * 32 && blockIdx.x == 0) g_base = base + p.rounds + 8;
    const float unit = *reinterpret_cast<const float*>(smem + W_UNIT);
    const float4* w4 = reinterpret_cast<const float4*>(smem + OFF_WSM);
#pragma unroll
    for (int i0 = 0; i0 < NR; i0 += 3) {
        uint2 mv[3];
        float4 o[3];
#pragma unroll
        for (int u = 0; u < 3; u++) mv[u] = __ldg(p.m + min(row0 + tid + (i0 + u) * NTHR, p.E - 1));
#pragma unroll
        for (int u = 0; u < 3; u++) {
            o[u] = make_float4(0.f, 0.f, 0.f, 0.f);
            if (dirty >> (i0 + u) & 1) o[u] = ld_rlx128f(&g_ovf[role * RPAD + tid + (i0 + u) * NTHR]);
        }
#pragma unroll
        for (int u = 0; u < 3; u++) {
            const int it = i0 + u, i = tid + it * NTHR;
            if (dirty >> it & 1) { g_ovf[role * RPAD + i] = make_float4(0.f, 0.f, 0.f, 0.f); g_dirty[role * DROW + i] = 0; }
            if (i < nrows) {
                const uint32_t u0 = reinterpret_cast<const uint32_t*>(smem + OFF_ACC0)[i] + 0x40004000u, u1 = reinterpret_cast<const uint32_t*>(smem + OFF_ACC1)[i] + 0x40004000u;
                const float a[4] = {(float)((int)(u0 & 0xffffu) - 0x8000) * unit + o[u].x, (float)((int)(u0 >> 16) - 0x8000) * unit + o[u].y,
                                    (float)((int)(u1 & 0xffffu) - 0x8000) * unit + o[u].z, (float)((int)(u1 >> 16) - 0x8000) * unit + o[u].w};
                float sd[4] = {0, 0, 0, 0}, uu[4] = {0, 0, 0, 0};
#pragma unroll
                for (int j = 0; j < 4; j++) {
                    float4 w = w4[j];
                    sd[0] += a[j] * w.x; sd[1] += a[j] * w.y; sd[2] += a[j] * w.z; sd[3] += a[j] * w.w;
                }
                const uint32_t a01 = pack_bf2(sd[0] * bf_lo(gh[it].x), sd[1] * bf_hi(gh[it].x)), a23 = pack_bf2(sd[2] * bf_lo(gh[it].y), sd[3] * bf_hi(gh[it].y));
                const float ag[4] = {bf_lo(a01), bf_hi(a01), bf_lo(a23), bf_hi(a23)};
#pragma unroll
                for (int j = 0; j < 4; j++) {
                    float4 w = w4[4 + j];
                    uu[0] += ag[j] * w.x; uu[1] += ag[j] * w.y; uu[2] += ag[j] * w.z; uu[3] += ag[j] * w.w;
                }
                const uint32_t t01 = hmul_bf2(pack_bf2(uu[0], uu[1]), gh[it].z);
                const uint32_t t23 = hmul_bf2(pack_bf2(uu[2], uu[3]), gh[it].w);
                uint2 q;
                asm("add.rn.bf16x2 %0, %1, %2;" : "=r"(q.x) : "r"(mv[u].x), "r"(t01));
                asm("add.rn.bf16x2 %0, %1, %2;" : "=r"(q.y) : "r"(mv[u].y), "r"(t23));
                p.out[row0 + i] = q;
            }
        }
    }
}

template <int HOP> __device__ __forceinline__ uint32_t mailbox(uint32_t sb, int lead) {
    const uint2 mp = lds64(sb + OFF_MAP + lead * 8);
    return (mp.y * (D * NPAIR) + 6) * PAIR + (((mp.x >> 6 & 1u) ^ (lead >= NG)) << 12) + 1024 + HOP * 1024;
}
template <int HOP> __device__ __forceinline__ uint4 nulls(int lane) {
    const uint32_t i = lane & 7;
    if (HOP == 1) {
        const uint32_t x = (NB + 2 * i) | 1u << H<1>::TB, y = (OFF_CNT2 - OFF_M) / 8 + 2 * i;
        return make_uint4(x, y, x + 1, y + 1);
    }
    const uint32_t x = 0x08000800u | (i & 2u) << 28 | blockIdx.x << 30, y = 0x08000800u | 1u << H<2>::TB | i << 31;
    return make_uint4(x, y, x | 1u << 28, y | 1u << 30);
}
template <int OFF> __device__ __forceinline__ void sts128(uint32_t a, const uint4& v) {
    asm volatile("st.shared.v4.u32 [%0+%5], {%1,%2,%3,%4};" ::"r"(a), "r"(v.x), "r"(v.y), "r"(v.z), "r"(v.w), "n"(OFF) : "memory");
}
template <int HOP> struct Prefill {
    uint32_t a0, a1;
    __device__ __forceinline__ Prefill(int lane) {
        const uint32_t q = lane >> 3, i = lane & 7, b = q + (i & 4), c = (q & 1) + (q & 2) * 4 + (i & 6);
        a0 = HOP == 1 ? q * 256 + ((8 + q + i) & 15) * 16 : b * 128 + ((4 + b + (i & 3)) & 7) * 16;
        a1 = HOP == 1 ? q * 256 + 1024 + ((12 + q + i) & 15) * 16 : c * 128 + ((2 + c + (i & 1)) & 7) * 16;
    }
    __device__ __forceinline__ void run(uint32_t win, const uint4& v) const {
#pragma unroll 1
        for (uint32_t w = win; w < win + 16384; w += 8192) {
            sts128<0>(w + a0, v); sts128<2048>(w + a0, v); sts128<4096>(w + a0, v); sts128<6144>(w + a0, v);
            sts128<0>(w + a1, v); sts128<2048>(w + a1, v); sts128<4096>(w + a1, v); sts128<6144>(w + a1, v);
            if (HOP == 2) { sts128<1024>(w + a0, v); sts128<3072>(w + a0, v); sts128<5120>(w + a0, v); sts128<7168>(w + a0, v); }
        }
        if (a0 < 512) sts128<16384>(win + a0, v);
        if (HOP == 2 && a1 < 512) sts128<16384>(win + a1, v);
    }
};
__device__ __forceinline__ bool elect() {
    uint32_t q; asm volatile("{ .reg .pred q; elect.sync _|q, 0xffffffff; selp.u32 %0, 1, 0, q; }" : "=r"(q)); return q;
}
template <int HOP>
__device__ __forceinline__ void manager(const Params& p, uint32_t sb, int lane, int role, uint32_t base) {
    typedef H<HOP> h;
    constexpr int V = h::NBIN / 32, PB = h::S * 8;
    const int RT = p.rounds, grp = role >= NG;
    unsigned char* dst = p.ring + (uint32_t)(blockIdx.x * D * SLOT);
    uint32_t halves = __reduce_or_sync(0xffffffffu, lds64(sb + OFF_MAP + role * 8).x ^ (HOP == 1 && grp ? ~0u : 0u)) & ((1u << D * NPAIR) - 1u);
    const unsigned char* cr = p.ring + mailbox<HOP>(sb, HOP == 1 ? role / J * J : max(role / (2 * J) * (2 * J), grp * NG));
    const unsigned char* cr0 = cr + lane * V * 4, *cr1 = cr + (32 * V + min(lane, V - 1)) * 4;
    const uint32_t ca0 = sb + h::CNT + lane * V * 4, ca1 = sb + h::CNT + (32 * V + min(lane, V + NDUM - 1)) * 4;
    const uint32_t rot0 = (lane * V & 7) * 16, rot1 = lane < V ? lane * 16 : 0x80000000u;
    const Prefill<HOP> pf(lane);
    uint4 nul = nulls<HOP>(lane);
    int slot = 0;
    uint32_t init = h::init(0, 1), prim = sb + h::STG;
    uint32_t cs[5];
    auto sample = [&]() {
        if (V == 2) asm volatile("ld.relaxed.gpu.global.v2.u32 {%0,%1}, [%2];" : "=r"(cs[0]), "=r"(cs[1]) : "l"(cr0) : "memory");
        else asm volatile("ld.relaxed.gpu.global.v4.u32 {%0,%1,%2,%3}, [%4];" : "=r"(cs[0]), "=r"(cs[1]), "=r"(cs[2]), "=r"(cs[3]) : "l"(cr0) : "memory");
        cs[V] = ld_rlx32(reinterpret_cast<const uint32_t*>(cr1));
    };
    sample();
    if (HOP == 1) bar_sync(BAR_CLEAR, 64);
    uint32_t c[5];
    TK_DECL
#pragma unroll 1
    for (int r = 0;; r++) {
        const int nslot = slot == D - 1 ? 0 : slot + 1;
        const uint32_t ninit = h::init(nslot, (init + 0x10000u) >> h::TB & 1u), done = prim;
        TK(5)
        mbar_wait(sb + B_FULL + (HOP - 1) * 8, r & 1);
        TK(0)
        if (V == 2) asm volatile("ld.shared.v2.u32 {%0,%1}, [%2];" : "=r"(c[0]), "=r"(c[1]) : "r"(ca0) : "memory");
        else asm volatile("ld.shared.v4.u32 {%0,%1,%2,%3}, [%4];" : "=r"(c[0]), "=r"(c[1]), "=r"(c[2]), "=r"(c[3]) : "r"(ca0) : "memory");
        c[V] = lds32(ca1);
        uint32_t nc[5], lo = c[V];
#pragma unroll
        for (int k = 0; k <= V; k++) {
            const uint32_t z = ninit + (k < V ? rot0 + k * 16 : rot1);
            nc[k] = min(max(c[k] + (ninit - init - h::S * h::INC), z), z + (h::CAP - h::S) * h::INC);
            lo = min(lo, c[k]);
        }
        if (V == 2) sts64(ca0, nc[0], nc[1]); else sts128<0>(ca0, make_uint4(nc[0], nc[1], nc[2], nc[3]));
        sts32(ca1, nc[V]);
        __syncwarp();
        if (lane == 0) mbar_arrive(sb + B_OPEN + (HOP - 1) * 8);
        TK(1)
        if (lo < init + (h::PRE << h::SH)) {
            const uint32_t gb = init & 1u << h::TB, vx = HOP == 1 ? NB | gb : 0x08000800u, vy = HOP == 1 ? nul.y : 0x08000800u | gb;
#pragma unroll 1
            for (int k = 0; k <= V; k++) {
                const uint32_t bin = k < V ? lane * V + k : 32 * V + lane;
#pragma unroll 1
                for (uint32_t x = pick(k, c); x < init + (h::PRE << h::SH); x += h::INC) sts64(prim + bin * PB + (x & h::PM), vx, vy);
            }
        }
        __syncwarp();
        TK(2)
        asm volatile("fence.proxy.async.shared::cta;" ::: "memory");
        TK(6)
        if (r >= D) {
            int it = 0;
            while (true) {
                uint32_t bad = 0;
#pragma unroll
                for (int k = 0; k <= V; k++) bad |= cs[k] - (base + r - D + 1);
                if (!__any_sync(0xffffffffu, bad >> 20)) break;
                if (++it > SPIN_LIMIT) __trap();
                if (it > 1) __nanosleep(100);
                sample();
            }
        }
        TK(3)
        if (elect()) {
#pragma unroll
            for (int i = 0; i < (HOP == 1 ? 5 : 6); i++) {
                const int k = HOP == 1 ? i : i % 3, pg = HOP == 1 ? 0 : i / 3, pair = HOP == 1 ? (k < 4 ? k : 6) : 4 + k;
                const uint32_t o = (((pg ? ~halves : halves) << (12 - pair)) & 4096u) | (pair * PAIR + (HOP == 1 && pair == 6 ? 1024 : 0));
                asm volatile("cp.async.bulk.global.shared::cta.bulk_group [%0], [%1], %2;"
                             ::"l"(dst + o), "r"(prim + pg * NG * PB + k * 4096), "r"(pair < 6 ? 4096 : 2 * PB) : "memory");
            }
            asm volatile("cp.async.bulk.commit_group;" ::: "memory");
            asm volatile("cp.async.bulk.wait_group.read 0;" ::: "memory");
            if (HOP == 1) mbar_arrive(sb + B_FREE);
        }
        __syncwarp();
        TK(4)
        prim = HOP == 1 ? prim ^ 0x20000u : sb + ((0x310u >> (nslot * 4) & 3u) << 16);
        if (r == RT - 1) break;
        sample();
        if (slot == (HOP == 1 ? 1 : 0)) {
            if (HOP == 1) { nul.x ^= 1u << h::TB; nul.z ^= 1u << h::TB; }
            else { nul.y ^= 1u << h::TB; nul.w ^= 1u << h::TB; }
        }
        pf.run(done, nul);
        dst += slot == D - 1 ? -(D - 1) * SLOT : SLOT;
        halves = (halves >> NPAIR | halves << (D - 1) * NPAIR) & ((1u << D * NPAIR) - 1u);
        slot = nslot;
        init = ninit;
    }
#pragma unroll 1
    for (int k = 0; k <= V; k++) {
        const uint32_t bin = k < V ? lane * V + k : 32 * V + lane, n = bin < h::NBIN ? min((pick(k, c) - init) >> h::SH, (uint32_t)h::CAP) : 0u;
#pragma unroll 1
        for (uint32_t x = h::S; x < n; x++) {
            const uint2 w = lds64(prim + bin * PB + ((x + (bin & 7) * 2) & (h::S - 1)) * 8);
            if (HOP == 1) slow_rec1(p, w.x, w.y, bin);
            else slow_rec2(p, w.x, w.y, bin, __uint_as_float(lds32(sb + W_UNIT)));
        }
    }
    asm volatile("cp.async.bulk.wait_group 0;" ::: "memory");
    TK_OUT
}

#define POLL_NS 200
template <int HOP> struct Reader {
    uint32_t cur[J];
    uint32_t st;
    uint32_t want;
    __device__ __forceinline__ bool wrap() const { return st & 0x80u; }
    static __device__ __forceinline__ int source(int w, int j, int lane, int role) { return HOP == 1 ? (role >= NG ? NG : 0) + w * J + j : (w * J + j) * 2 + (lane >> 4); }
    __device__ __forceinline__ void init(const Params& p, uint32_t sb, int w, int lane, int role) {
        const int grp = role >= NG, l = role - grp * NG;
        const int pair = HOP == 1 ? (l < 64 ? l >> 4 : 6) : 4 + (l >> 5);
        const uint32_t in = HOP == 1 ? (l & 15) * 256 + (l < 64 ? 0 : 1024) + lane * 8 : (l & 31) * 128 + (lane & 15) * 8;
        st = 0xc04000u;
        if (lane == 0) sts32(sb + OFF_CADR + ((HOP - 1) * NC + w) * 4, mailbox<HOP>(sb, source(w, 0, 0, role)) + (HOP == 1 ? l : role) * 4);
        if (HOP == 2 && w == NC / 2 && lane == 0) sts32(sb + OFF_CADR + 2 * NC * 4, mailbox<HOP>(sb, NG) + role * 4);
        __syncwarp();
#pragma unroll
        for (int j = 0; j < J; j++) {
            const uint2 mp = lds64(sb + OFF_MAP + source(w, j, lane, role) * 8);
            const uint32_t hv = mp.x >> pair;
            cur[j] = (mp.y * (D * NPAIR) + pair) * PAIR + in + (((hv & 1u) ^ grp) << 12);
#pragma unroll
            for (int s = 0; s < D; s++) st |= ((hv >> (s * NPAIR) ^ hv >> ((s + 1) % D * NPAIR)) & 1u) << (s * 8 + j);
        }
        want = 1u << H<HOP>::TB;
    }
    __device__ __forceinline__ void load(const Params& p, uint2 (&rec)[J]) const {
#pragma unroll
        for (int j = 0; j < J; j++) rec[j] = ld_rlx64(p.ring + cur[j]);
    }
    __device__ __forceinline__ void check(const Params& p, uint32_t sb, uint2 (&rec)[J], uint32_t done TK_ARG) const {
        constexpr uint32_t BIT = 1u << H<HOP>::TB;
        int it = 0;
        uint32_t bad;
        while (true) {
            bad = 0;
#pragma unroll
            for (int j = 0; j < J; j++) bad |= (HOP == 1 ? rec[j].x : rec[j].y) ^ want;
            if (!__any_sync(0xffffffffu, bad & BIT)) break;
            if (++it > SPIN_LIMIT) __trap();
            __nanosleep(POLL_NS);
            TK_CNT(7)
#pragma unroll
            for (int j = 0; j < J; j++)
                asm volatile("{ .reg .pred q; .reg .u32 t; .reg .u64 a; xor.b32 t, %5, %4; and.b32 t, t, %6; setp.ne.u32 q, t, 0;\n"
                             "cvt.u64.u32 a, %3; add.u64 a, a, %2; @q ld.relaxed.gpu.global.v2.u32 {%0,%1}, [a]; }"
                             : "+r"(rec[j].x), "+r"(rec[j].y) : "l"(p.ring), "r"(cur[j]), "r"(want), "r"(HOP == 1 ? rec[j].x : rec[j].y), "n"(BIT) : "memory");
        }
        uint32_t t;
        asm volatile("mov.u32 %0, %%tid.x;" : "=r"(t));
        const bool extra = HOP == 2 && t == (NS1 + NC + 1 + NC / 2) * 32 + 1;
        if ((t & 31u) == 0 || extra)
            st_rlx32(reinterpret_cast<uint32_t*>(p.ring + lds32(sb + OFF_CADR + (extra ? 2 * NC * 4 : (t >> 3) - (NS1 + HOP - 1) * 4))), done);
    }
    __device__ __forceinline__ void advance() {
        const uint32_t ds = wrap() ? -(D - 1) * SLOT : SLOT;
#pragma unroll
        for (int j = 0; j < J; j++) cur[j] = (cur[j] ^ (st << (12 - j) & 4096u)) + ds;
        want ^= (st & 0x80u) << (H<HOP>::TB - 7);
        st = __byte_perm(st, 0u, 0x3021);
    }
};

#define NPROBE 7
__device__ __forceinline__ uint32_t near_half(unsigned char* pair, uint32_t zero) {
#pragma unroll
    for (int i = 0; i < 4; i++) *reinterpret_cast<uint4*>(pair + (i >> 1) * 4096 + (i & 1) * 16) = make_uint4(0u, 0u, 0u, 0u);
    uint32_t best[2] = {~0u, ~0u}, v = 0, prev = 0;
#pragma unroll
    for (int t = 0; t <= NPROBE; t++) {
        uint32_t now;
        asm volatile("atom.relaxed.gpu.global.add.u32 %0, [%1], 1;" : "=r"(v) : "l"(pair + (t & 1) * 4096 + (v & zero)) : "memory");
        asm volatile("mov.u32 %0, %%clock;" : "=r"(now) :: "memory");
        if (t > 1) best[(t - 1) & 1] = min(best[(t - 1) & 1], now - prev);
        prev = now;
    }
    return (best[1] < best[0] ? 1u : 0u) | (v & zero);
}
template <bool B> struct BoolC { static constexpr bool value = B; };

template <int NP>
__device__ __forceinline__ void stage1(const Params& p, uint32_t sb, const int pos0, int lane) {
    typedef H<1> h;
    const int RT = p.rounds;
    const uint32_t ff = *reinterpret_cast<const uint16_t*>(p.ang_freq) * 0x10001u;
    auto pair_of = [&](int r, int pos) {
        const int q = r < RT - 1 ? (r * NB + blockIdx.x) * NPR + pos : (RT - 1) * NB * NPR + blockIdx.x * p.lastn + pos;
        return (r < RT - 1 || (r == RT - 1 && pos < p.lastn)) && q < p.T2 ? q : -1;
    };
    uint2 vi[NP], vo[NP]; uint32_t va[NP];
    auto load_edge = [&](int r) {
#pragma unroll
        for (int u = 0; u < NP; u++) {
            const int q = max(pair_of(r, pos0 + u * 32), 0);
            vi[u] = ld_in(p.idx_in + q); vo[u] = ld_in(p.idx_out + q); va[u] = ld_in(p.angle + q);
        }
    };
    load_edge(0);
    if (blockIdx.x == 0 && pos0 == 0 && (p.T & 1)) {
        const int t = p.T - 1;
        slow_triplet(p, reinterpret_cast<const uint32_t*>(p.idx_in)[t], reinterpret_cast<const uint32_t*>(p.idx_out)[t],
                     bf16r(cos_bf(hmul_bf2(reinterpret_cast<const uint16_t*>(p.angle)[t], ff) & 0xffffu)));
    }
    uint32_t init = h::init(0, 1);
    int slot = 0;
    TK_DECL
    auto step = [&](const int r, auto edge) {
        constexpr bool EDGE = decltype(edge)::value;
        uint32_t cc[NP], big = 0;
#pragma unroll
        for (int u = 0; u < NP; u++) {
            va[u] = hmul_bf2(va[u], ff);
            cc[u] = pack_bf2(__cosf(bf_lo(va[u])), __cosf(bf_hi(va[u])));
            big = __vmaxu2(big, va[u] & 0x7fff7fffu);
        }
        if ((big + (0x7fffu - BIGX) * 0x10001u) & 0x80008000u) {
#pragma unroll 1
            for (int u = 0; u < NP; u++) {
                const uint32_t a = pick(u, va);
                float c0 = cos_bf(a & 0xffffu), c1 = cos_bf(a >> 16);
                if ((c0 != c0 || c1 != c1) && (!EDGE || pair_of(r, pos0 + u * 32) >= 0)) {
                    const uint2 i2 = pick(u, vi), o2 = pick(u, vo);
                    if (c0 != c0) slow_triplet(p, i2.x, o2.x, c0);
                    if (c1 != c1) slow_triplet(p, i2.y, o2.y, c1);
                }
                const uint32_t v = pack_bf2(c0 != c0 ? 0.f : c0, c1 != c1 ? 0.f : c1);
#pragma unroll
                for (int k = 0; k < NP; k++) if (k == u) cc[k] = v;
            }
        }
        uint32_t bin[2 * NP], x[2 * NP], y[2 * NP];
#pragma unroll
        for (int j = 0; j < 2 * NP; j++) {
            const uint32_t ii = j & 1 ? vi[j >> 1].y : vi[j >> 1].x, oo = j & 1 ? vo[j >> 1].y : vo[j >> 1].x;
            bin[j] = __umulhi(ii, p.mg1);
            y[j] = __byte_perm(bin[j] * p.k1 + ii, cc[j >> 1], j & 1 ? 0x7610 : 0x5410);
            const uint32_t bo = __umulhi(oo, p.mg2);
            x[j] = __byte_perm(bo * p.k2 + oo * 4u, bo, 0x0514);
            if (EDGE && pair_of(r, pos0 + (j >> 1) * 32) < 0) bin[j] = NG + (lane & (NDUM - 1));
        }
        if (EDGE) load_edge(r + 1);
        else {
            uint32_t dep = 0;
#pragma unroll
            for (int j = 0; j < 2 * NP; j++) dep |= x[j] | y[j];
            const int q = ((r + 1) * NB + blockIdx.x) * NPR + pos0 + (dep & p.zero);
#pragma unroll
            for (int u = 0; u < NP; u++) { vi[u] = ld_in(p.idx_in + q + u * 32); vo[u] = ld_in(p.idx_out + q + u * 32); va[u] = ld_in(p.angle + q + u * 32); }
        }
        const uint32_t kb = sb + h::win(r + 1), lim = init + (h::CAP << h::SH);
        TK(0)
        mbar_wait(sb + B_OPEN, (r - 1) & 1);
        TK(1)
        bool freed = false;
        uint32_t over = 0;
#pragma unroll
        for (int g = 0; g < 2 * NP; g += 4) {
            uint32_t ret[4];
#pragma unroll
            for (int j = 0; j < 4; j++) ret[j] = atoms_add<h::CNT>(sb + bin[g + j] * 4, h::INC);
            const int mx = max(max((int)ret[0], (int)ret[1]), max((int)ret[2], (int)ret[3]));
            if (!freed && __any_sync(0xffffffffu, mx >= (int)(init + 0x10000u))) { TK(2) mbar_wait(sb + B_FREE, (r - 1) & 1); freed = true; TK(3) }
            TK(2)
#pragma unroll
            for (int j = 0; j < 4; j++) {
                x[g + j] = and_or<1u << h::TB>(ret[j], x[g + j]);
                put_rec<h::STG>(ret[j], lim, and_xor(ret[j], 0x20000u | h::PM, bin[g + j] * 256 + kb), x[g + j], y[g + j]);
            }
            if (mx >= (int)lim) {
#pragma unroll
                for (int j = 0; j < 4; j++) if ((int)ret[j] >= (int)lim) over |= 1u << (g + j);
            }
        }
        __syncwarp();
        if (lane == 0) mbar_arrive(sb + B_FULL);
        TK(4)
#pragma unroll 1
        while (over) {
            TK_CNT(7)
            const int j = __ffs(over) - 1;
            over &= over - 1;
            slow_rec1(p, pick(j, x), pick(j, y), pick(j, bin));
        }
        slot = slot == D - 1 ? 0 : slot + 1;
        init = h::init(slot, (init + 0x10000u) >> h::TB & 1u);
    };
    int r = 0;
    const int nfast = p.T2 / (NB * NPR) - 1;
#pragma unroll 1
    for (; r < nfast; r++) step(r, BoolC<false>());
#pragma unroll 1
    for (; r < RT; r++) step(r, BoolC<true>());
    TK_OUT
}

__device__ __forceinline__ void stage2(const Params& p, uint32_t sb, int w, int lane, int role, uint32_t base) {
    typedef H<2> h;
    const int RT = p.rounds;
    Reader<1> rd;
    rd.init(p, sb, w, lane, role);
    uint2 rec[J];
    bar_sync(BAR_TABLE, (2 * NC + 1) * 32);
    rd.load(p, rec);
    TK_DECL
#pragma unroll 1
    for (int r = 0; r < RT; r++) {
        rd.check(p, sb, rec, base + r + 1 TK_PASS);
        TK(0)
        uint2 mv[J];
#pragma unroll
        for (int j = 0; j < J; j++) mv[j] = lds64<OFF_M>(sb + (rec[j].y & 0xffffu) * 8);
        uint32_t fl = 0;
#pragma unroll
        for (int j = 0; j < J; j++) fl |= mv[j].y;
        if (fl & 0x40000000u) {
#pragma unroll 1
            for (int j = 0; j < J; j++) {
                const uint2 v = pick(j, mv), w = pick(j, rec);
                if ((v.y & 0x40000000u) && (w.x & 0xffu) < NB) {
                    if (v.x & 0x40000000u) slow_rec1(p, w.x, w.y, lds32(sb + W_ROLE) % NG);
                    else {
                        const float c = bf_hi(w.y), s = __uint_as_float(lds32(sb + W_UNIT)) * 1024.f;
                        side_add(w.x & 0xffu, __byte_perm(w.x, 0u, 0x4413) >> 2, c * (bf_lo(v.x) * s), c * (bf_hi(v.x) * s),
                                 c * (bf_lo(v.y) * s), c * (bf_hi(v.y & 0xbfffffffu) * s));
                    }
                }
            }
#pragma unroll
            for (int j = 0; j < J; j++) if (mv[j].y & 0x40000000u) rec[j].x = NB;
        }
        uint32_t w0[J], w1[J], bin[J], ret[J];
#pragma unroll
        for (int j = 0; j < J; j++) {
            const float c = bf_hi(rec[j].y), MG = 8194.0f;
            const uint32_t x = rec[j].x;
            w0[j] = and_or<0xf000f000u>(x, __byte_perm(__float_as_uint(fmaf(c, bf_lo(mv[j].x), MG)), __float_as_uint(fmaf(c, bf_hi(mv[j].x), MG)), 0x5410));
            w1[j] = and_or<0xf000f000u>(x << 4, __byte_perm(__float_as_uint(fmaf(c, bf_lo(mv[j].y), MG)), __float_as_uint(fmaf(c, bf_hi(mv[j].y), MG)), 0x5410));
            bin[j] = x & 0xffu;
        }
        const uint32_t lim = h::init(rd.wrap() ? D - 1 : 0, rd.want >> H<1>::TB) + 0x20000u;
        rd.advance();
        rd.load(p, rec);
        TK(1)
        mbar_wait(sb + B_OPEN + 8, (r - 1) & 1);
        TK(2)
#pragma unroll
        for (int j = 0; j < J; j++) ret[j] = atoms_add<h::CNT>(sb + bin[j] * 4, h::INC);
        const uint32_t am = and_or<0x30000u>(rd.st << 10 ^ rd.st >> 6, h::PM), kb = and_or<0x30000u>(rd.st << 10, sb);
        int mx = -1;
#pragma unroll
        for (int j = 0; j < J; j++) {
            w1[j] = and_or<1u << h::TB>(ret[j], w1[j]);
            put_rec<0>(ret[j], lim, and_xor(ret[j], am, bin[j] * 128 + kb), w0[j], w1[j]);
            mx = max(mx, (int)ret[j]);
        }
        __syncwarp();
        if (lane == 0) mbar_arrive(sb + B_FULL + 8);
        TK(3)
        if (mx >= (int)lim) {
#pragma unroll 1
            for (int j = 0; j < J; j++)
                if ((int)pick(j, ret) >= (int)lim) slow_rec2(p, pick(j, w0), pick(j, w1), pick(j, bin), __uint_as_float(lds32(sb + W_UNIT)));
        }
        __syncwarp();
        TK(4)
    }
    TK_OUT
}

__device__ __forceinline__ float2 acc_fix(uint32_t old, uint32_t q) {
    const uint32_t u = old + 0x40004000u, n = u + q - 0x08000800u;
    return make_float2((float)((int)(u & 0xffffu) + (int)(q & 0xffffu) - 2048 - (int)(n & 0xffffu)), (float)((int)(u >> 16) + (int)(q >> 16) - 2048 - (int)(n >> 16)));
}
__device__ __forceinline__ void stage3(const Params& p, uint32_t sb, int w, int lane, int role, uint32_t base) {
    const int RT = p.rounds;
    Reader<2> rd;
    rd.init(p, sb, w, lane, role);
    uint2 rec[J];
    bar_sync(BAR_TABLE, (2 * NC + 1) * 32);
    rd.load(p, rec);
    TK_DECL
#pragma unroll 1
    for (int r = 0; r < RT; r++) {
        rd.check(p, sb, rec, base + r + 1 TK_PASS);
        TK(0)
        uint32_t o0[J], o1[J];
        const uint32_t ab = sb - (rd.want >> H<2>::TB);
#pragma unroll
        for (int j = 0; j < J; j++) {
            const uint32_t ad = ab + aux_of(rec[j].x, rec[j].y);
            o0[j] = atoms_add<OFF_ACC0>(ad, (rec[j].x & 0x0fff0fffu) - 0x08000800u);
            o1[j] = atoms_add<OFF_ACC1>(ad, (rec[j].y & 0x0fff0fffu) - 0x08000800u);
        }
        rd.advance();
        uint32_t g = 0;
#pragma unroll
        for (int j = 0; j < J; j++) g |= o0[j] | o1[j];
        if (g & 0x80008000u) {
#pragma unroll 1
            for (int j = 0; j < J; j++) {
                const uint2 w = pick(j, rec);
                const float2 a = acc_fix(pick(j, o0), w.x & 0x0fff0fffu), b = acc_fix(pick(j, o1), w.y & 0x0fff0fffu);
                const float unit = __uint_as_float(lds32(sb + W_UNIT));
                if (a.x != 0.f || a.y != 0.f || b.x != 0.f || b.y != 0.f)
                    side_add(lds32(sb + W_ROLE), aux_of(w.x, w.y) >> 2, a.x * unit, a.y * unit, b.x * unit, b.y * unit);
            }
        }
        rd.load(p, rec);
        TK(1)
    }
    TK_OUT
}

__device__ __forceinline__ uint32_t row_max(uint32_t x, uint32_t y) {
    const uint32_t mx = __vmaxu2(x & 0x7fff7fffu, y & 0x7fff7fffu);
    return max(mx & 0xffffu, mx >> 16);
}
constexpr int EWIN = 5;

__global__ void __launch_bounds__(NTHR, 1) fused_kernel(const Params p) {
    const int tid = threadIdx.x, lane = tid & 31;
    const int hw = __reduce_max_sync(0xffffffffu, tid >> 5);
    const uint32_t sb = __reduce_or_sync(0xffffffffu, (uint32_t)__cvta_generic_to_shared(smem));
    TKX(0)
    uint32_t base = ld_rlx32(&g_base);
    if (tid < NB + NDUM) sts32(sb + OFF_CNT2 + tid * 4, H<2>::init(0, 1) + (tid < NB ? (tid & 7) * 16 : 0x80000000u));
    else if (tid >= 160 && tid < 160 + NG + NDUM) sts32(sb + OFF_CNT1 + (tid - 160) * 4, H<1>::init(0, 1) + (tid < 160 + NG ? (tid & 7) * 16 : 0x80000000u));
    else if (tid >= 256 && tid < 512) sts32(sb + OFF_HIST + (tid - 256) * 4, 0u);
    else if (tid == 544) {
        if (sb & 255u) __trap();
        asm volatile("mbarrier.init.shared::cta.b64 [%0], %1;" ::"r"(sb + B_FULL), "n"(NS1) : "memory");
        asm volatile("mbarrier.init.shared::cta.b64 [%0], %1;" ::"r"(sb + B_FULL + 8), "n"(NC) : "memory");
        for (int i = 0; i < 3; i++) asm volatile("mbarrier.init.shared::cta.b64 [%0], 1;" ::"r"(sb + B_OPEN + i * 8) : "memory");
        sts32(sb + W_PROBE, 0u);
    } else if (tid >= 576 && (tid - 576) * 16 < p.R2 && (blockIdx.x * p.R2 + (tid - 576) * 16) < p.E)
        prefetch_l2(p.m + blockIdx.x * p.R2 + (tid - 576) * 16);
    sts64(sb + OFF_ZERO + tid * 8, 0u, 0u);
    if (hw >= 30) Prefill<1>(lane).run(sb + OFF_H1 + H<1>::win(hw), nulls<1>(lane));
    __syncthreads();

    if (hw < NS1) {
        if (hw < NS1 - 1) stage1<4>(p, sb, hw * 128 + lane, lane);
        else stage1<NPR / 32 - (NS1 - 1) * 4>(p, sb, hw * 128 + lane, lane);
        __threadfence();
        bar_arrive(BAR_DONE, (NS1 + NC + 2) * 32);
    } else if (hw == W_M1) {
        base = __reduce_or_sync(0xffffffffu, base);
        bar_sync(BAR_PROBE, (2 * NC + 1) * 32);
        {
            const uint32_t raw = lds32(sb + W_PROBE), side = raw >> (D * NPAIR);
            if (lane < 2)
                asm volatile("st.relaxed.gpu.global.v2.u32 [%0], {%1,%2};" ::"l"(p.ring + REF + REF_PUB + lane * 4096 + blockIdx.x * 8), "r"(base),
                             "r"(side ? ~raw | 0x80000000u : raw) : "memory");
            uint32_t best = 0;
#pragma unroll 1
            for (int e = 11 + lane; e <= 230; e += 32) {
                uint32_t c = 0;
#pragma unroll
                for (int i = 0; i < EWIN; i++) c += lds32(sb + OFF_HIST + (e - i) * 4);
                best = max(best, c << 8 | (255 - e));
            }
            const uint32_t e = 255 - (__reduce_max_sync(0xffffffffu, best) & 255u);
            if (lane == 0) { sts32(sb + W_EXP, e); sts32(sb + W_UNIT, (e - 10) << 23); }
            uint2 pb[5];
            int it = 0;
            while (true) {
                bool ok = true;
#pragma unroll
                for (int j = 0; j < 5; j++) { pb[j] = ld_rlx64(p.ring + REF + REF_PUB + side * 4096 + min(lane + 32 * j, NB - 1) * 8); ok = ok && pb[j].x == base; }
                if (__all_sync(0xffffffffu, ok)) break;
                __nanosleep(50);
                if (++it > SPIN_LIMIT) __trap();
            }
            uint32_t bal[5], n1 = 0;
#pragma unroll
            for (int j = 0; j < 5; j++) { bal[j] = __ballot_sync(0xffffffffu, lane + 32 * j < NB && (int)pb[j].y < 0); n1 += __popc(bal[j]); }
            uint32_t before = 0;
#pragma unroll
            for (int j = 0; j < 5; j++) {
                const uint32_t b = lane + 32 * j, k = before + __popc(bal[j] & ((1u << lane) - 1u)), ro = (int)pb[j].y < 0 ? NB - n1 + k : b - k;
                if (b < NB) sts64(sb + OFF_MAP + ro * 8, pb[j].y, b);
                if (b == blockIdx.x) sts32(sb + W_ROLE, ro);
                before += __popc(bal[j]);
            }
        }
        bar_sync(BAR_ROLE, (2 * NC + 2) * 32);
        manager<1>(p, sb, lane, __reduce_max_sync(0xffffffffu, lds32(sb + W_ROLE)), base);
        bar_arrive(BAR_H1, (NS1 + 1) * 32);
        __threadfence();
        bar_arrive(BAR_DONE, (NS1 + NC + 2) * 32);
    } else if (hw == W_M2) {
        base = __reduce_or_sync(0xffffffffu, base);
        uint32_t* flag = reinterpret_cast<uint32_t*>(p.ring + REF + REF_FLAG + (lane & 1) * 4096) + blockIdx.x;
        bar_sync(BAR_ROLE, (2 * NC + 2) * 32);
        const int role = __reduce_max_sync(0xffffffffu, lds32(sb + W_ROLE));
        asm volatile("fence.proxy.async.shared::cta;" ::: "memory");
        if (lane < D * 8) {
            const int k = lane & 7, pair = (lane >> 3) * NPAIR + min(k, 6);
            const uint32_t half = k < 4 ? (lds32(sb + OFF_MAP + role * 8) >> pair & 1u) ^ (role >= NG) : k == 7;
            asm volatile("cp.async.bulk.global.shared::cta.bulk_group [%0], [%1], %2;" ::"l"(p.ring + (uint32_t)((blockIdx.x * D * NPAIR + pair) * PAIR + half * 4096)),
                         "r"(sb + OFF_ZERO), "r"(k < 4 ? 4096 : k < 6 ? 8192 : 1536) : "memory");
            asm volatile("cp.async.bulk.commit_group;" ::: "memory");
            asm volatile("cp.async.bulk.wait_group 0;" ::: "memory");
            __threadfence();
        }
        __syncwarp();
        if (lane < 2) { __threadfence(); st_rlx32(flag, base + 1); }
        bar_arrive(BAR_CLEAR, 64);
#pragma unroll 1
        for (int i = 0; i < 3; i++) Prefill<2>(lane).run(sb + H<2>::win(i), nulls<2>(lane));
        wait_flags(p, sb, lane, base + 1, 1);
        bar_arrive(BAR_TABLE, (2 * NC + 1) * 32);
        manager<2>(p, sb, lane, role, base);
        __threadfence();
        bar_sync(BAR_DONE, (NS1 + NC + 2) * 32);
        if (lane < 2) { __threadfence(); st_rlx32(flag, base + 2); }
    } else {
        const int pw = __reduce_max_sync(0xffffffffu, hw < W_M1 ? hw - NS1 : hw - NS1 - 1), ct = pw * 32 + lane;
        constexpr int CT = 2 * NC * 32;
        uint2 sm3[3];
#pragma unroll
        for (int u = 0; u < 3; u++) sm3[u] = __ldg(p.m + (uint32_t)(ct * 3 + u) * (uint32_t)p.E / (3 * CT));
        if (lane == 0) {
            const uint32_t v = near_half(p.ring + (uint32_t)(pw < D * NPAIR ? (blockIdx.x * D * NPAIR + pw) * PAIR : REF + (blockIdx.x & 63) * 32), p.zero);
            asm volatile("red.shared.or.b32 [%0], %1;" ::"r"(sb + W_PROBE), "r"(v << pw) : "memory");
        }
        __syncwarp();
#pragma unroll
        for (int u = 0; u < 3; u++) {
            const uint32_t mx = row_max(sm3[u].x, sm3[u].y);
            if (mx) atoms_add<OFF_HIST>(sb + (mx >> 7) * 4, 1u);
        }
        TKX(1)
        bar_arrive(BAR_PROBE, (2 * NC + 1) * 32);
        base = __reduce_or_sync(0xffffffffu, base);
        for (int i = ct; i < R2MAX / 2; i += CT) reinterpret_cast<uint4*>(smem + OFF_ACC0)[i] = make_uint4(0x40004000u, 0x40004000u, 0x40004000u, 0x40004000u);
        bar_sync(BAR_ROLE, (2 * NC + 2) * 32);
        const int role = __reduce_max_sync(0xffffffffu, lds32(sb + W_ROLE));
        TKX(2)
        {
            const int e = lds32(sb + W_EXP), q0 = (role >= NG ? role - NG : role) * (p.R1 >> 1), nq = min(p.R1 >> 1, (p.E >> 1) - q0);
            const uint32_t sc = (uint32_t)(254 - e) * 0x800080u;
            constexpr int CH = (R1MAX / 2 + CT - 1) / CT;
            uint4 v[CH];
#pragma unroll
            for (int u = 0; u < CH; u++) v[u] = __ldg(reinterpret_cast<const uint4*>(p.m) + min(q0 + ct + u * CT, (p.E >> 1) - 1));
            auto conv = [&](uint32_t& x, uint32_t& y) {
                const uint32_t mx = row_max(x, y);
                const int d = e - (int)(mx >> 7);
                x = hmul_bf2(x, sc); y = hmul_bf2(y, sc);
                if (d >= EWIN) y |= 0x40000000u;
                if (d < 0 || (d >= EWIN && e > 127)) { x = 0x40000000u; y = x; }
                if (mx == 0) { x = 0; y = 0; }
            };
#pragma unroll
            for (int u = 0; u < CH; u++) {
                conv(v[u].x, v[u].y); conv(v[u].z, v[u].w);
                if (ct + u * CT < nq) sts128<OFF_M>(sb + (ct + u * CT) * 16, v[u]);
            }
        }
        TKX(3)
        if (hw < W_M1) {
            stage2(p, sb, pw, lane, role, base);
            __threadfence();
            bar_arrive(BAR_DONE, (NS1 + NC + 2) * 32);
        } else {
            stage3(p, sb, pw - NC, lane, role, base);
            __threadfence();
        }
    }
    TKX(4)
    epilogue(p, sb, base);
}

__global__ void fb_scatter(const uint2* __restrict__ m, const int* __restrict__ idx_in, const int* __restrict__ idx_out,
                           const uint16_t* __restrict__ angle, const __nv_bfloat16* __restrict__ ang_freq, int T, int e0, int e1) {
    const uint32_t fb = *reinterpret_cast<const uint16_t*>(ang_freq);
    for (long long t = blockIdx.x * (long long)blockDim.x + threadIdx.x; t < T; t += (long long)gridDim.x * blockDim.x) {
        int o = idx_out[t];
        if (o < e0 || o >= e1) continue;
        float c = bf16r(cos_bf(hmul_bf2(angle[t], fb) & 0xffffu));
        uint2 v = __ldg(m + idx_in[t]);
        red4(&g_ovf[o - e0], c * bf_lo(v.x), c * bf_hi(v.x), c * bf_lo(v.y), c * bf_hi(v.y));
    }
}
__global__ void fb_final(const Params p, int e0, int e1) {
    int e = e0 + blockIdx.x * blockDim.x + threadIdx.x;
    if (e >= e1) return;
    float4 a4 = g_ovf[e - e0];
    g_ovf[e - e0] = make_float4(0.f, 0.f, 0.f, 0.f);
    float a[4] = {a4.x, a4.y, a4.z, a4.w};
    float d = __bfloat162float(p.dist[e]);
    float g[4] = {0, 0, 0, 0}, h[4] = {0, 0, 0, 0};
    for (int r = 0; r < 8; r++) {
        float df = bf16r(d - __bfloat162float(p.centers[r]));
        float rb = bf16r(expf(bf16r(-10.0f * bf16r(df * df))));
        for (int k = 0; k < 4; k++) {
            g[k] += rb * __bfloat162float(p.w_sbf[r * 4 + k]);
            h[k] += rb * __bfloat162float(p.w_rbf[r * 4 + k]);
        }
    }
    float ag[4];
    for (int k = 0; k < 4; k++) {
        float s = 0.f;
        for (int j = 0; j < 4; j++) s += a[j] * __bfloat162float(p.w_down[j * 4 + k]);
        ag[k] = bf16r(s * g[k]);
    }
    uint2 mv = p.m[e];
    float mm[4] = {bf_lo(mv.x), bf_hi(mv.x), bf_lo(mv.y), bf_hi(mv.y)};
    __nv_bfloat16 o[4];
    for (int k = 0; k < 4; k++) {
        float u = 0.f;
        for (int j = 0; j < 4; j++) u += ag[j] * __bfloat162float(p.w_up[j * 4 + k]);
        o[k] = __float2bfloat16_rn(mm[k] + bf16r(bf16r(u) * bf16r(h[k])));
    }
    p.out[e] = *reinterpret_cast<uint2*>(o);
}

}

static bool exact_div(int E, int lo, int hi, int* R, uint32_t* magic) {
    for (int r = lo + (lo & 1); r <= hi; r += 2) {
        unsigned long long mg = ((1ull << 32) + r - 1) / r, err = mg * r - (1ull << 32);
        if (err * (unsigned long long)E < (1ull << 32)) { *R = r; *magic = (uint32_t)mg; return true; }
    }
    return false;
}

extern "C" void kernel_launch(void* const* d_in, const int* in_sizes, int n_in, void* d_out, int out_size) {
    typedef const __nv_bfloat16* B;
    Params p;
    p.m = (const uint2*)d_in[0]; p.idx_in = (const uint2*)d_in[1]; p.idx_out = (const uint2*)d_in[2]; p.dist = (B)d_in[3];
    p.angle = (const uint32_t*)d_in[4]; p.centers = (B)d_in[5]; p.ang_freq = (B)d_in[6]; p.w_rbf = (B)d_in[7]; p.w_sbf = (B)d_in[8];
    p.w_down = (B)d_in[9]; p.w_up = (B)d_in[10]; p.out = (uint2*)d_out;
    p.E = in_sizes[3]; p.T = in_sizes[1]; p.T2 = p.T >> 1; p.zero = 0;
    p.R1 = p.R2 = p.rounds = p.lastn = 0; p.mg1 = p.mg2 = p.k1 = p.k2 = 0;
    static int ok = -1;
    static unsigned char* ring = nullptr;
    if (ok < 0) {
        void* ra = nullptr;
        cudaGetSymbolAddress(&ra, g_ring);
        ring = reinterpret_cast<unsigned char*>(((uintptr_t)ra + PAIR - 1) & ~(uintptr_t)(PAIR - 1));
        int dev = 0, sms = 0, occ = 0;
        cudaGetDevice(&dev);
        cudaDeviceGetAttribute(&sms, cudaDevAttrMultiProcessorCount, dev);
        cudaError_t e = cudaFuncSetAttribute(fused_kernel, cudaFuncAttributeMaxDynamicSharedMemorySize, SMEM_BYTES);
        if (e == cudaSuccess) e = cudaOccupancyMaxActiveBlocksPerMultiprocessor(&occ, fused_kernel, NTHR, SMEM_BYTES);
        ok = (e == cudaSuccess && occ >= 1 && sms >= NB) ? 1 : 0;
        (void)cudaGetLastError();
    }
    p.ring = ring;
    const bool fused = ok == 1 && p.E <= EMAX && p.E >= 2 * NB && p.E % 2 == 0 && p.T >= 2 && exact_div(p.E, (p.E + NG - 1) / NG, R1MAX, &p.R1, &p.mg1) &&
                       exact_div(p.E, (p.E + NB - 1) / NB, R2MAX, &p.R2, &p.mg2);
    if (fused) {
        p.k1 = 0u - (uint32_t)p.R1; p.k2 = 0u - 4u * (uint32_t)p.R2;
        const int per = NB * NPR;
        int full = p.T2 / per, rest = p.T2 - full * per;
        p.lastn = (rest + NB - 1) / NB;
        if (p.lastn > NPR / 2) { full++; p.lastn = 0; }
        if (full < D) { full = D; p.lastn = 0; }
        p.rounds = full + 1;
        fused_kernel<<<NB, NTHR, SMEM_BYTES>>>(p);
    } else {
        for (int e0 = 0; e0 < p.E; e0 += EMAX) {
            int e1 = p.E - e0 < EMAX ? p.E : e0 + EMAX;
            fb_scatter<<<1056, 256>>>(p.m, (const int*)d_in[1], (const int*)d_in[2], (const uint16_t*)d_in[4], p.ang_freq, p.T, e0, e1);
            fb_final<<<(e1 - e0 + 255) / 256, 256>>>(p, e0, e1);
        }
    }
}
```

```cpp
#include <cuda_runtime.h>
#include <cuda_bf16.h>
#include <stdint.h>

namespace {

constexpr int NB = 132, NG = 66;
constexpr int R2MAX = 6062, R1MAX = 12124;
constexpr int EMAX = NB * R2MAX;
constexpr int NTHR = 1024;
constexpr int NS1 = 8, NC = 11, J = 6;
#define TILES 15
constexpr int NPR = TILES * 64;
#define RING_DEPTH 3
constexpr int D = RING_DEPTH;
constexpr int NPAIR = 7, PAIR = 8192, SLOT = NPAIR * PAIR;
constexpr int WIN = 16896;
constexpr int NDUM = 16;

constexpr int OFF_ACC = WIN, OFF_BAR = OFF_ACC + R2MAX * 8;
constexpr int OFF_H1 = 0x10000 + WIN, OFF_M = OFF_H1 + WIN, OFF_WSM = OFF_M + R1MAX * 8;
constexpr int OFF_CNT1 = OFF_H1 + 0x20000 + WIN, OFF_CNT2 = OFF_CNT1 + (NG + NDUM + 2) * 4, OFF_MAP = OFF_CNT2 + (NB + NDUM) * 4;
constexpr int OFF_HIST = 0x30000, OFF_ZERO = 0x10000;
constexpr int OFF_CADR = OFF_WSM + 128;
constexpr int SMEM_BYTES = OFF_MAP + NB * 8;
static_assert(SMEM_BYTES <= 232448 && OFF_BAR + 64 <= 0x10000 && OFF_CADR + 96 <= 0x30000, "smem");
static_assert(OFF_BAR % 8 == 0 && OFF_MAP % 8 == 0 && OFF_WSM % 16 == 0 && OFF_CNT2 % 16 == 0, "align");
static_assert(NC * J == NG && D == 3 && D * NPAIR + 1 == 2 * NC && NC * 32 * 6 * 16 == 2 * WIN, "shape");

template <int HOP> struct H {
    static constexpr int S = HOP == 1 ? 32 : 16, NBIN = HOP == 1 ? NG : NB, CAP = HOP == 1 ? 48 : 32, PRE = HOP == 1 ? 16 : 4, SH = HOP == 1 ? 11 : 12;
    static constexpr int TB = HOP == 1 ? 20 : 28, CNT = HOP == 1 ? OFF_CNT1 : OFF_CNT2, STG = HOP == 1 ? OFF_H1 : 0;
    static constexpr uint32_t INC = (1u << SH) + 8u, PM = (S - 1) * 8;
    static __device__ __forceinline__ uint32_t init(int slot, uint32_t gen) { return 0x30000u | gen << TB | (slot == D - 1 ? (1u << TB) - (1u << 18) : 0u); }
    static __device__ __forceinline__ uint32_t win(int r) { return HOP == 1 ? (r & 1) << 17 : (0x310u >> (r % 3 * 4) & 3u) << 16; }
};

__device__ __align__(256) unsigned char g_ring[(size_t)(NB * D * NPAIR + 2) * PAIR];
constexpr int REF = NB * D * SLOT;
constexpr int REF_PUB = 2048;
constexpr int REF_FLAG = 3136;
constexpr int RPAD = 6064, DROW = 6144;
__device__ __align__(128) uint8_t g_dirty[NB * DROW];
__device__ uint32_t g_base = 2;
__device__ __align__(128) float4 g_ovf[NB * RPAD];

struct Params {
    const uint2* m; const uint2* idx_in; const uint2* idx_out; const __nv_bfloat16* dist; const uint32_t* angle;
    const __nv_bfloat16* centers; const __nv_bfloat16* ang_freq; const __nv_bfloat16* w_rbf; const __nv_bfloat16* w_sbf;
    const __nv_bfloat16* w_down; const __nv_bfloat16* w_up; uint2* out; unsigned char* ring;
    int E, T, T2, R1, R2, rounds, lastn; uint32_t mg1, mg2, k1, k2, zero;
};

__device__ __forceinline__ float bf16r(float x) { return __bfloat162float(__float2bfloat16_rn(x)); }
__device__ __forceinline__ float bf_lo(uint32_t v) { return __uint_as_float(v << 16); }
__device__ __forceinline__ float bf_hi(uint32_t v) { return __uint_as_float(v & 0xffff0000u); }
__device__ __forceinline__ void red4(float4* a, float x, float y, float z, float w) {
    asm volatile("red.global.add.v4.f32 [%0], {%1,%2,%3,%4};" ::"l"(a), "f"(x), "f"(y), "f"(z), "f"(w) : "memory");
}
__device__ __forceinline__ void bar_sync(int id, int n) { __syncwarp(); asm volatile("bar.sync %0, %1;" ::"r"(id), "r"(n) : "memory"); }
__device__ __forceinline__ void bar_arrive(int id, int n) { __syncwarp(); asm volatile("bar.arrive %0, %1;" ::"r"(id), "r"(n) : "memory"); }
template <int OFF> __device__ __forceinline__ uint32_t atoms_add(uint32_t addr, uint32_t v) {
    uint32_t r; asm volatile("atom.shared.add.u32 %0, [%1+%3], %2;" : "=r"(r) : "r"(addr), "r"(v), "n"(OFF) : "memory"); return r;
}
__device__ __forceinline__ void sts64(uint32_t addr, uint32_t x, uint32_t y) {
    asm volatile("st.shared.v2.u32 [%0], {%1,%2};" ::"r"(addr), "r"(x), "r"(y) : "memory");
}
__device__ __forceinline__ void sts32(uint32_t addr, uint32_t x) { asm volatile("st.shared.u32 [%0], %1;" ::"r"(addr), "r"(x) : "memory"); }
template <int OFF = 0> __device__ __forceinline__ uint2 lds64(uint32_t addr) {
    uint2 v; asm volatile("ld.shared.v2.u32 {%0,%1}, [%2+%3];" : "=r"(v.x), "=r"(v.y) : "r"(addr), "n"(OFF) : "memory"); return v;
}
__device__ __forceinline__ uint32_t lds32(uint32_t addr) {
    uint32_t v; asm volatile("ld.shared.u32 %0, [%1];" : "=r"(v) : "r"(addr) : "memory"); return v;
}
__device__ __forceinline__ uint32_t ld_rlx32(const uint32_t* p) {
    uint32_t v; asm volatile("ld.relaxed.gpu.global.u32 %0, [%1];" : "=r"(v) : "l"(p) : "memory"); return v;
}
__device__ __forceinline__ uint2 ld_rlx64(const void* p) {
    uint2 v; asm volatile("ld.relaxed.gpu.global.v2.u32 {%0,%1}, [%2];" : "=r"(v.x), "=r"(v.y) : "l"(p) : "memory"); return v;
}
__device__ __forceinline__ float4 ld_rlx128f(const float4* p) {
    float4 v; asm volatile("ld.relaxed.gpu.global.v4.f32 {%0,%1,%2,%3}, [%4];" : "=f"(v.x), "=f"(v.y), "=f"(v.z), "=f"(v.w) : "l"(p) : "memory"); return v;
}
__device__ __forceinline__ void st_rlx32(uint32_t* p, uint32_t v) { asm volatile("st.relaxed.gpu.global.u32 [%0], %1;" ::"l"(p), "r"(v) : "memory"); }
__device__ __forceinline__ uint32_t hmul_bf2(uint32_t a, uint32_t b) {
    uint32_t r; asm("mul.rn.bf16x2 %0, %1, %2;" : "=r"(r) : "r"(a), "r"(b)); return r;
}
__device__ __forceinline__ uint32_t hsub_bf2(uint32_t a, uint32_t b) {
    uint32_t r; asm("sub.rn.bf16x2 %0, %1, %2;" : "=r"(r) : "r"(a), "r"(b)); return r;
}
constexpr int SPIN_LIMIT = 1 << 22;

__constant__ uint32_t c_inv2pi[8] = {0u, 0x28be60dbu, 0x9391054au, 0x7f09d5f4u, 0x7d4d3770u, 0x36d8a566u, 0x4f10e410u, 0x7f9458eau};
constexpr uint32_t BIGX = 0x4280u;
__device__ __forceinline__ float cos_big(uint32_t xb) {
    uint32_t e = (xb >> 7) & 0xffu, M = (xb & 0x7fu) | 0x80u;
    uint32_t pp = e - 102u;
    uint32_t wi = pp >> 5;
    uint32_t t0 = c_inv2pi[wi], t1 = c_inv2pi[wi + 1], t2 = c_inv2pi[wi + 2];
    uint32_t f = M * __funnelshift_l(t1, t0, pp) + __umulhi(M, __funnelshift_l(t2, t1, pp));
    float c = __cosf((float)(int)f * 1.4629180792671596e-9f);
    return e == 255u ? __uint_as_float(0x7fc00000u) : c;
}
__device__ __forceinline__ float cos_bf(uint32_t xb) {
    return (xb & 0x7fffu) > BIGX ? cos_big(xb) : __cosf(__uint_as_float(xb << 16));
}
__device__ __forceinline__ uint32_t pack_bf2(float lo, float hi) {
    uint32_t r; asm("cvt.rn.bf16x2.f32 %0, %1, %2;" : "=r"(r) : "f"(hi), "f"(lo)); return r;
}
template <int N> __device__ __forceinline__ uint32_t pick(int k, const uint32_t (&a)[N]) {
    uint32_t v = a[0];
#pragma unroll
    for (int i = 1; i < N; i++) if (k == i) v = a[i];
    return v;
}
template <int N> __device__ __forceinline__ uint2 pick(int k, const uint2 (&a)[N]) {
    uint2 v = a[0];
#pragma unroll
    for (int i = 1; i < N; i++) if (k == i) v = a[i];
    return v;
}
__device__ __forceinline__ void side_add(uint32_t bin, uint32_t row, float a, float b, float c, float d) {
    red4(&g_ovf[bin * RPAD + row], a, b, c, d);
    g_dirty[bin * DROW + row] = 1;
}
__device__ __forceinline__ void slow_triplet(const Params& p, uint32_t ii, uint32_t oo, float c) {
    const uint2 v = __ldg(p.m + ii);
    const uint32_t bo = __umulhi(oo, p.mg2);
    side_add(bo, oo - bo * p.R2, c * bf_lo(v.x), c * bf_hi(v.x), c * bf_lo(v.y), c * bf_hi(v.y));
}
__device__ __forceinline__ void slow_rec1(const Params& p, uint32_t x, uint32_t y, uint32_t bin) {
    const uint2 v = __ldg(p.m + bin * p.R1 + (y & 0xffffu));
    const float c = bf_hi(y);
    side_add(x & 0xffu, __byte_perm(x, 0u, 0x4413) >> 2, c * bf_lo(v.x), c * bf_hi(v.x), c * bf_lo(v.y), c * bf_hi(v.y));
}
__device__ __forceinline__ uint32_t aux_of(uint32_t w0, uint32_t w1) {
    uint32_t u; asm("lop3.b32 %0, %1, %2, 0xf000f000, 0xe4;" : "=r"(u) : "r"(w0), "r"(w1 >> 4));
    return __byte_perm(u, 0u, 0x4413);
}
__device__ __forceinline__ void slow_rec2(const Params& p, uint32_t w0, uint32_t w1, uint32_t bin, float unit) {
    side_add(bin, aux_of(w0, w1) >> 2, (float)((int)(w0 & 0xfffu) - 2048) * unit, (float)((int)(w0 >> 16 & 0xfffu) - 2048) * unit,
             (float)((int)(w1 & 0xfffu) - 2048) * unit, (float)((int)(w1 >> 16 & 0xfffu) - 2048) * unit);
}
template <uint32_t M> __device__ __forceinline__ uint32_t and_or(uint32_t a, uint32_t c) {
    uint32_t r; asm("lop3.b32 %0, %1, %2, %3, 0xea;" : "=r"(r) : "r"(a), "n"(M), "r"(c)); return r;
}
__device__ __forceinline__ uint32_t and_xor(uint32_t a, uint32_t m, uint32_t c) {
    uint32_t r; asm("lop3.b32 %0, %1, %2, %3, 0x6a;" : "=r"(r) : "r"(a), "r"(m), "r"(c)); return r;
}
__device__ __forceinline__ uint2 ld_in(const uint2* a) {
    uint2 v; asm volatile("ld.global.nc.L1::no_allocate.v2.u32 {%0,%1}, [%2];" : "=r"(v.x), "=r"(v.y) : "l"(a)); return v;
}
__device__ __forceinline__ uint32_t ld_in(const uint32_t* a) {
    uint32_t v; asm volatile("ld.global.nc.L1::no_allocate.u32 %0, [%1];" : "=r"(v) : "l"(a)); return v;
}
template <int OFF> __device__ __forceinline__ void put_rec(uint32_t ret, uint32_t lim, uint32_t addr, uint32_t x, uint32_t y) {
    asm volatile("{ .reg .pred q; setp.lt.u32 q, %0, %1; @q st.shared.v2.u32 [%2+%5], {%3,%4}; }" ::"r"(ret), "r"(lim), "r"(addr), "r"(x), "r"(y), "n"(OFF) : "memory");
}
__device__ __forceinline__ uint32_t mbar_try(uint32_t mb, uint32_t parity) {
    uint32_t ok;
    asm volatile("{ .reg .pred q; mbarrier.try_wait.parity.shared::cta.b64 q, [%1], %2; selp.u32 %0, 1, 0, q; }" : "=r"(ok) : "r"(mb), "r"(parity) : "memory");
    return ok;
}
__device__ __forceinline__ void mbar_wait(uint32_t mb, uint32_t parity) {
    if (!mbar_try(mb, parity)) {
        int it = 0;
        while (!mbar_try(mb, parity)) if (++it > SPIN_LIMIT) __trap();
    }
}
__device__ __forceinline__ void mbar_arrive(uint32_t mb) { asm volatile("mbarrier.arrive.shared::cta.b64 _, [%0];" ::"r"(mb) : "memory"); }
constexpr int B_FULL = OFF_BAR, B_OPEN = OFF_BAR + 16, B_FREE = OFF_BAR + 32, W_PROBE = OFF_BAR + 48, W_ROLE = OFF_BAR + 52, W_EXP = OFF_BAR + 56, W_UNIT = OFF_BAR + 60;
enum { BAR_PROBE = 1, BAR_ROLE, BAR_CLEAR, BAR_TABLE, BAR_H1, BAR_DONE };
constexpr int W_M1 = NS1 + NC, W_M2 = 31;

extern __shared__ __align__(1024) unsigned char smem[];
#define TK_DECL
#define TK(i)
#define TK_CNT(i)
#define TK_OUT
#define TK_ARG
#define TK_PASS
#define TKX(i)

constexpr int NR = (R2MAX + NTHR - 1) / NTHR;
__device__ __forceinline__ void gates(const Params& p, int e0, int e1, int e2, uint4* gh) {
    constexpr int NH = 3;
    const int e[NH] = {e0, e1, e2};
    uint32_t dd[NH];
    float g[NH][4], h[NH][4];
#pragma unroll
    for (int u = 0; u < NH; u++) {
        dd[u] = reinterpret_cast<const uint16_t*>(p.dist)[min(e[u], p.E - 1)] * 0x10001u;
#pragma unroll
        for (int k = 0; k < 4; k++) { g[u][k] = 0.f; h[u][k] = 0.f; }
    }
#pragma unroll 1
    for (int r2 = 0; r2 < 4; r2++) {
        const uint32_t cen = __ldg(reinterpret_cast<const uint32_t*>(p.centers) + r2);
        const uint4 s4 = __ldg(reinterpret_cast<const uint4*>(p.w_sbf) + r2), r4 = __ldg(reinterpret_cast<const uint4*>(p.w_rbf) + r2);
        const uint32_t sw[4] = {s4.x, s4.y, s4.z, s4.w}, rw[4] = {r4.x, r4.y, r4.z, r4.w};
        uint32_t rb[NH];
#pragma unroll
        for (int u = 0; u < NH; u++) {
            const uint32_t df = hsub_bf2(dd[u], cen);
            const uint32_t ar = hmul_bf2(hmul_bf2(df, df), 0xc120c120u);
            rb[u] = pack_bf2(__expf(bf_lo(ar)), __expf(bf_hi(ar)));
        }
#pragma unroll
        for (int i = 0; i < 8; i++) {
            const float ws = i & 1 ? bf_hi(sw[i >> 1]) : bf_lo(sw[i >> 1]), wr = i & 1 ? bf_hi(rw[i >> 1]) : bf_lo(rw[i >> 1]);
#pragma unroll
            for (int u = 0; u < NH; u++) {
                const float x = i < 4 ? bf_lo(rb[u]) : bf_hi(rb[u]);
                g[u][i & 3] += x * ws;
                h[u][i & 3] += x * wr;
            }
        }
    }
#pragma unroll
    for (int u = 0; u < NH; u++)
        gh[u] = make_uint4(pack_bf2(g[u][0], g[u][1]), pack_bf2(g[u][2], g[u][3]), pack_bf2(h[u][0], h[u][1]), pack_bf2(h[u][2], h[u][3]));
}
__device__ __forceinline__ void prefetch_l2(const void* a) { asm volatile("prefetch.global.L2 [%0];" ::"l"(a)); }
__device__ __forceinline__ uint4* gate_slot(int k) { return reinterpret_cast<uint4*>(smem + OFF_H1 + (k >= WIN / 16 ? 0x20000 - WIN : 0)) + k; }
__device__ __forceinline__ void wait_flags(const Params& p, uint32_t sb, int lane, uint32_t need, uint32_t span) {
    const unsigned char* f = p.ring + REF + REF_FLAG + (lds32(sb + W_PROBE) >> (D * NPAIR) << 12);
    int it = 0;
    while (true) {
        const float4 a = ld_rlx128f(reinterpret_cast<const float4*>(f) + lane);
        const uint32_t b = ld_rlx32(reinterpret_cast<const uint32_t*>(f) + 128 + (lane & 3));
        const uint32_t d = max(max(max(__float_as_uint(a.x) - need, __float_as_uint(a.y) - need), max(__float_as_uint(a.z) - need, __float_as_uint(a.w) - need)), b - need);
        if (__all_sync(0xffffffffu, d <= span)) break;
        __nanosleep(50);
        if (++it > SPIN_LIMIT) __trap();
    }
    __threadfence();
}
__device__ __forceinline__ void epilogue(const Params& p, uint32_t sb, uint32_t base) {
    int tid;
    asm volatile("mov.u32 %0, %%tid.x;" : "=r"(tid));
    const int role = lds32(sb + W_ROLE), row0 = role * p.R2, nrows = min(p.R2, p.E - row0), hw = tid >> 5;
    const bool s3 = hw > W_M1 && hw < W_M2;
    constexpr int T3 = (W_M1 + 1) * 32, N3 = NC * 32;
    uint4 gh[NR];
    if (hw < NS1) {
        if (tid * 64 < nrows) prefetch_l2(p.dist + row0 + tid * 64);
        for (int i = tid * 16; i < nrows; i += NS1 * 32 * 16) prefetch_l2(p.m + row0 + i);
    }
    if (!s3) gates(p, row0 + tid + 3 * NTHR, row0 + tid + 4 * NTHR, row0 + tid + 5 * NTHR, gh + 3);
    if (hw < NS1) {
        bar_sync(BAR_H1, (NS1 + 1) * 32);
#pragma unroll 1
        for (int k0 = tid; k0 < NR * N3; k0 += 3 * NS1 * 32) {
            int k[3], e[3];
#pragma unroll
            for (int u = 0; u < 3; u++) { k[u] = k0 + u * NS1 * 32; e[u] = row0 + T3 + k[u] + k[u] / N3 * (NTHR - N3); }
            gates(p, e[0], e[1], e[2], gh);
#pragma unroll
            for (int u = 0; u < 3; u++) if (k[u] < NR * N3) *gate_slot(k[u]) = gh[u];
        }
#pragma unroll
        for (int i = tid; i < DROW / 8; i += NS1 * 32) {
            const uint2 f = ld_rlx64(g_dirty + role * DROW + i * 8);
            if (f.x | f.y) prefetch_l2(g_ovf + role * RPAD + i * 8);
        }
    }
    if (!s3) gates(p, row0 + tid, row0 + tid + NTHR, row0 + tid + 2 * NTHR, gh);
    if (hw == W_M1) {
        reinterpret_cast<float*>(smem + OFF_WSM)[tid & 31] = __bfloat162float(tid & 16 ? p.w_up[tid & 15] : p.w_down[tid & 15]);
        wait_flags(p, sb, tid & 31, base + 2, 0);
    }
    TKX(5)
    bar_sync(0, NTHR);
    TKX(6)
    uint32_t dirty = 0;
#pragma unroll
    for (int it = 0; it < NR; it++) {
        uint32_t f;
        asm volatile("ld.relaxed.gpu.global.u8 %0, [%1];" : "=r"(f) : "l"(g_dirty + role * DROW + tid + it * NTHR) : "memory");
        dirty |= f << it;
    }
    if (s3) {
#pragma unroll
        for (int it = 0; it < NR; it++) gh[it] = *gate_slot(tid - T3 + it * N3);
    }
    if (tid == W_M1 * 32 && blockIdx.x == 0) g_base = base + p.rounds + 8;
    const float unit = *reinterpret_cast<const float*>(smem + W_UNIT);
    const float4* w4 = reinterpret_cast<const float4*>(smem + OFF_WSM);
#pragma unroll
    for (int i0 = 0; i0 < NR; i0 += 3) {
        uint2 mv[3];
        float4 o[3];
#pragma unroll
        for (int u = 0; u < 3; u++) mv[u] = __ldg(p.m + min(row0 + tid + (i0 + u) * NTHR, p.E - 1));
#pragma unroll
        for (int u = 0; u < 3; u++) {
            o[u] = make_float4(0.f, 0.f, 0.f, 0.f);
            if (dirty >> (i0 + u) & 1) o[u] = ld_rlx128f(&g_ovf[role * RPAD + tid + (i0 + u) * NTHR]);
        }
#pragma unroll
        for (int u = 0; u < 3; u++) {
            const int it = i0 + u, i = tid + it * NTHR;
            if (dirty >> it & 1) { g_ovf[role * RPAD + i] = make_float4(0.f, 0.f, 0.f, 0.f); g_dirty[role * DROW + i] = 0; }
            if (i < nrows) {
                const uint2 ac = reinterpret_cast<const uint2*>(smem + OFF_ACC)[i];
                const uint32_t u0 = ac.x + 0x40004000u, u1 = ac.y + 0x40004000u;
                const float a[4] = {(float)((int)(u0 & 0xffffu) - 0x8000) * unit + o[u].x, (float)((int)(u0 >> 16) - 0x8000) * unit + o[u].y,
                                    (float)((int)(u1 & 0xffffu) - 0x8000) * unit + o[u].z, (float)((int)(u1 >> 16) - 0x8000) * unit + o[u].w};
                float sd[4] = {0, 0, 0, 0}, uu[4] = {0, 0, 0, 0};
#pragma unroll
                for (int j = 0; j < 4; j++) {
                    float4 w = w4[j];
                    sd[0] += a[j] * w.x; sd[1] += a[j] * w.y; sd[2] += a[j] * w.z; sd[3] += a[j] * w.w;
                }
                const uint32_t a01 = pack_bf2(sd[0] * bf_lo(gh[it].x), sd[1] * bf_hi(gh[it].x)), a23 = pack_bf2(sd[2] * bf_lo(gh[it].y), sd[3] * bf_hi(gh[it].y));
                const float ag[4] = {bf_lo(a01), bf_hi(a01), bf_lo(a23), bf_hi(a23)};
#pragma unroll
                for (int j = 0; j < 4; j++) {
                    float4 w = w4[4 + j];
                    uu[0] += ag[j] * w.x; uu[1] += ag[j] * w.y; uu[2] += ag[j] * w.z; uu[3] += ag[j] * w.w;
                }
                const uint32_t t01 = hmul_bf2(pack_bf2(uu[0], uu[1]), gh[it].z);
                const uint32_t t23 = hmul_bf2(pack_bf2(uu[2], uu[3]), gh[it].w);
                uint2 q;
                asm("add.rn.bf16x2 %0, %1, %2;" : "=r"(q.x) : "r"(mv[u].x), "r"(t01));
                asm("add.rn.bf16x2 %0, %1, %2;" : "=r"(q.y) : "r"(mv[u].y), "r"(t23));
                p.out[row0 + i] = q;
            }
        }
    }
}

template <int HOP> __device__ __forceinline__ uint32_t mailbox(uint32_t sb, int lead) {
    const uint2 mp = lds64(sb + OFF_MAP + lead * 8);
    return (mp.y * (D * NPAIR) + 6) * PAIR + (((mp.x >> 6 & 1u) ^ (lead >= NG)) << 12) + 1024 + HOP * 1024;
}
template <int HOP> __device__ __forceinline__ uint4 nulls(int lane) {
    const uint32_t i = lane & 7;
    if (HOP == 1) {
        const uint32_t x = (NB + 2 * i) | 1u << H<1>::TB, y = (OFF_CNT2 - OFF_M) / 8 + 2 * i;
        return make_uint4(x, y, x + 1, y + 1);
    }
    return make_uint4(0x08000800u, 0x08000800u | 3u << H<2>::TB, 0x08000800u, 0x08000800u | 3u << H<2>::TB);
}
template <int OFF> __device__ __forceinline__ void sts128(uint32_t a, const uint4& v) {
    asm volatile("st.shared.v4.u32 [%0+%5], {%1,%2,%3,%4};" ::"r"(a), "r"(v.x), "r"(v.y), "r"(v.z), "r"(v.w), "n"(OFF) : "memory");
}
template <int HOP> struct Prefill {
    uint32_t a0, a1;
    __device__ __forceinline__ Prefill(int lane) {
        const uint32_t q = lane >> 3, i = lane & 7, b = q + (i & 4), c = (q & 1) + (q & 2) * 4 + (i & 6);
        a0 = HOP == 1 ? q * 256 + ((8 + q + i) & 15) * 16 : b * 128 + ((4 + b + (i & 3)) & 7) * 16;
        a1 = HOP == 1 ? q * 256 + 1024 + ((12 + q + i) & 15) * 16 : c * 128 + ((2 + c + (i & 1)) & 7) * 16;
    }
    __device__ __forceinline__ void run(uint32_t win, const uint4& v) const {
#pragma unroll 1
        for (uint32_t w = win; w < win + 16384; w += 8192) {
            sts128<0>(w + a0, v); sts128<2048>(w + a0, v); sts128<4096>(w + a0, v); sts128<6144>(w + a0, v);
            sts128<0>(w + a1, v); sts128<2048>(w + a1, v); sts128<4096>(w + a1, v); sts128<6144>(w + a1, v);
            if (HOP == 2) { sts128<1024>(w + a0, v); sts128<3072>(w + a0, v); sts128<5120>(w + a0, v); sts128<7168>(w + a0, v); }
        }
        if (a0 < 512) sts128<16384>(win + a0, v);
        if (HOP == 2 && a1 < 512) sts128<16384>(win + a1, v);
    }
};
__device__ __forceinline__ bool elect() {
    uint32_t q; asm volatile("{ .reg .pred q; elect.sync _|q, 0xffffffff; selp.u32 %0, 1, 0, q; }" : "=r"(q)); return q;
}
#define LATE_SAMPLE 3
template <int HOP>
__device__ __forceinline__ void manager(const Params& p, uint32_t sb, int lane, int role, uint32_t base) {
    typedef H<HOP> h;
    constexpr int V = h::NBIN / 32, PB = h::S * 8;
    const int RT = p.rounds, grp = role >= NG;
    unsigned char* dst = p.ring + (uint32_t)(blockIdx.x * D * SLOT);
    uint32_t halves = __reduce_or_sync(0xffffffffu, lds64(sb + OFF_MAP + role * 8).x ^ (HOP == 1 && grp ? ~0u : 0u)) & ((1u << D * NPAIR) - 1u);
    const unsigned char* cr = p.ring + mailbox<HOP>(sb, HOP == 1 ? role / J * J : max(role / (2 * J) * (2 * J), grp * NG));
    const unsigned char* cr0 = cr + lane * V * 4, *cr1 = cr + (32 * V + min(lane, V - 1)) * 4;
    const uint32_t ca0 = sb + h::CNT + lane * V * 4, ca1 = sb + h::CNT + (32 * V + min(lane, V + NDUM - 1)) * 4;
    const uint32_t rot0 = (lane * V & 7) * 16, rot1 = lane < V ? lane * 16 : 0x80000000u;
    const Prefill<HOP> pf(lane);
    uint4 nul = nulls<HOP>(lane);
    int slot = 0;
    uint32_t init = h::init(0, 1), prim = sb + h::STG;
    uint32_t cs[5];
    auto sample = [&]() {
        if (V == 2) asm volatile("ld.relaxed.gpu.global.v2.u32 {%0,%1}, [%2];" : "=r"(cs[0]), "=r"(cs[1]) : "l"(cr0) : "memory");
        else asm volatile("ld.relaxed.gpu.global.v4.u32 {%0,%1,%2,%3}, [%4];" : "=r"(cs[0]), "=r"(cs[1]), "=r"(cs[2]), "=r"(cs[3]) : "l"(cr0) : "memory");
        cs[V] = ld_rlx32(reinterpret_cast<const uint32_t*>(cr1));
    };
    sample();
    if (HOP == 1) bar_sync(BAR_CLEAR, 64);
    uint32_t c[5];
    TK_DECL
#pragma unroll 1
    for (int r = 0;; r++) {
        const int nslot = slot == D - 1 ? 0 : slot + 1;
        const uint32_t ninit = h::init(nslot, (init + 0x10000u) >> h::TB & 1u), done = prim;
        TK(5)
        mbar_wait(sb + B_FULL + (HOP - 1) * 8, r & 1);
        TK(0)
        if (V == 2) asm volatile("ld.shared.v2.u32 {%0,%1}, [%2];" : "=r"(c[0]), "=r"(c[1]) : "r"(ca0) : "memory");
        else asm volatile("ld.shared.v4.u32 {%0,%1,%2,%3}, [%4];" : "=r"(c[0]), "=r"(c[1]), "=r"(c[2]), "=r"(c[3]) : "r"(ca0) : "memory");
        c[V] = lds32(ca1);
        uint32_t nc[5], lo = c[V];
#pragma unroll
        for (int k = 0; k <= V; k++) {
            const uint32_t z = ninit + (k < V ? rot0 + k * 16 : rot1);
            nc[k] = min(max(c[k] + (ninit - init - h::S * h::INC), z), z + (h::CAP - h::S) * h::INC);
            lo = min(lo, c[k]);
        }
        if (V == 2) sts64(ca0, nc[0], nc[1]); else sts128<0>(ca0, make_uint4(nc[0], nc[1], nc[2], nc[3]));
        sts32(ca1, nc[V]);
        __syncwarp();
        if (lane == 0) mbar_arrive(sb + B_OPEN + (HOP - 1) * 8);
        TK(1)
        if (lo < init + (h::PRE << h::SH)) {
            const uint32_t gb = init & 1u << h::TB, vx = HOP == 1 ? NB | gb : 0x08000800u, vy = HOP == 1 ? nul.y : 0x28000800u | gb;
#pragma unroll 1
            for (int k = 0; k <= V; k++) {
                const uint32_t bin = k < V ? lane * V + k : 32 * V + lane;
#pragma unroll 1
                for (uint32_t x = pick(k, c); x < init + (h::PRE << h::SH); x += h::INC) sts64(prim + bin * PB + (x & h::PM), vx, vy);
            }
        }
        __syncwarp();
        TK(2)
        asm volatile("fence.proxy.async.shared::cta;" ::: "memory");
        TK(6)
        if (r >= D) {
            int it = 0;
            while (true) {
                uint32_t bad = 0;
#pragma unroll
                for (int k = 0; k <= V; k++) bad |= cs[k] - (base + r - D + 1);
                if (!__any_sync(0xffffffffu, bad >> 20)) break;
                if (++it > SPIN_LIMIT) __trap();
                if (it > 1) __nanosleep(100);
                sample();
            }
        }
        TK(3)
        if (elect()) {
#pragma unroll
            for (int i = 0; i < (HOP == 1 ? 5 : 6); i++) {
                const int k = HOP == 1 ? i : i % 3, pg = HOP == 1 ? 0 : i / 3, pair = HOP == 1 ? (k < 4 ? k : 6) : 4 + k;
                const uint32_t o = (((pg ? ~halves : halves) << (12 - pair)) & 4096u) | (pair * PAIR + (HOP == 1 && pair == 6 ? 1024 : 0));
                asm volatile("cp.async.bulk.global.shared::cta.bulk_group [%0], [%1], %2;"
                             ::"l"(dst + o), "r"(prim + pg * NG * PB + k * 4096), "r"(pair < 6 ? 4096 : 2 * PB) : "memory");
            }
            asm volatile("cp.async.bulk.commit_group;" ::: "memory");
            asm volatile("cp.async.bulk.wait_group.read 0;" ::: "memory");
            if (HOP == 1) mbar_arrive(sb + B_FREE);
        }
        __syncwarp();
        TK(4)
        prim = HOP == 1 ? prim ^ 0x20000u : sb + ((0x310u >> (nslot * 4) & 3u) << 16);
        if (r == RT - 1) break;
        if (!(LATE_SAMPLE & HOP)) sample();
        if (slot == (HOP == 1 ? 1 : 0)) {
            if (HOP == 1) { nul.x ^= 1u << h::TB; nul.z ^= 1u << h::TB; }
            else { nul.y ^= 1u << h::TB; nul.w ^= 1u << h::TB; }
        }
        pf.run(done, nul);
        if (LATE_SAMPLE & HOP) sample();
        dst += slot == D - 1 ? -(D - 1) * SLOT : SLOT;
        halves = (halves >> NPAIR | halves << (D - 1) * NPAIR) & ((1u << D * NPAIR) - 1u);
        slot = nslot;
        init = ninit;
    }
#pragma unroll 1
    for (int k = 0; k <= V; k++) {
        const uint32_t bin = k < V ? lane * V + k : 32 * V + lane, n = bin < h::NBIN ? min((pick(k, c) - init) >> h::SH, (uint32_t)h::CAP) : 0u;
#pragma unroll 1
        for (uint32_t x = h::S; x < n; x++) {
            const uint2 w = lds64(prim + bin * PB + ((x + (bin & 7) * 2) & (h::S - 1)) * 8);
            if (HOP == 1) slow_rec1(p, w.x, w.y, bin);
            else slow_rec2(p, w.x, w.y, bin, __uint_as_float(lds32(sb + W_UNIT)));
        }
    }
    asm volatile("cp.async.bulk.wait_group 0;" ::: "memory");
    TK_OUT
}

#define POLL_NS 200
#define POLL_NS3 1500
template <int HOP> struct Reader {
    uint32_t cur[J];
    uint32_t st;
    uint32_t want;
    __device__ __forceinline__ bool wrap() const { return st & 0x80u; }
    static __device__ __forceinline__ int source(int w, int j, int lane, int role) { return HOP == 1 ? (role >= NG ? NG : 0) + w * J + j : (w * J + j) * 2 + (lane >> 4); }
    __device__ __forceinline__ void init(const Params& p, uint32_t sb, int w, int lane, int role) {
        const int grp = role >= NG, l = role - grp * NG;
        const int pair = HOP == 1 ? (l < 64 ? l >> 4 : 6) : 4 + (l >> 5);
        const uint32_t in = HOP == 1 ? (l & 15) * 256 + (l < 64 ? 0 : 1024) + lane * 8 : (l & 31) * 128 + (lane & 15) * 8;
        st = 0xc04000u;
        if (lane == 0) sts32(sb + OFF_CADR + ((HOP - 1) * NC + w) * 4, mailbox<HOP>(sb, source(w, 0, 0, role)) + (HOP == 1 ? l : role) * 4);
        if (HOP == 2 && w == NC / 2 && lane == 0) sts32(sb + OFF_CADR + 2 * NC * 4, mailbox<HOP>(sb, NG) + role * 4);
        __syncwarp();
#pragma unroll
        for (int j = 0; j < J; j++) {
            const uint2 mp = lds64(sb + OFF_MAP + source(w, j, lane, role) * 8);
            const uint32_t hv = mp.x >> pair;
            cur[j] = (mp.y * (D * NPAIR) + pair) * PAIR + in + (((hv & 1u) ^ grp) << 12);
#pragma unroll
            for (int s = 0; s < D; s++) st |= ((hv >> (s * NPAIR) ^ hv >> ((s + 1) % D * NPAIR)) & 1u) << (s * 8 + j);
        }
        want = 1u << H<HOP>::TB;
    }
    __device__ __forceinline__ void load(const Params& p, uint2 (&rec)[J]) const {
#pragma unroll
        for (int j = 0; j < J; j++) rec[j] = ld_rlx64(p.ring + cur[j]);
    }
    __device__ __forceinline__ void check(const Params& p, uint32_t sb, uint2 (&rec)[J], uint32_t done TK_ARG) const {
        constexpr uint32_t BIT = 1u << H<HOP>::TB;
        int it = 0;
        uint32_t bad;
        while (true) {
            bad = 0;
#pragma unroll
            for (int j = 0; j < J; j++) bad |= (HOP == 1 ? rec[j].x : rec[j].y) ^ want;
            if (!__any_sync(0xffffffffu, bad & BIT)) break;
            if (++it > SPIN_LIMIT) __trap();
            __nanosleep(HOP == 1 ? POLL_NS : POLL_NS3);
            TK_CNT(7)
#pragma unroll
            for (int j = 0; j < J; j++)
                asm volatile("{ .reg .pred q; .reg .u32 t; .reg .u64 a; xor.b32 t, %5, %4; and.b32 t, t, %6; setp.ne.u32 q, t, 0;\n"
                             "cvt.u64.u32 a, %3; add.u64 a, a, %2; @q ld.relaxed.gpu.global.v2.u32 {%0,%1}, [a]; }"
                             : "+r"(rec[j].x), "+r"(rec[j].y) : "l"(p.ring), "r"(cur[j]), "r"(want), "r"(HOP == 1 ? rec[j].x : rec[j].y), "n"(BIT) : "memory");
        }
        uint32_t t;
        asm volatile("mov.u32 %0, %%tid.x;" : "=r"(t));
        const bool extra = HOP == 2 && t == (NS1 + NC + 1 + NC / 2) * 32 + 1;
        if ((t & 31u) == 0 || extra)
            st_rlx32(reinterpret_cast<uint32_t*>(p.ring + lds32(sb + OFF_CADR + (extra ? 2 * NC * 4 : (t >> 3) - (NS1 + HOP - 1) * 4))), done);
    }
    __device__ __forceinline__ void advance() {
        const uint32_t ds = wrap() ? -(D - 1) * SLOT : SLOT;
#pragma unroll
        for (int j = 0; j < J; j++) cur[j] = (cur[j] ^ (st << (12 - j) & 4096u)) + ds;
        want ^= (st & 0x80u) << (H<HOP>::TB - 7);
        st = __byte_perm(st, 0u, 0x3021);
    }
};

#define NPROBE 7
__device__ __forceinline__ uint32_t near_half(unsigned char* pair, uint32_t zero) {
#pragma unroll
    for (int i = 0; i < 4; i++) *reinterpret_cast<uint4*>(pair + (i >> 1) * 4096 + (i & 1) * 16) = make_uint4(0u, 0u, 0u, 0u);
    uint32_t best[2] = {~0u, ~0u}, v = 0, prev = 0;
#pragma unroll
    for (int t = 0; t <= NPROBE; t++) {
        uint32_t now;
        asm volatile("atom.relaxed.gpu.global.add.u32 %0, [%1], 1;" : "=r"(v) : "l"(pair + (t & 1) * 4096 + (v & zero)) : "memory");
        asm volatile("mov.u32 %0, %%clock;" : "=r"(now) :: "memory");
        if (t > 1) best[(t - 1) & 1] = min(best[(t - 1) & 1], now - prev);
        prev = now;
    }
    return (best[1] < best[0] ? 1u : 0u) | (v & zero);
}
template <bool B> struct BoolC { static constexpr bool value = B; };

template <int NP>
__device__ __forceinline__ void stage1(const Params& p, uint32_t sb, const int pos0, int lane) {
    typedef H<1> h;
    const int RT = p.rounds;
    const uint32_t ff = *reinterpret_cast<const uint16_t*>(p.ang_freq) * 0x10001u;
    auto pair_of = [&](int r, int pos) {
        const int q = r < RT - 1 ? (r * NB + blockIdx.x) * NPR + pos : (RT - 1) * NB * NPR + blockIdx.x * p.lastn + pos;
        return (r < RT - 1 || (r == RT - 1 && pos < p.lastn)) && q < p.T2 ? q : -1;
    };
    uint2 vi[NP], vo[NP]; uint32_t va[NP];
    auto load_edge = [&](int r) {
#pragma unroll
        for (int u = 0; u < NP; u++) {
            const int q = max(pair_of(r, pos0 + u * 32), 0);
            vi[u] = ld_in(p.idx_in + q); vo[u] = ld_in(p.idx_out + q); va[u] = ld_in(p.angle + q);
        }
    };
    load_edge(0);
    if (blockIdx.x == 0 && pos0 == 0 && (p.T & 1)) {
        const int t = p.T - 1;
        slow_triplet(p, reinterpret_cast<const uint32_t*>(p.idx_in)[t], reinterpret_cast<const uint32_t*>(p.idx_out)[t],
                     bf16r(cos_bf(hmul_bf2(reinterpret_cast<const uint16_t*>(p.angle)[t], ff) & 0xffffu)));
    }
    uint32_t init = h::init(0, 1);
    int slot = 0;
    TK_DECL
    auto step = [&](const int r, auto edge) {
        constexpr bool EDGE = decltype(edge)::value;
        uint32_t cc[NP], big = 0;
#pragma unroll
        for (int u = 0; u < NP; u++) {
            va[u] = hmul_bf2(va[u], ff);
            cc[u] = pack_bf2(__cosf(bf_lo(va[u])), __cosf(bf_hi(va[u])));
            big = __vmaxu2(big, va[u] & 0x7fff7fffu);
        }
        if ((big + (0x7fffu - BIGX) * 0x10001u) & 0x80008000u) {
#pragma unroll 1
            for (int u = 0; u < NP; u++) {
                const uint32_t a = pick(u, va);
                float c0 = cos_bf(a & 0xffffu), c1 = cos_bf(a >> 16);
                if ((c0 != c0 || c1 != c1) && (!EDGE || pair_of(r, pos0 + u * 32) >= 0)) {
                    const uint2 i2 = pick(u, vi), o2 = pick(u, vo);
                    if (c0 != c0) slow_triplet(p, i2.x, o2.x, c0);
                    if (c1 != c1) slow_triplet(p, i2.y, o2.y, c1);
                }
                const uint32_t v = pack_bf2(c0 != c0 ? 0.f : c0, c1 != c1 ? 0.f : c1);
#pragma unroll
                for (int k = 0; k < NP; k++) if (k == u) cc[k] = v;
            }
        }
        uint32_t bin[2 * NP], x[2 * NP], y[2 * NP];
#pragma unroll
        for (int j = 0; j < 2 * NP; j++) {
            const uint32_t ii = j & 1 ? vi[j >> 1].y : vi[j >> 1].x, oo = j & 1 ? vo[j >> 1].y : vo[j >> 1].x;
            bin[j] = __umulhi(ii, p.mg1);
            y[j] = __byte_perm(bin[j] * p.k1 + ii, cc[j >> 1], j & 1 ? 0x7610 : 0x5410);
            const uint32_t bo = __umulhi(oo, p.mg2);
            x[j] = __byte_perm(bo * p.k2 + oo * 4u, bo, 0x0514);
            if (EDGE && pair_of(r, pos0 + (j >> 1) * 32) < 0) bin[j] = NG + (lane & (NDUM - 1));
        }
        if (EDGE) load_edge(r + 1);
        else {
            uint32_t dep = 0;
#pragma unroll
            for (int j = 0; j < 2 * NP; j++) dep |= x[j] | y[j];
            const int q = ((r + 1) * NB + blockIdx.x) * NPR + pos0 + (dep & p.zero);
#pragma unroll
            for (int u = 0; u < NP; u++) { vi[u] = ld_in(p.idx_in + q + u * 32); vo[u] = ld_in(p.idx_out + q + u * 32); va[u] = ld_in(p.angle + q + u * 32); }
        }
        const uint32_t kb = sb + h::win(r + 1), lim = init + (h::CAP << h::SH);
        TK(0)
        mbar_wait(sb + B_OPEN, (r - 1) & 1);
        TK(1)
        bool freed = false;
        uint32_t over = 0;
#pragma unroll
        for (int g = 0; g < 2 * NP; g += 4) {
            uint32_t ret[4];
#pragma unroll
            for (int j = 0; j < 4; j++) ret[j] = atoms_add<h::CNT>(sb + bin[g + j] * 4, h::INC);
            const int mx = max(max((int)ret[0], (int)ret[1]), max((int)ret[2], (int)ret[3]));
            if (!freed && __any_sync(0xffffffffu, mx >= (int)(init + 0x10000u))) { TK(2) mbar_wait(sb + B_FREE, (r - 1) & 1); freed = true; TK(3) }
            TK(2)
#pragma unroll
            for (int j = 0; j < 4; j++) {
                x[g + j] = and_or<1u << h::TB>(ret[j], x[g + j]);
                put_rec<h::STG>(ret[j], lim, and_xor(ret[j], 0x20000u | h::PM, bin[g + j] * 256 + kb), x[g + j], y[g + j]);
            }
            if (mx >= (int)lim) {
#pragma unroll
                for (int j = 0; j < 4; j++) if ((int)ret[j] >= (int)lim) over |= 1u << (g + j);
            }
        }
        __syncwarp();
        if (lane == 0) mbar_arrive(sb + B_FULL);
        TK(4)
#pragma unroll 1
        while (over) {
            TK_CNT(7)
            const int j = __ffs(over) - 1;
            over &= over - 1;
            slow_rec1(p, pick(j, x), pick(j, y), pick(j, bin));
        }
        slot = slot == D - 1 ? 0 : slot + 1;
        init = h::init(slot, (init + 0x10000u) >> h::TB & 1u);
    };
    int r = 0;
    const int nfast = p.T2 / (NB * NPR) - 1;
#pragma unroll 1
    for (; r < nfast; r++) step(r, BoolC<false>());
#pragma unroll 1
    for (; r < RT; r++) step(r, BoolC<true>());
    TK_OUT
}

__device__ __forceinline__ void stage2(const Params& p, uint32_t sb, int w, int lane, int role, uint32_t base) {
    typedef H<2> h;
    const int RT = p.rounds;
    Reader<1> rd;
    rd.init(p, sb, w, lane, role);
    uint2 rec[J];
    bar_sync(BAR_TABLE, (2 * NC + 1) * 32);
    rd.load(p, rec);
    TK_DECL
#pragma unroll 1
    for (int r = 0; r < RT; r++) {
        rd.check(p, sb, rec, base + r + 1 TK_PASS);
        TK(0)
        uint2 mv[J];
#pragma unroll
        for (int j = 0; j < J; j++) mv[j] = lds64<OFF_M>(sb + (rec[j].y & 0xffffu) * 8);
        uint32_t fl = 0;
#pragma unroll
        for (int j = 0; j < J; j++) fl |= mv[j].y;
        if (fl & 0x40000000u) {
#pragma unroll 1
            for (int j = 0; j < J; j++) {
                const uint2 v = pick(j, mv), w = pick(j, rec);
                if ((v.y & 0x40000000u) && (w.x & 0xffu) < NB) {
                    if (v.x & 0x40000000u) slow_rec1(p, w.x, w.y, lds32(sb + W_ROLE) % NG);
                    else {
                        const float c = bf_hi(w.y), s = __uint_as_float(lds32(sb + W_UNIT)) * 1024.f;
                        side_add(w.x & 0xffu, __byte_perm(w.x, 0u, 0x4413) >> 2, c * (bf_lo(v.x) * s), c * (bf_hi(v.x) * s),
                                 c * (bf_lo(v.y) * s), c * (bf_hi(v.y & 0xbfffffffu) * s));
                    }
                }
            }
#pragma unroll
            for (int j = 0; j < J; j++) if (mv[j].y & 0x40000000u) rec[j].x = NB;
        }
        uint32_t w0[J], w1[J], bin[J], ret[J];
#pragma unroll
        for (int j = 0; j < J; j++) {
            const float c = bf_hi(rec[j].y), MG = 8194.0f;
            const uint32_t x = rec[j].x;
            w0[j] = and_or<0xf000f000u>(x, __byte_perm(__float_as_uint(fmaf(c, bf_lo(mv[j].x), MG)), __float_as_uint(fmaf(c, bf_hi(mv[j].x), MG)), 0x5410));
            w1[j] = and_or<0xf000f000u>(x << 4, __byte_perm(__float_as_uint(fmaf(c, bf_lo(mv[j].y), MG)), __float_as_uint(fmaf(c, bf_hi(mv[j].y), MG)), 0x5410));
            bin[j] = x & 0xffu;
        }
        const uint32_t lim = h::init(rd.wrap() ? D - 1 : 0, rd.want >> H<1>::TB) + 0x20000u;
        rd.advance();
        rd.load(p, rec);
        TK(1)
        mbar_wait(sb + B_OPEN + 8, (r - 1) & 1);
        TK(2)
#pragma unroll
        for (int j = 0; j < J; j++) ret[j] = atoms_add<h::CNT>(sb + bin[j] * 4, h::INC);
        const uint32_t am = and_or<0x30000u>(rd.st << 10 ^ rd.st >> 6, h::PM), kb = and_or<0x30000u>(rd.st << 10, sb);
        int mx = -1;
#pragma unroll
        for (int j = 0; j < J; j++) {
            w1[j] = and_or<1u << h::TB>(ret[j], w1[j]);
            put_rec<0>(ret[j], lim, and_xor(ret[j], am, bin[j] * 128 + kb), w0[j], w1[j]);
            mx = max(mx, (int)ret[j]);
        }
        __syncwarp();
        if (lane == 0) mbar_arrive(sb + B_FULL + 8);
        TK(3)
        if (mx >= (int)lim) {
#pragma unroll 1
            for (int j = 0; j < J; j++)
                if ((int)pick(j, ret) >= (int)lim) slow_rec2(p, pick(j, w0), pick(j, w1), pick(j, bin), __uint_as_float(lds32(sb + W_UNIT)));
        }
        __syncwarp();
        TK(4)
    }
    TK_OUT
}

__device__ __forceinline__ float2 acc_fix(uint32_t old, uint32_t q) {
    const uint32_t u = old + 0x40004000u, n = u + q - 0x08000800u;
    return make_float2((float)((int)(u & 0xffffu) + (int)(q & 0xffffu) - 2048 - (int)(n & 0xffffu)), (float)((int)(u >> 16) + (int)(q >> 16) - 2048 - (int)(n >> 16)));
}
__device__ __forceinline__ void stage3(const Params& p, uint32_t sb, int w, int lane, int role, uint32_t base) {
    const int RT = p.rounds;
    Reader<2> rd;
    rd.init(p, sb, w, lane, role);
    uint2 rec[J];
    bar_sync(BAR_TABLE, (2 * NC + 1) * 32);
    rd.load(p, rec);
    TK_DECL
#pragma unroll 1
    for (int r = 0; r < RT; r++) {
        rd.check(p, sb, rec, base + r + 1 TK_PASS);
        TK(0)
        uint32_t o0[J], o1[J];
        const uint32_t ab = sb - (rd.want >> (H<2>::TB - 1));
                auto odd = [&](uint32_t aux) { return lane & 1u; };
        uint32_t ad[J];
#pragma unroll
        for (int j = 0; j < J; j++) { ad[j] = aux_of(rec[j].x, rec[j].y); o0[j] = odd(ad[j]); }
#pragma unroll
        for (int j = 0; j < J; j++) {
            const uint32_t t = o0[j], a = ab + ad[j] * 2;
            const uint32_t v0 = (rec[j].x & 0x0fff0fffu) - 0x08000800u, v1 = (rec[j].y & 0x0fff0fffu) - 0x08000800u;
            o0[j] = t ? v1 : v0; o1[j] = t ? v0 : v1;
            if (!(rec[j].y & 0x20000000u)) {
                o0[j] = atoms_add<OFF_ACC>(a + t * 4, o0[j]);
                o1[j] = atoms_add<OFF_ACC + 4>(a - t * 4, o1[j]);
            }
        }
        rd.advance();
        uint32_t g = 0;
#pragma unroll
        for (int j = 0; j < J; j++) g |= o0[j] | o1[j];
        if (__any_sync(0xffffffffu, g & 0x80008000u)) {
#pragma unroll 1
            for (int j = 0; j < J; j++) {
                const uint2 w = pick(j, rec);
                const uint32_t aux = aux_of(w.x, w.y), t = odd(aux), p0 = pick(j, o0), p1 = pick(j, o1);
                const float2 a = acc_fix(t ? p1 : p0, w.x & 0x0fff0fffu), b = acc_fix(t ? p0 : p1, w.y & 0x0fff0fffu);
                const float unit = __uint_as_float(lds32(sb + W_UNIT));
                if (a.x != 0.f || a.y != 0.f || b.x != 0.f || b.y != 0.f)
                    side_add(lds32(sb + W_ROLE), aux >> 2, a.x * unit, a.y * unit, b.x * unit, b.y * unit);
                __syncwarp();
            }
        }
        rd.load(p, rec);
        TK(1)
    }
    TK_OUT
}

__device__ __forceinline__ uint32_t row_max(uint32_t x, uint32_t y) {
    const uint32_t mx = __vmaxu2(x & 0x7fff7fffu, y & 0x7fff7fffu);
    return max(mx & 0xffffu, mx >> 16);
}
constexpr int EWIN = 5;

__global__ void __launch_bounds__(NTHR, 1) fused_kernel(const Params p) {
    const int tid = threadIdx.x, lane = tid & 31;
    const int hw = __reduce_max_sync(0xffffffffu, tid >> 5);
    const uint32_t sb = __reduce_or_sync(0xffffffffu, (uint32_t)__cvta_generic_to_shared(smem));
    TKX(0)
    uint32_t base = ld_rlx32(&g_base);
    if (tid < NB + NDUM) sts32(sb + OFF_CNT2 + tid * 4, H<2>::init(0, 1) + (tid < NB ? (tid & 7) * 16 : 0x80000000u));
    else if (tid >= 160 && tid < 160 + NG + NDUM) sts32(sb + OFF_CNT1 + (tid - 160) * 4, H<1>::init(0, 1) + (tid < 160 + NG ? (tid & 7) * 16 : 0x80000000u));
    else if (tid >= 256 && tid < 512) sts32(sb + OFF_HIST + (tid - 256) * 4, 0u);
    else if (tid == 544) {
        if (sb & 255u) __trap();
        asm volatile("mbarrier.init.shared::cta.b64 [%0], %1;" ::"r"(sb + B_FULL), "n"(NS1) : "memory");
        asm volatile("mbarrier.init.shared::cta.b64 [%0], %1;" ::"r"(sb + B_FULL + 8), "n"(NC) : "memory");
        for (int i = 0; i < 3; i++) asm volatile("mbarrier.init.shared::cta.b64 [%0], 1;" ::"r"(sb + B_OPEN + i * 8) : "memory");
        sts32(sb + W_PROBE, 0u);
    } else if (tid >= 576 && (tid - 576) * 16 < p.R2 && (blockIdx.x * p.R2 + (tid - 576) * 16) < p.E)
        prefetch_l2(p.m + blockIdx.x * p.R2 + (tid - 576) * 16);
    sts64(sb + OFF_ZERO + tid * 8, 0u, 0u);
    if (hw >= 30) Prefill<1>(lane).run(sb + OFF_H1 + H<1>::win(hw), nulls<1>(lane));
    __syncthreads();

    if (hw < NS1) {
        if (hw < NS1 - 1) stage1<4>(p, sb, hw * 128 + lane, lane);
        else stage1<NPR / 32 - (NS1 - 1) * 4>(p, sb, hw * 128 + lane, lane);
        __threadfence();
        bar_arrive(BAR_DONE, (NS1 + NC + 2) * 32);
    } else if (hw == W_M1) {
        base = __reduce_or_sync(0xffffffffu, base);
        bar_sync(BAR_PROBE, (2 * NC + 1) * 32);
        {
            const uint32_t raw = lds32(sb + W_PROBE), side = raw >> (D * NPAIR);
            if (lane < 2)
                asm volatile("st.relaxed.gpu.global.v2.u32 [%0], {%1,%2};" ::"l"(p.ring + REF + REF_PUB + lane * 4096 + blockIdx.x * 8), "r"(base),
                             "r"(side ? ~raw | 0x80000000u : raw) : "memory");
            uint32_t best = 0;
#pragma unroll 1
            for (int e = 11 + lane; e <= 230; e += 32) {
                uint32_t c = 0;
#pragma unroll
                for (int i = 0; i < EWIN; i++) c += lds32(sb + OFF_HIST + (e - i) * 4);
                best = max(best, c << 8 | (255 - e));
            }
            const uint32_t e = 255 - (__reduce_max_sync(0xffffffffu, best) & 255u);
            if (lane == 0) { sts32(sb + W_EXP, e); sts32(sb + W_UNIT, (e - 10) << 23); }
            uint2 pb[5];
            int it = 0;
            while (true) {
                bool ok = true;
#pragma unroll
                for (int j = 0; j < 5; j++) { pb[j] = ld_rlx64(p.ring + REF + REF_PUB + side * 4096 + min(lane + 32 * j, NB - 1) * 8); ok = ok && pb[j].x == base; }
                if (__all_sync(0xffffffffu, ok)) break;
                __nanosleep(50);
                if (++it > SPIN_LIMIT) __trap();
            }
            uint32_t bal[5], n1 = 0;
#pragma unroll
            for (int j = 0; j < 5; j++) { bal[j] = __ballot_sync(0xffffffffu, lane + 32 * j < NB && (int)pb[j].y < 0); n1 += __popc(bal[j]); }
            uint32_t before = 0;
#pragma unroll
            for (int j = 0; j < 5; j++) {
                const uint32_t b = lane + 32 * j, k = before + __popc(bal[j] & ((1u << lane) - 1u)), ro = (int)pb[j].y < 0 ? NB - n1 + k : b - k;
                if (b < NB) sts64(sb + OFF_MAP + ro * 8, pb[j].y, b);
                if (b == blockIdx.x) sts32(sb + W_ROLE, ro);
                before += __popc(bal[j]);
            }
        }
        bar_sync(BAR_ROLE, (2 * NC + 2) * 32);
        manager<1>(p, sb, lane, __reduce_max_sync(0xffffffffu, lds32(sb + W_ROLE)), base);
        bar_arrive(BAR_H1, (NS1 + 1) * 32);
        __threadfence();
        bar_arrive(BAR_DONE, (NS1 + NC + 2) * 32);
    } else if (hw == W_M2) {
        base = __reduce_or_sync(0xffffffffu, base);
        uint32_t* flag = reinterpret_cast<uint32_t*>(p.ring + REF + REF_FLAG + (lane & 1) * 4096) + blockIdx.x;
        bar_sync(BAR_ROLE, (2 * NC + 2) * 32);
        const int role = __reduce_max_sync(0xffffffffu, lds32(sb + W_ROLE));
        asm volatile("fence.proxy.async.shared::cta;" ::: "memory");
        if (lane < D * 8) {
            const int k = lane & 7, pair = (lane >> 3) * NPAIR + min(k, 6);
            const uint32_t half = k < 4 ? (lds32(sb + OFF_MAP + role * 8) >> pair & 1u) ^ (role >= NG) : k == 7;
            asm volatile("cp.async.bulk.global.shared::cta.bulk_group [%0], [%1], %2;" ::"l"(p.ring + (uint32_t)((blockIdx.x * D * NPAIR + pair) * PAIR + half * 4096)),
                         "r"(sb + OFF_ZERO), "r"(k < 4 ? 4096 : k < 6 ? 8192 : 1536) : "memory");
            asm volatile("cp.async.bulk.commit_group;" ::: "memory");
            asm volatile("cp.async.bulk.wait_group 0;" ::: "memory");
            __threadfence();
        }
        __syncwarp();
        if (lane < 2) { __threadfence(); st_rlx32(flag, base + 1); }
        bar_arrive(BAR_CLEAR, 64);
#pragma unroll 1
        for (int i = 0; i < 3; i++) Prefill<2>(lane).run(sb + H<2>::win(i), nulls<2>(lane));
        wait_flags(p, sb, lane, base + 1, 1);
        bar_arrive(BAR_TABLE, (2 * NC + 1) * 32);
        manager<2>(p, sb, lane, role, base);
        __threadfence();
        bar_sync(BAR_DONE, (NS1 + NC + 2) * 32);
        if (lane < 2) { __threadfence(); st_rlx32(flag, base + 2); }
    } else {
        const int pw = __reduce_max_sync(0xffffffffu, hw < W_M1 ? hw - NS1 : hw - NS1 - 1), ct = pw * 32 + lane;
        constexpr int CT = 2 * NC * 32;
        uint2 sm3[3];
#pragma unroll
        for (int u = 0; u < 3; u++) sm3[u] = __ldg(p.m + (uint32_t)(ct * 3 + u) * (uint32_t)p.E / (3 * CT));
        if (lane == 0) {
            const uint32_t v = near_half(p.ring + (uint32_t)(pw < D * NPAIR ? (blockIdx.x * D * NPAIR + pw) * PAIR : REF + (blockIdx.x & 63) * 32), p.zero);
            asm volatile("red.shared.or.b32 [%0], %1;" ::"r"(sb + W_PROBE), "r"(v << pw) : "memory");
        }
        __syncwarp();
#pragma unroll
        for (int u = 0; u < 3; u++) {
            const uint32_t mx = row_max(sm3[u].x, sm3[u].y);
            if (mx) atoms_add<OFF_HIST>(sb + (mx >> 7) * 4, 1u);
        }
        TKX(1)
        bar_arrive(BAR_PROBE, (2 * NC + 1) * 32);
        base = __reduce_or_sync(0xffffffffu, base);
        for (int i = ct; i < R2MAX / 2; i += CT) reinterpret_cast<uint4*>(smem + OFF_ACC)[i] = make_uint4(0x40004000u, 0x40004000u, 0x40004000u, 0x40004000u);
        bar_sync(BAR_ROLE, (2 * NC + 2) * 32);
        const int role = __reduce_max_sync(0xffffffffu, lds32(sb + W_ROLE));
        TKX(2)
        {
            const int e = lds32(sb + W_EXP), q0 = (role >= NG ? role - NG : role) * (p.R1 >> 1), nq = min(p.R1 >> 1, (p.E >> 1) - q0);
            const uint32_t sc = (uint32_t)(254 - e) * 0x800080u;
            constexpr int CH = (R1MAX / 2 + CT - 1) / CT;
            uint4 v[CH];
#pragma unroll
            for (int u = 0; u < CH; u++) v[u] = __ldg(reinterpret_cast<const uint4*>(p.m) + min(q0 + ct + u * CT, (p.E >> 1) - 1));
            auto conv = [&](uint32_t& x, uint32_t& y) {
                const uint32_t mx = row_max(x, y);
                const int d = e - (int)(mx >> 7);
                x = hmul_bf2(x, sc); y = hmul_bf2(y, sc);
                if (d >= EWIN) y |= 0x40000000u;
                if (d < 0 || (d >= EWIN && e > 127)) { x = 0x40000000u; y = x; }
                if (mx == 0) { x = 0; y = 0; }
            };
#pragma unroll
            for (int u = 0; u < CH; u++) {
                conv(v[u].x, v[u].y); conv(v[u].z, v[u].w);
                if (ct + u * CT < nq) sts128<OFF_M>(sb + (ct + u * CT) * 16, v[u]);
            }
        }
        TKX(3)
        if (hw < W_M1) {
            stage2(p, sb, pw, lane, role, base);
            __threadfence();
            bar_arrive(BAR_DONE, (NS1 + NC + 2) * 32);
        } else {
            stage3(p, sb, pw - NC, lane, role, base);
            __threadfence();
        }
    }
    TKX(4)
    epilogue(p, sb, base);
}

__global__ void fb_scatter(const uint2* __restrict__ m, const int* __restrict__ idx_in, const int* __restrict__ idx_out,
                           const uint16_t* __restrict__ angle, const __nv_bfloat16* __restrict__ ang_freq, int T, int e0, int e1) {
    const uint32_t fb = *reinterpret_cast<const uint16_t*>(ang_freq);
    for (long long t = blockIdx.x * (long long)blockDim.x + threadIdx.x; t < T; t += (long long)gridDim.x * blockDim.x) {
        int o = idx_out[t];
        if (o < e0 || o >= e1) continue;
        float c = bf16r(cos_bf(hmul_bf2(angle[t], fb) & 0xffffu));
        uint2 v = __ldg(m + idx_in[t]);
        red4(&g_ovf[o - e0], c * bf_lo(v.x), c * bf_hi(v.x), c * bf_lo(v.y), c * bf_hi(v.y));
    }
}
__global__ void fb_final(const Params p, int e0, int e1) {
    int e = e0 + blockIdx.x * blockDim.x + threadIdx.x;
    if (e >= e1) return;
    float4 a4 = g_ovf[e - e0];
    g_ovf[e - e0] = make_float4(0.f, 0.f, 0.f, 0.f);
    float a[4] = {a4.x, a4.y, a4.z, a4.w};
    float d = __bfloat162float(p.dist[e]);
    float g[4] = {0, 0, 0, 0}, h[4] = {0, 0, 0, 0};
    for (int r = 0; r < 8; r++) {
        float df = bf16r(d - __bfloat162float(p.centers[r]));
        float rb = bf16r(expf(bf16r(-10.0f * bf16r(df * df))));
        for (int k = 0; k < 4; k++) {
            g[k] += rb * __bfloat162float(p.w_sbf[r * 4 + k]);
            h[k] += rb * __bfloat162float(p.w_rbf[r * 4 + k]);
        }
    }
    float ag[4];
    for (int k = 0; k < 4; k++) {
        float s = 0.f;
        for (int j = 0; j < 4; j++) s += a[j] * __bfloat162float(p.w_down[j * 4 + k]);
        ag[k] = bf16r(s * g[k]);
    }
    uint2 mv = p.m[e];
    float mm[4] = {bf_lo(mv.x), bf_hi(mv.x), bf_lo(mv.y), bf_hi(mv.y)};
    __nv_bfloat16 o[4];
    for (int k = 0; k < 4; k++) {
        float u = 0.f;
        for (int j = 0; j < 4; j++) u += ag[j] * __bfloat162float(p.w_up[j * 4 + k]);
        o[k] = __float2bfloat16_rn(mm[k] + bf16r(bf16r(u) * bf16r(h[k])));
    }
    p.out[e] = *reinterpret_cast<uint2*>(o);
}

}

static bool exact_div(int E, int lo, int hi, int* R, uint32_t* magic) {
    for (int r = lo + (lo & 1); r <= hi; r += 2) {
        unsigned long long mg = ((1ull << 32) + r - 1) / r, err = mg * r - (1ull << 32);
        if (err * (unsigned long long)E < (1ull << 32)) { *R = r; *magic = (uint32_t)mg; return true; }
    }
    return false;
}

extern "C" void kernel_launch(void* const* d_in, const int* in_sizes, int n_in, void* d_out, int out_size) {
    typedef const __nv_bfloat16* B;
    Params p;
    p.m = (const uint2*)d_in[0]; p.idx_in = (const uint2*)d_in[1]; p.idx_out = (const uint2*)d_in[2]; p.dist = (B)d_in[3];
    p.angle = (const uint32_t*)d_in[4]; p.centers = (B)d_in[5]; p.ang_freq = (B)d_in[6]; p.w_rbf = (B)d_in[7]; p.w_sbf = (B)d_in[8];
    p.w_down = (B)d_in[9]; p.w_up = (B)d_in[10]; p.out = (uint2*)d_out;
    p.E = in_sizes[3]; p.T = in_sizes[1]; p.T2 = p.T >> 1; p.zero = 0;
    p.R1 = p.R2 = p.rounds = p.lastn = 0; p.mg1 = p.mg2 = p.k1 = p.k2 = 0;
    static int ok = -1;
    static unsigned char* ring = nullptr;
    if (ok < 0) {
        void* ra = nullptr;
        cudaGetSymbolAddress(&ra, g_ring);
        ring = reinterpret_cast<unsigned char*>(((uintptr_t)ra + PAIR - 1) & ~(uintptr_t)(PAIR - 1));
        int dev = 0, sms = 0, occ = 0;
        cudaGetDevice(&dev);
        cudaDeviceGetAttribute(&sms, cudaDevAttrMultiProcessorCount, dev);
        cudaError_t e = cudaFuncSetAttribute(fused_kernel, cudaFuncAttributeMaxDynamicSharedMemorySize, SMEM_BYTES);
        if (e == cudaSuccess) e = cudaOccupancyMaxActiveBlocksPerMultiprocessor(&occ, fused_kernel, NTHR, SMEM_BYTES);
        ok = (e == cudaSuccess && occ >= 1 && sms >= NB) ? 1 : 0;
        (void)cudaGetLastError();
    }
    p.ring = ring;
    const bool fused = ok == 1 && p.E <= EMAX && p.E >= 2 * NB && p.E % 2 == 0 && p.T >= 2 && exact_div(p.E, (p.E + NG - 1) / NG, R1MAX, &p.R1, &p.mg1) &&
                       exact_div(p.E, (p.E + NB - 1) / NB, R2MAX, &p.R2, &p.mg2);
    if (fused) {
        p.k1 = 0u - (uint32_t)p.R1; p.k2 = 0u - 4u * (uint32_t)p.R2;
        const int per = NB * NPR;
        int full = p.T2 / per, rest = p.T2 - full * per;
        p.lastn = (rest + NB - 1) / NB;
        if (p.lastn > NPR / 2) { full++; p.lastn = 0; }
        if (full < D) { full = D; p.lastn = 0; }
        p.rounds = full + 1;
        fused_kernel<<<NB, NTHR, SMEM_BYTES>>>(p);
    } else {
        for (int e0 = 0; e0 < p.E; e0 += EMAX) {
            int e1 = p.E - e0 < EMAX ? p.E : e0 + EMAX;
            fb_scatter<<<1056, 256>>>(p.m, (const int*)d_in[1], (const int*)d_in[2], (const uint16_t*)d_in[4], p.ang_freq, p.T, e0, e1);
            fb_final<<<(e1 - e0 + 255) / 256, 256>>>(p, e0, e1);
        }
    }
}
```

```cpp
#include <cuda_runtime.h>
#include <cuda_bf16.h>
#include <stdint.h>

namespace {

constexpr int NB = 132, NG = 66;
constexpr int R2MAX = 6062, R1MAX = 12124;
constexpr int EMAX = NB * R2MAX;
constexpr int NTHR = 1024;
constexpr int NS1 = 8, NC = 11, J = 6;
#define TILES 15
constexpr int NPR = TILES * 64;
constexpr int D = 3;
constexpr int WIN = 16896;
constexpr int NDUM = 16;

constexpr int OFF_ACC = WIN, OFF_BAR = OFF_ACC + R2MAX * 8;
constexpr int OFF_H1 = 0x10000 + WIN, OFF_M = OFF_H1 + WIN, OFF_WSM = OFF_M + R1MAX * 8;
constexpr int OFF_CNT1 = OFF_H1 + 0x20000 + WIN, OFF_CNT2 = OFF_CNT1 + (NG + NDUM + 2) * 4, OFF_WG = OFF_CNT2 + (NB + NDUM) * 4;
constexpr int OFF_HIST = OFF_M;
constexpr int OFF_PROBE = OFF_WSM + 128;
constexpr int SMEM_BYTES = OFF_WG + 272;
static_assert(SMEM_BYTES <= 232448 && OFF_BAR + 64 <= 0x10000 && OFF_PROBE + 32 <= 0x30000, "smem");
static_assert(OFF_BAR % 8 == 0 && OFF_WG % 16 == 0 && OFF_WSM % 16 == 0 && OFF_CNT2 % 16 == 0, "align");
static_assert(NC * J == NG && NC * 32 * 6 * 16 == 2 * WIN, "shape");

template <int HOP> struct H {
    static constexpr int S = HOP == 1 ? 32 : 16, NBIN = HOP == 1 ? NG : NB, CAP = HOP == 1 ? 48 : 32, PRE = HOP == 1 ? 16 : 4, SH = HOP == 1 ? 11 : 12;
    static constexpr int TB = HOP == 1 ? 20 : 28, CNT = HOP == 1 ? OFF_CNT1 : OFF_CNT2, STG = HOP == 1 ? OFF_H1 : 0;
    static constexpr uint32_t INC = (1u << SH) + 8u, PM = (S - 1) * 8;
    static __device__ __forceinline__ uint32_t lap(uint32_t R) { return R * (((1u << TB) + 2u) / 3u); }
    static __device__ __forceinline__ uint32_t gen(uint32_t R) { return lap(R) & 1u << TB; }
    static __device__ __forceinline__ uint32_t init(uint32_t R) { return 0x30000u | gen(R) | (lap(R) & 1u << (TB - 1) ? (1u << TB) - (1u << 18) : 0u); }
    static __device__ __forceinline__ uint32_t win(int r) { return HOP == 1 ? (r & 1) << 17 : (0x310u >> (r % 3 * 4) & 3u) << 16; }
};

constexpr uint32_t PAGE = 1u << 21;
__device__ __align__(256) unsigned char g_ring[(size_t)(2 * NC + 1) * PAGE];
constexpr int MID = 1 << 20, MISC = MID + 0xc000;
constexpr int M_CNT = MISC + 1024, M_PAR = MISC + 1088;
constexpr int M_FLAG = MISC + 2048;
constexpr int PROBE = MID + 0x4c000;
#define ALT 1
__device__ __forceinline__ uint32_t alt(int page) { return (page & ALT) << 20; }
constexpr int NLO = 60, NHI = 72;
__host__ __device__ constexpr uint32_t src_off(int j) { return (j % 3) << 14 | (j / 3) << 18; }
__device__ __forceinline__ uint32_t slot_off(uint32_t s) { return (0xa930u >> s * 4 & 15u) << 16; }
__device__ __forceinline__ uint32_t slot_steps(uint32_t R) { return (uint32_t)(0x30a09030aull >> (2 - R % 3) * 8) & 0xffffffu; }
__device__ __forceinline__ void slot_next(uint32_t& a, uint32_t st) { a ^= st & 0xf0000u; }
__device__ __forceinline__ uint32_t slot_rot(uint32_t st) { return __byte_perm(st, 0u, 0x4102); }
constexpr int RPAD = 6064, DROW = 6144;
__device__ __align__(128) uint8_t g_dirty[NB * DROW];
__device__ uint32_t g_base = 3;
__device__ __align__(128) float4 g_ovf[NB * RPAD];

struct Params {
    const uint2* m; const uint2* idx_in; const uint2* idx_out; const __nv_bfloat16* dist; const uint32_t* angle;
    const __nv_bfloat16* centers; const __nv_bfloat16* ang_freq; const __nv_bfloat16* w_rbf; const __nv_bfloat16* w_sbf;
    const __nv_bfloat16* w_down; const __nv_bfloat16* w_up; uint2* out; unsigned char* ring;
    int E, T, T2, R1, R2, rounds, lastn, qfull; uint32_t mg1, mg2, k1, k2, zero;
};

__device__ __forceinline__ float bf16r(float x) { return __bfloat162float(__float2bfloat16_rn(x)); }
__device__ __forceinline__ float bf_lo(uint32_t v) { return __uint_as_float(v << 16); }
__device__ __forceinline__ float bf_hi(uint32_t v) { return __uint_as_float(v & 0xffff0000u); }
__device__ __forceinline__ void red4(float4* a, float x, float y, float z, float w) {
    asm volatile("red.global.add.v4.f32 [%0], {%1,%2,%3,%4};" ::"l"(a), "f"(x), "f"(y), "f"(z), "f"(w) : "memory");
}
__device__ __forceinline__ void bar_sync(int id, int n) { __syncwarp(); asm volatile("bar.sync %0, %1;" ::"r"(id), "r"(n) : "memory"); }
__device__ __forceinline__ void bar_arrive(int id, int n) { __syncwarp(); asm volatile("bar.arrive %0, %1;" ::"r"(id), "r"(n) : "memory"); }
template <int OFF> __device__ __forceinline__ uint32_t atoms_add(uint32_t addr, uint32_t v) {
    uint32_t r; asm volatile("atom.shared.add.u32 %0, [%1+%3], %2;" : "=r"(r) : "r"(addr), "r"(v), "n"(OFF) : "memory"); return r;
}
__device__ __forceinline__ void sts64(uint32_t addr, uint32_t x, uint32_t y) {
    asm volatile("st.shared.v2.u32 [%0], {%1,%2};" ::"r"(addr), "r"(x), "r"(y) : "memory");
}
__device__ __forceinline__ void sts32(uint32_t addr, uint32_t x) { asm volatile("st.shared.u32 [%0], %1;" ::"r"(addr), "r"(x) : "memory"); }
template <int OFF = 0> __device__ __forceinline__ uint2 lds64(uint32_t addr) {
    uint2 v; asm volatile("ld.shared.v2.u32 {%0,%1}, [%2+%3];" : "=r"(v.x), "=r"(v.y) : "r"(addr), "n"(OFF) : "memory"); return v;
}
__device__ __forceinline__ uint32_t lds32(uint32_t addr) {
    uint32_t v; asm volatile("ld.shared.u32 %0, [%1];" : "=r"(v) : "r"(addr) : "memory"); return v;
}
__device__ __forceinline__ uint32_t ld_rlx32(const uint32_t* p) {
    uint32_t v; asm volatile("ld.relaxed.gpu.global.u32 %0, [%1];" : "=r"(v) : "l"(p) : "memory"); return v;
}
__device__ __forceinline__ uint2 ld_rlx64(const void* p) {
    uint2 v; asm volatile("ld.relaxed.gpu.global.v2.u32 {%0,%1}, [%2];" : "=r"(v.x), "=r"(v.y) : "l"(p) : "memory"); return v;
}
__device__ __forceinline__ float4 ld_rlx128f(const float4* p) {
    float4 v; asm volatile("ld.relaxed.gpu.global.v4.f32 {%0,%1,%2,%3}, [%4];" : "=f"(v.x), "=f"(v.y), "=f"(v.z), "=f"(v.w) : "l"(p) : "memory"); return v;
}
__device__ __forceinline__ void take3(float4* p, uint32_t mask, float4 (&v)[3]) {
    asm volatile("{ .reg .b128 a, b, c; .reg .b64 x, y; .reg .pred q0, q1, q2; .reg .b32 t;\n"
                 "mov.b64 x, 0; mov.b128 a, {x, x}; mov.b128 b, {x, x}; mov.b128 c, {x, x};\n"
                 "and.b32 t, %13, 1; setp.ne.u32 q0, t, 0; and.b32 t, %13, 2; setp.ne.u32 q1, t, 0; and.b32 t, %13, 4; setp.ne.u32 q2, t, 0;\n"
                 "@q0 atom.relaxed.gpu.global.exch.b128 a, [%12], a; @q1 atom.relaxed.gpu.global.exch.b128 b, [%12+16384], b;\n"
                 "@q2 atom.relaxed.gpu.global.exch.b128 c, [%12+32768], c;\n"
                 "mov.b128 {x, y}, a; mov.b64 {%0,%1}, x; mov.b64 {%2,%3}, y; mov.b128 {x, y}, b; mov.b64 {%4,%5}, x; mov.b64 {%6,%7}, y;\n"
                 "mov.b128 {x, y}, c; mov.b64 {%8,%9}, x; mov.b64 {%10,%11}, y; }"
                 : "=f"(v[0].x), "=f"(v[0].y), "=f"(v[0].z), "=f"(v[0].w), "=f"(v[1].x), "=f"(v[1].y), "=f"(v[1].z), "=f"(v[1].w),
                   "=f"(v[2].x), "=f"(v[2].y), "=f"(v[2].z), "=f"(v[2].w) : "l"(p), "r"(mask) : "memory");
}
__device__ __forceinline__ void st_rlx32(uint32_t* p, uint32_t v) { asm volatile("st.relaxed.gpu.global.u32 [%0], %1;" ::"l"(p), "r"(v) : "memory"); }
__device__ __forceinline__ uint32_t hmul_bf2(uint32_t a, uint32_t b) {
    uint32_t r; asm("mul.rn.bf16x2 %0, %1, %2;" : "=r"(r) : "r"(a), "r"(b)); return r;
}
__device__ __forceinline__ uint32_t hsub_bf2(uint32_t a, uint32_t b) {
    uint32_t r; asm("sub.rn.bf16x2 %0, %1, %2;" : "=r"(r) : "r"(a), "r"(b)); return r;
}
constexpr int SPIN_LIMIT = 1 << 22;

__constant__ uint32_t c_inv2pi[8] = {0u, 0x28be60dbu, 0x9391054au, 0x7f09d5f4u, 0x7d4d3770u, 0x36d8a566u, 0x4f10e410u, 0x7f9458eau};
constexpr uint32_t BIGX = 0x4280u;
__device__ __forceinline__ float cos_big(uint32_t xb) {
    uint32_t e = (xb >> 7) & 0xffu, M = (xb & 0x7fu) | 0x80u;
    uint32_t pp = e - 102u;
    uint32_t wi = pp >> 5;
    uint32_t t0 = c_inv2pi[wi], t1 = c_inv2pi[wi + 1], t2 = c_inv2pi[wi + 2];
    uint32_t f = M * __funnelshift_l(t1, t0, pp) + __umulhi(M, __funnelshift_l(t2, t1, pp));
    float c = __cosf((float)(int)f * 1.4629180792671596e-9f);
    return e == 255u ? __uint_as_float(0x7fc00000u) : c;
}
__device__ __forceinline__ float cos_bf(uint32_t xb) {
    return (xb & 0x7fffu) > BIGX ? cos_big(xb) : __cosf(__uint_as_float(xb << 16));
}
__device__ __forceinline__ uint32_t pack_bf2(float lo, float hi) {
    uint32_t r; asm("cvt.rn.bf16x2.f32 %0, %1, %2;" : "=r"(r) : "f"(hi), "f"(lo)); return r;
}
template <int N> __device__ __forceinline__ uint32_t pick(int k, const uint32_t (&a)[N]) {
    uint32_t v = a[0];
#pragma unroll
    for (int i = 1; i < N; i++) if (k == i) v = a[i];
    return v;
}
template <int N> __device__ __forceinline__ uint2 pick(int k, const uint2 (&a)[N]) {
    uint2 v = a[0];
#pragma unroll
    for (int i = 1; i < N; i++) if (k == i) v = a[i];
    return v;
}
__device__ __forceinline__ void side_add(uint32_t bin, uint32_t row, float a, float b, float c, float d) {
    red4(&g_ovf[bin * RPAD + row], a, b, c, d);
    g_dirty[bin * DROW + row] = 1;
}
__device__ __forceinline__ void slow_triplet(const Params& p, uint32_t ii, uint32_t oo, float c) {
    const uint2 v = __ldg(p.m + ii);
    const uint32_t bo = __umulhi(oo, p.mg2);
    side_add(bo, oo - bo * p.R2, c * bf_lo(v.x), c * bf_hi(v.x), c * bf_lo(v.y), c * bf_hi(v.y));
}
__device__ __forceinline__ void slow_rec1(const Params& p, uint32_t x, uint32_t y, uint32_t bin) {
    const uint2 v = __ldg(p.m + bin * p.R1 + (y & 0xffffu));
    const float c = bf_hi(y);
    side_add(x & 0xffu, __byte_perm(x, 0u, 0x4413) >> 2, c * bf_lo(v.x), c * bf_hi(v.x), c * bf_lo(v.y), c * bf_hi(v.y));
}
__device__ __forceinline__ uint32_t aux_of(uint32_t w0, uint32_t w1) {
    uint32_t u; asm("lop3.b32 %0, %1, %2, 0xf000f000, 0xe4;" : "=r"(u) : "r"(w0), "r"(w1 >> 4));
    return __byte_perm(u, 0u, 0x4413);
}
__device__ __forceinline__ void slow_rec2(const Params& p, uint32_t w0, uint32_t w1, uint32_t bin, float unit) {
    side_add(bin, aux_of(w0, w1) >> 2, (float)((int)(w0 & 0xfffu) - 2048) * unit, (float)((int)(w0 >> 16 & 0xfffu) - 2048) * unit,
             (float)((int)(w1 & 0xfffu) - 2048) * unit, (float)((int)(w1 >> 16 & 0xfffu) - 2048) * unit);
}
template <uint32_t M> __device__ __forceinline__ uint32_t and_or(uint32_t a, uint32_t c) {
    uint32_t r; asm("lop3.b32 %0, %1, %2, %3, 0xea;" : "=r"(r) : "r"(a), "n"(M), "r"(c)); return r;
}
__device__ __forceinline__ uint32_t and_xor(uint32_t a, uint32_t m, uint32_t c) {
    uint32_t r; asm("lop3.b32 %0, %1, %2, %3, 0x6a;" : "=r"(r) : "r"(a), "r"(m), "r"(c)); return r;
}
__device__ __forceinline__ uint2 ld_in(const uint2* a) {
    uint2 v; asm volatile("ld.global.nc.L1::no_allocate.v2.u32 {%0,%1}, [%2];" : "=r"(v.x), "=r"(v.y) : "l"(a)); return v;
}
__device__ __forceinline__ uint32_t ld_in(const uint32_t* a) {
    uint32_t v; asm volatile("ld.global.nc.L1::no_allocate.u32 %0, [%1];" : "=r"(v) : "l"(a)); return v;
}
template <int OFF> __device__ __forceinline__ void put_rec(uint32_t ret, uint32_t lim, uint32_t addr, uint32_t x, uint32_t y) {
    asm volatile("{ .reg .pred q; setp.lt.u32 q, %0, %1; @q st.shared.v2.u32 [%2+%5], {%3,%4}; }" ::"r"(ret), "r"(lim), "r"(addr), "r"(x), "r"(y), "n"(OFF) : "memory");
}
__device__ __forceinline__ uint32_t mbar_try(uint32_t mb, uint32_t parity) {
    uint32_t ok;
    asm volatile("{ .reg .pred q; mbarrier.try_wait.parity.shared::cta.b64 q, [%1], %2; selp.u32 %0, 1, 0, q; }" : "=r"(ok) : "r"(mb), "r"(parity) : "memory");
    return ok;
}
__device__ __forceinline__ void mbar_wait(uint32_t mb, uint32_t parity) {
    if (!mbar_try(mb, parity)) {
        int it = 0;
        while (!mbar_try(mb, parity)) if (++it > SPIN_LIMIT) __trap();
    }
}
__device__ __forceinline__ void mbar_init(uint32_t mb, uint32_t n) { asm volatile("mbarrier.init.shared::cta.b64 [%0], %1;" ::"r"(mb), "r"(n) : "memory"); }
__device__ __forceinline__ void mbar_arrive(uint32_t mb) { asm volatile("mbarrier.arrive.shared::cta.b64 _, [%0];" ::"r"(mb) : "memory"); }
constexpr int B_FULL = OFF_BAR, B_OPEN = OFF_BAR + 16, B_FREE = OFF_BAR + 32;
constexpr int W_END = OFF_BAR + 40, W_SIDE = OFF_BAR + 44, W_PAR = OFF_BAR + 48, W_ROLE = OFF_BAR + 52, W_EXP = OFF_BAR + 56, W_UNIT = OFF_BAR + 60;
enum { BAR_S1 = 1, BAR_PROBE, BAR_HIST, BAR_ROLE, BAR_TABLE, BAR_H1, BAR_DONE };
constexpr int W_M1 = NS1 + NC, W_M2 = 31;

extern __shared__ __align__(1024) unsigned char smem[];
#define TK_DECL
#define TK(i)
#define TK_CNT(i)
#define TK_OUT
#define TK_ARG
#define TK_PASS
#define TKX(i)
#define TKY(i)

constexpr int NR = (R2MAX + NTHR - 1) / NTHR;
__device__ __forceinline__ void gates(const Params& p, int e0, int e1, int e2, uint4* gh) {
    constexpr int NH = 3;
    const int e[NH] = {e0, e1, e2};
    uint32_t dd[NH];
    float g[NH][4], h[NH][4];
#pragma unroll
    for (int u = 0; u < NH; u++) {
        dd[u] = reinterpret_cast<const uint16_t*>(p.dist)[min(e[u], p.E - 1)] * 0x10001u;
#pragma unroll
        for (int k = 0; k < 4; k++) { g[u][k] = 0.f; h[u][k] = 0.f; }
    }
#pragma unroll 1
    for (int r2 = 0; r2 < 4; r2++) {
        const uint32_t cen = reinterpret_cast<const uint32_t*>(smem + OFF_WG + 256)[r2];
        uint32_t rb[NH];
#pragma unroll
        for (int u = 0; u < NH; u++) {
            const uint32_t df = hsub_bf2(dd[u], cen);
            const uint32_t ar = hmul_bf2(hmul_bf2(df, df), 0xc120c120u);
            rb[u] = pack_bf2(__expf(bf_lo(ar)), __expf(bf_hi(ar)));
        }
#pragma unroll
        for (int i = 0; i < 2; i++) {
            const float4 ws = reinterpret_cast<const float4*>(smem + OFF_WG)[r2 * 2 + i], wr = reinterpret_cast<const float4*>(smem + OFF_WG + 128)[r2 * 2 + i];
#pragma unroll
            for (int u = 0; u < NH; u++) {
                const float x = i ? bf_hi(rb[u]) : bf_lo(rb[u]);
                g[u][0] += x * ws.x; g[u][1] += x * ws.y; g[u][2] += x * ws.z; g[u][3] += x * ws.w;
                h[u][0] += x * wr.x; h[u][1] += x * wr.y; h[u][2] += x * wr.z; h[u][3] += x * wr.w;
            }
        }
    }
#pragma unroll
    for (int u = 0; u < NH; u++)
        gh[u] = make_uint4(pack_bf2(g[u][0], g[u][1]), pack_bf2(g[u][2], g[u][3]), pack_bf2(h[u][0], h[u][1]), pack_bf2(h[u][2], h[u][3]));
}
__device__ __forceinline__ void prefetch_l2(const void* a) { asm volatile("prefetch.global.L2 [%0];" ::"l"(a)); }
__device__ __forceinline__ uint4* gate_slot(int k) { return reinterpret_cast<uint4*>(smem + OFF_H1 + (k >= WIN / 16 ? 0x20000 - WIN : 0)) + k; }
__device__ __forceinline__ void wait_flags(const Params& p, uint32_t sb, int lane, uint32_t need) {
    const unsigned char* f = p.ring + M_FLAG + (lds32(sb + W_SIDE) << 12);
    int it = 0;
    while (true) {
        const float4 a = ld_rlx128f(reinterpret_cast<const float4*>(f) + lane);
        const uint32_t b = ld_rlx32(reinterpret_cast<const uint32_t*>(f) + 128 + (lane & 3));
        const uint32_t d = (__float_as_uint(a.x) ^ need) | (__float_as_uint(a.y) ^ need) | (__float_as_uint(a.z) ^ need) | (__float_as_uint(a.w) ^ need) | (b ^ need);
        if (__all_sync(0xffffffffu, d == 0)) break;
        __nanosleep(50);
        if (++it > SPIN_LIMIT) __trap();
    }
    __threadfence();
}
__device__ __forceinline__ void epilogue(const Params& p, uint32_t sb) {
    int tid;
    asm volatile("mov.u32 %0, %%tid.x;" : "=r"(tid));
    const int role = lds32(sb + W_ROLE), row0 = role * p.R2, nrows = min(p.R2, p.E - row0), hw = tid >> 5;
    const bool s3 = hw > W_M1 && hw < W_M2;
    constexpr int T3 = (W_M1 + 1) * 32, N3 = NC * 32;
    uint4 gh[NR];
    if (hw < NS1) {
        if (tid * 64 < nrows) prefetch_l2(p.dist + row0 + tid * 64);
        for (int i = tid * 16; i < nrows; i += NS1 * 32 * 16) prefetch_l2(p.m + row0 + i);
    }
    if (!s3) gates(p, row0 + tid + 3 * NTHR, row0 + tid + 4 * NTHR, row0 + tid + 5 * NTHR, gh + 3);
    if (hw < NS1) {
        bar_sync(BAR_H1, (NS1 + 1) * 32);
#pragma unroll 1
        for (int k0 = tid; k0 < NR * N3; k0 += 3 * NS1 * 32) {
            int k[3], e[3];
#pragma unroll
            for (int u = 0; u < 3; u++) { k[u] = k0 + u * NS1 * 32; e[u] = row0 + T3 + k[u] + k[u] / N3 * (NTHR - N3); }
            gates(p, e[0], e[1], e[2], gh);
#pragma unroll
            for (int u = 0; u < 3; u++) if (k[u] < NR * N3) *gate_slot(k[u]) = gh[u];
        }
#pragma unroll
        for (int i = tid; i < DROW / 8; i += NS1 * 32) {
            const uint2 f = ld_rlx64(g_dirty + role * DROW + i * 8);
            if (f.x | f.y) prefetch_l2(g_ovf + role * RPAD + i * 8);
        }
    }
    if (!s3) gates(p, row0 + tid, row0 + tid + NTHR, row0 + tid + 2 * NTHR, gh);
    if (hw == W_M1) wait_flags(p, sb, tid & 31, lds32(sb + W_END));
    TKX(5)
    bar_sync(0, NTHR);
    TKX(6)
    uint32_t dirty = 0;
#pragma unroll
    for (int it = 0; it < NR; it++) {
        uint32_t f;
        asm volatile("ld.relaxed.gpu.global.u8 %0, [%1];" : "=r"(f) : "l"(g_dirty + role * DROW + tid + it * NTHR) : "memory");
        dirty |= f << it;
    }
    if (s3) {
#pragma unroll
        for (int it = 0; it < NR; it++) gh[it] = *gate_slot(tid - T3 + it * N3);
    }
    if (hw == W_M1 && blockIdx.x == 0) {
        if (tid == W_M1 * 32) g_base = lds32(sb + W_END);
        if (tid < W_M1 * 32 + 3) *reinterpret_cast<uint32_t*>(p.ring + (tid & 2 ? M_PAR : M_CNT + (tid & 1) * 4096)) = 0;
    }
    const float unit = *reinterpret_cast<const float*>(smem + W_UNIT);
    const float4* w4 = reinterpret_cast<const float4*>(smem + OFF_WSM);
#pragma unroll
    for (int i0 = 0; i0 < NR; i0 += 3) {
        uint2 mv[3];
        float4 o[3];
#pragma unroll
        for (int u = 0; u < 3; u++) mv[u] = __ldg(p.m + min(row0 + tid + (i0 + u) * NTHR, p.E - 1));
        take3(&g_ovf[role * RPAD + tid + i0 * NTHR], dirty >> i0, o);
#pragma unroll
        for (int u = 0; u < 3; u++) {
            const int it = i0 + u, i = tid + it * NTHR;
            if (dirty >> it & 1) g_dirty[role * DROW + i] = 0;
            if (i < nrows) {
                const uint2 ac = reinterpret_cast<const uint2*>(smem + OFF_ACC)[i];
                const uint32_t u0 = ac.x + 0x40004000u, u1 = ac.y + 0x40004000u;
                const float a[4] = {(float)((int)(u0 & 0xffffu) - 0x8000) * unit + o[u].x, (float)((int)(u0 >> 16) - 0x8000) * unit + o[u].y,
                                    (float)((int)(u1 & 0xffffu) - 0x8000) * unit + o[u].z, (float)((int)(u1 >> 16) - 0x8000) * unit + o[u].w};
                float sd[4] = {0, 0, 0, 0}, uu[4] = {0, 0, 0, 0};
#pragma unroll
                for (int j = 0; j < 4; j++) {
                    float4 w = w4[j];
                    sd[0] += a[j] * w.x; sd[1] += a[j] * w.y; sd[2] += a[j] * w.z; sd[3] += a[j] * w.w;
                }
                const uint32_t a01 = pack_bf2(sd[0] * bf_lo(gh[it].x), sd[1] * bf_hi(gh[it].x)), a23 = pack_bf2(sd[2] * bf_lo(gh[it].y), sd[3] * bf_hi(gh[it].y));
                const float ag[4] = {bf_lo(a01), bf_hi(a01), bf_lo(a23), bf_hi(a23)};
#pragma unroll
                for (int j = 0; j < 4; j++) {
                    float4 w = w4[4 + j];
                    uu[0] += ag[j] * w.x; uu[1] += ag[j] * w.y; uu[2] += ag[j] * w.z; uu[3] += ag[j] * w.w;
                }
                const uint32_t t01 = hmul_bf2(pack_bf2(uu[0], uu[1]), gh[it].z);
                const uint32_t t23 = hmul_bf2(pack_bf2(uu[2], uu[3]), gh[it].w);
                uint2 q;
                asm("add.rn.bf16x2 %0, %1, %2;" : "=r"(q.x) : "r"(mv[u].x), "r"(t01));
                asm("add.rn.bf16x2 %0, %1, %2;" : "=r"(q.y) : "r"(mv[u].y), "r"(t23));
                p.out[row0 + i] = q;
            }
        }
        if (i0 == 0) { TKY(3) }
    }
}

template <int HOP> __device__ __forceinline__ uint4 nulls(int lane, uint32_t R) {
    const uint32_t i = lane & 7;
    if (HOP == 1) {
        const uint32_t x = (NB + 2 * i) | H<1>::gen(R), y = (OFF_CNT2 - OFF_M) / 8;
        return make_uint4(x, y, x + 1, y);
    }
    return make_uint4(0x08000800u, 0x28000800u | H<2>::gen(R), 0x08000800u, 0x28000800u | H<2>::gen(R));
}
template <int OFF> __device__ __forceinline__ void sts128(uint32_t a, const uint4& v) {
    asm volatile("st.shared.v4.u32 [%0+%5], {%1,%2,%3,%4};" ::"r"(a), "r"(v.x), "r"(v.y), "r"(v.z), "r"(v.w), "n"(OFF) : "memory");
}
template <int HOP> struct Prefill {
    uint32_t a0, a1;
    __device__ __forceinline__ Prefill(int lane) {
        const uint32_t q = lane >> 3, i = lane & 7, b = q + (i & 4), c = (q & 1) + (q & 2) * 4 + (i & 6);
        a0 = HOP == 1 ? q * 256 + ((8 + q + i) & 15) * 16 : b * 128 + ((4 + b + (i & 3)) & 7) * 16;
        a1 = HOP == 1 ? q * 256 + 1024 + ((12 + q + i) & 15) * 16 : c * 128 + ((2 + c + (i & 1)) & 7) * 16;
    }
    __device__ __forceinline__ void run(uint32_t win, const uint4& v) const {
#pragma unroll 1
        for (uint32_t w = win; w < win + 16384; w += 8192) {
            sts128<0>(w + a0, v); sts128<2048>(w + a0, v); sts128<4096>(w + a0, v); sts128<6144>(w + a0, v);
            sts128<0>(w + a1, v); sts128<2048>(w + a1, v); sts128<4096>(w + a1, v); sts128<6144>(w + a1, v);
            if (HOP == 2) { sts128<1024>(w + a0, v); sts128<3072>(w + a0, v); sts128<5120>(w + a0, v); sts128<7168>(w + a0, v); }
        }
        if (a0 < 512) sts128<16384>(win + a0, v);
        if (HOP == 2 && a1 < 512) sts128<16384>(win + a1, v);
    }
};
__device__ __forceinline__ bool elect() {
    uint32_t q; asm volatile("{ .reg .pred q; elect.sync _|q, 0xffffffff; selp.u32 %0, 1, 0, q; }" : "=r"(q)); return q;
}
__device__ __forceinline__ const unsigned char* mk_ptr(uint32_t lo, uint32_t hi) { return reinterpret_cast<const unsigned char*>((uint64_t)hi << 32 | lo); }
__device__ __forceinline__ void bulk_store(uint32_t lo, uint32_t hi, uint32_t src, uint32_t n) {
    asm volatile("cp.async.bulk.global.shared::cta.bulk_group [%0], [%1], %2;" ::"l"(mk_ptr(lo, hi)), "r"(src), "r"(n) : "memory");
}
template <int HOP>
__device__ __forceinline__ void manager(const Params& p, uint32_t sb, int lane, int role, uint32_t base) {
    typedef H<HOP> h;
    constexpr int V = h::NBIN / 32, PB = h::S * 8;
    const int RT = p.rounds, lo = HOP == 1 && role >= NG ? NG : 0, hi = lo + h::NBIN;
    const int w = (role - lo) / (HOP * J), page = (HOP - 1) * NC + w, j = (role - lo - w * HOP * J) / HOP;
    const uint32_t par = __reduce_or_sync(0xffffffffu, lds32(sb + W_PAR)) >> page & 1u, side = lds32(sb + W_SIDE);
    const uint64_t pg = reinterpret_cast<uint64_t>(p.ring) + (uint64_t)page * PAGE;
    const uint32_t dhi = pg >> 32;
    const uint32_t c0 = HOP == 2 ? role & 1 : 0, up = (HOP == 1 && lo) ^ par ^ c0;
    uint32_t dA = ((uint32_t)pg + src_off(j) + (c0 << 16) + (up ? 4096 : 12288)) ^ slot_off(base % 3) ^ alt(page);
    uint32_t dM = ((uint32_t)pg + src_off(j) + MID + c0 * 2048 + (par << 12)) ^ slot_off(base % 3) ^ alt(page);
    const int a0 = max(64, lo), b1 = min(68, hi);
    int n0 = (min(NHI, hi) - a0) * PB, a1 = (max(NLO, lo) - lo) * PB;
    const unsigned char* cr = reinterpret_cast<const unsigned char*>(pg) + (MISC ^ alt(page)) + ((side ^ par) << 12) + lo * 4;
    const unsigned char* cr0 = cr + lane * V * 4, *cr1 = cr + (32 * V + min(lane, V - 1)) * 4;
    const uint32_t ca0 = sb + h::CNT + lane * V * 4, ca1 = sb + h::CNT + (32 * V + min(lane, V + NDUM - 1)) * 4;
    const uint32_t rot0 = (lane * V & 7) * 16, rot1 = lane < V ? lane * 16 : 0x80000000u;
    const Prefill<HOP> pf(lane);
    uint4 nul = nulls<HOP>(lane, base + HOP);
    uint32_t st = slot_steps(base);
    uint32_t init = h::init(base), prim = sb + h::STG + (HOP == 1 ? h::win(base) : 0u);
    uint32_t cs[5];
    auto sample = [&]() {
        if (V == 2) asm volatile("ld.relaxed.gpu.global.v2.u32 {%0,%1}, [%2];" : "=r"(cs[0]), "=r"(cs[1]) : "l"(cr0) : "memory");
        else asm volatile("ld.relaxed.gpu.global.v4.u32 {%0,%1,%2,%3}, [%4];" : "=r"(cs[0]), "=r"(cs[1]), "=r"(cs[2]), "=r"(cs[3]) : "l"(cr0) : "memory");
        cs[V] = ld_rlx32(reinterpret_cast<const uint32_t*>(cr1));
    };
    sample();
    uint32_t c[5];
    TK_DECL
#pragma unroll 1
    for (int r = 0;; r++) {
        const uint32_t R = base + r, ninit = h::init(R + 1), done = prim;
        TK(5)
        mbar_wait(sb + B_FULL + (HOP - 1) * 8, r & 1);
        TK(0)
        if (V == 2) asm volatile("ld.shared.v2.u32 {%0,%1}, [%2];" : "=r"(c[0]), "=r"(c[1]) : "r"(ca0) : "memory");
        else asm volatile("ld.shared.v4.u32 {%0,%1,%2,%3}, [%4];" : "=r"(c[0]), "=r"(c[1]), "=r"(c[2]), "=r"(c[3]) : "r"(ca0) : "memory");
        c[V] = lds32(ca1);
        uint32_t nc[5], low = c[V];
#pragma unroll
        for (int k = 0; k <= V; k++) {
            const uint32_t z = ninit + (k < V ? rot0 + k * 16 : rot1);
            nc[k] = min(max(c[k] + (ninit - init - h::S * h::INC), z), z + (h::CAP - h::S) * h::INC);
            low = min(low, c[k]);
        }
        if (V == 2) sts64(ca0, nc[0], nc[1]); else sts128<0>(ca0, make_uint4(nc[0], nc[1], nc[2], nc[3]));
        sts32(ca1, nc[V]);
        __syncwarp();
        if (lane == 0) mbar_arrive(sb + B_OPEN + (HOP - 1) * 8);
        TK(1)
        if (low < init + (h::PRE << h::SH) && r != RT - 1) {
            const uint32_t gb = init & 1u << h::TB, vx = HOP == 1 ? NB | gb : 0x08000800u, vy = HOP == 1 ? nul.y : 0x28000800u | gb;
#pragma unroll 1
            for (int k = 0; k <= V; k++) {
                const uint32_t bin = k < V ? lane * V + k : 32 * V + lane;
#pragma unroll 1
                for (uint32_t x = pick(k, c); x < init + (h::PRE << h::SH); x += h::INC) sts64(prim + bin * PB + (x & h::PM), vx, vy);
            }
        }
        __syncwarp();
        TK(2)
        asm volatile("fence.proxy.async.shared::cta;" ::: "memory");
        TK(6)
        if (r >= D) {
            int it = 0;
            while (true) {
                uint32_t bad = 0;
#pragma unroll
                for (int k = 0; k <= V; k++) bad |= cs[k] - (R - D + 1);
                if (!__any_sync(0xffffffffu, bad >> 20)) break;
                if (++it > SPIN_LIMIT) __trap();
                if (it > 1) __nanosleep(100);
                sample();
            }
        }
        TK(3)
        const bool last = r == RT - 2 - HOP;
        if (elect()) {
            const uint32_t dB = (HOP == 1 ? dA ^ 0x10000u : dA) + (up ? 8192 : -8192), sm = prim + (lo ? 2 * PB : 0);
            bulk_store(dA, dhi, sm, 8192);
            bulk_store(dB, dhi, HOP == 1 ? sm + 8192 : prim + 68 * PB, 8192);
            if (n0 > 0) bulk_store(dM + (a0 - 64) * PB, dhi, prim + (a0 - lo) * PB, n0);
            if (a1 < (b1 - lo) * PB) bulk_store((dM ^ 4096u) + (uint32_t)((lo - NLO) * PB + a1), dhi, prim + a1, (b1 - lo) * PB - a1);
            asm volatile("cp.async.bulk.commit_group;" ::: "memory");
            asm volatile("cp.async.bulk.wait_group.read 0;" ::: "memory");
            if (HOP == 1 && !last) mbar_arrive(sb + B_FREE);
        }
        __syncwarp();
        TK(4)
        prim = HOP == 1 ? prim ^ 0x20000u : prim >= sb + 0x30000u ? sb : prim + (prim - sb) + 0x10000u;
        if (r == RT - 1) break;
        if (h::lap(R + HOP) & 1u << (h::TB - 1)) {
            if (HOP == 1) { nul.x ^= 1u << h::TB; nul.z ^= 1u << h::TB; }
            else { nul.y ^= 1u << h::TB; nul.w ^= 1u << h::TB; }
        }
        if (!last) pf.run(done, nul);
        else {
#pragma unroll 1
            for (uint32_t a = done + lane * 16; a < done + WIN; a += 512) sts128<0>(a, nul);
            __syncwarp();
            if (HOP == 1 && lane == 0) mbar_arrive(sb + B_FREE);
        }
        if (r == D - 1 || r == RT - D - 1) {
            uint32_t n = NHI, m = NLO;
            if (r < RT - D - 1) {
                int it = 0;
                while (true) {
                    n = ld_rlx32(reinterpret_cast<const uint32_t*>(p.ring + M_CNT + (side << 12)));
                    if ((n & 0xffffu) + (n >> 16) == NB) break;
                    if (++it > SPIN_LIMIT) __trap();
                }
                m = n = min(max(__reduce_or_sync(0xffffffffu, n) & 0xffffu, (uint32_t)NLO), (uint32_t)NHI);
            }
            n0 = (min((int)n, hi) - a0) * PB;
            a1 = (max((int)m, lo) - lo) * PB;
        }
        sample();
        slot_next(dA, st); slot_next(dM, st);
        st = slot_rot(st);
        init = ninit;
    }
#pragma unroll 1
    for (int k = 0; k <= V; k++) {
        const uint32_t bin = k < V ? lane * V + k : 32 * V + lane, n = bin < h::NBIN ? min((pick(k, c) - init) >> h::SH, (uint32_t)h::CAP) : 0u;
#pragma unroll 1
        for (uint32_t x = h::S; x < n; x++) {
            const uint2 w = lds64(prim + bin * PB + ((x + (bin & 7) * 2) & (h::S - 1)) * 8);
            if (HOP == 1) slow_rec1(p, w.x, w.y, bin);
            else slow_rec2(p, w.x, w.y, bin, __uint_as_float(lds32(sb + W_UNIT)));
        }
    }
    asm volatile("cp.async.bulk.wait_group 0;" ::: "memory");
    TK_OUT
}

#define POLL_NS 200
#define POLL_NS3 1500
template <int HOP> struct Reader {
    uint32_t lo, hi, st;
    uint32_t* cred;
    __device__ __forceinline__ void init(const Params& p, uint32_t sb, int w, int lane, int role, uint32_t base) {
        constexpr int PB = H<HOP>::S * 8;
        const int page = (HOP - 1) * NC + w, first = HOP == 1 ? (role >= NG ? NG : 0) + w * J : w * 2 * J;
        const uint32_t par = lds32(sb + W_PAR) >> page & 1u, side = lds32(sb + W_SIDE);
        const uint64_t pg = reinterpret_cast<uint64_t>(p.ring) + (uint64_t)page * PAGE;
        const bool mid = side ? role < 68 : role >= 64;
        const uint32_t i = role - (side ? (mid ? NLO : 68) : (mid ? 64 : 0));
        const uint32_t c = HOP == 1 ? i >> 5 : lane >> 4, in = HOP == 1 ? (i & 31) * PB + lane * 8 : i * PB + (lane & 15) * 8;
        lo = ((uint32_t)pg + in + (mid ? MID + c * 2048 + ((side ^ par) << 12) : (c << 16) + (side ^ par ^ c ? 4096 : 12288))) ^ slot_off(base % 3) ^ alt(page);
        hi = pg >> 32;
        st = slot_steps(base);
        const bool both = first >= NLO && first < NHI;
        cred = lane < 1 + both ? reinterpret_cast<uint32_t*>(pg + (MISC ^ alt(page)) + (((both ? lane : first >= NG) ^ par) << 12)) + role : nullptr;
    }
    template <int K> __device__ __forceinline__ void load1(uint2& v) const {
        asm volatile("ld.relaxed.gpu.global.v2.u32 {%0,%1}, [%2+%3];" : "=r"(v.x), "=r"(v.y) : "l"(mk_ptr(lo, hi)), "n"(src_off(K)) : "memory");
    }
    template <int K> __device__ __forceinline__ void again(uint2& v, uint32_t want) const {
        asm volatile("{ .reg .pred q; .reg .u32 t; xor.b32 t, %4, %3; and.b32 t, t, %5; setp.ne.u32 q, t, 0;\n"
                     "@q ld.relaxed.gpu.global.v2.u32 {%0,%1}, [%2+%6]; }"
                     : "+r"(v.x), "+r"(v.y) : "l"(mk_ptr(lo, hi)), "r"(want), "r"(HOP == 1 ? v.x : v.y), "n"(1u << H<HOP>::TB), "n"(src_off(K)) : "memory");
    }
    __device__ __forceinline__ void load(uint2 (&rec)[J]) const {
        load1<0>(rec[0]); load1<1>(rec[1]); load1<2>(rec[2]); load1<3>(rec[3]); load1<4>(rec[4]); load1<5>(rec[5]);
    }
    __device__ __forceinline__ void check(uint2 (&rec)[J], uint32_t R, uint32_t ns TK_ARG) {
        constexpr uint32_t BIT = 1u << H<HOP>::TB;
        const uint32_t want = H<HOP>::lap(R);
        int it = 0;
        while (true) {
            uint32_t bad = 0;
#pragma unroll
            for (int j = 0; j < J; j++) bad |= (HOP == 1 ? rec[j].x : rec[j].y) ^ want;
            if (!__any_sync(0xffffffffu, bad & BIT)) break;
            if (++it > SPIN_LIMIT) __trap();
            __nanosleep(ns);
            TK_CNT(7)
            again<0>(rec[0], want); again<1>(rec[1], want); again<2>(rec[2], want); again<3>(rec[3], want); again<4>(rec[4], want); again<5>(rec[5], want);
        }
        if (cred) st_rlx32(cred, R + 1);
        slot_next(lo, st);
        st = slot_rot(st);
    }
    __device__ __forceinline__ void finish() const { if (cred) st_rlx32(cred, 0u); }
};

#define NPROBE 9
__device__ __forceinline__ uint32_t near_half(unsigned char* pair, uint32_t zero) {
#pragma unroll
    for (int i = 0; i < 4; i++) *reinterpret_cast<uint4*>(pair + (i >> 1) * 4096 + (i & 1) * 16) = make_uint4(0u, 0u, 0u, 0u);
    uint32_t best[2] = {~0u, ~0u}, v = 0, prev = 0;
    asm volatile("red.relaxed.gpu.global.add.u32 [%0], 1;" ::"l"(pair + 4096) : "memory");
#pragma unroll
    for (int t = 0; t <= NPROBE; t++) {
        uint32_t now;
        asm volatile("atom.relaxed.gpu.global.add.u32 %0, [%1], 1;" : "=r"(v) : "l"(pair + (t & 1) * 4096 + (v & zero)) : "memory");
        asm volatile("mov.u32 %0, %%clock;" : "=r"(now) :: "memory");
        if (t > 1) best[(t - 1) & 1] = min(best[(t - 1) & 1], now - prev);
        prev = now;
    }
    return (best[1] < best[0] ? 1u : 0u) | (v & zero);
}
template <bool B> struct BoolC { static constexpr bool value = B; };

template <int NP>
__device__ __forceinline__ void stage1(const Params& p, uint32_t sb, const int pos0, int lane, uint32_t base) {
    typedef H<1> h;
    const int RT = p.rounds;
    uint32_t ff = *reinterpret_cast<const uint16_t*>(p.ang_freq) * 0x10001u;
    auto pair_of = [&](int r, int pos) {
        const int q = r < RT - 1 ? (r * NB + blockIdx.x) * NPR + pos : (RT - 1) * NB * NPR + blockIdx.x * p.lastn + pos;
        return (r < RT - 1 || (r == RT - 1 && pos < p.lastn)) && q < p.T2 ? q : -1;
    };
    uint2 vi[NP], vo[NP]; uint32_t va[NP];
    auto load_edge = [&](int r) {
#pragma unroll
        for (int u = 0; u < NP; u++) {
            const int q = max(pair_of(r, pos0 + u * 32), 0);
            vi[u] = ld_in(p.idx_in + q); vo[u] = ld_in(p.idx_out + q); va[u] = ld_in(p.angle + q);
        }
    };
    load_edge(0);
    if (blockIdx.x == 0 && pos0 == 0 && (p.T & 1)) {
        const int t = p.T - 1;
        slow_triplet(p, reinterpret_cast<const uint32_t*>(p.idx_in)[t], reinterpret_cast<const uint32_t*>(p.idx_out)[t],
                     bf16r(cos_bf(hmul_bf2(reinterpret_cast<const uint16_t*>(p.angle)[t], ff) & 0xffffu)));
    }
    for (int i = threadIdx.x * 16; i < p.R2 && blockIdx.x * p.R2 + i < p.E; i += NS1 * 32 * 16) prefetch_l2(p.m + blockIdx.x * p.R2 + i);
    uint32_t R = __reduce_or_sync(0xffffffffu, base);
    ff = __reduce_or_sync(0xffffffffu, ff);
    bar_sync(BAR_S1, (NS1 + 1) * 32);
    TK_DECL
    auto step = [&](const int r, const int qn, auto edge) {
        constexpr bool EDGE = decltype(edge)::value;
        uint32_t cc[NP], big = 0;
#pragma unroll
        for (int u = 0; u < NP; u++) {
            va[u] = hmul_bf2(va[u], ff);
            cc[u] = pack_bf2(__cosf(bf_lo(va[u])), __cosf(bf_hi(va[u])));
            big = __vmaxu2(big, va[u] & 0x7fff7fffu);
        }
        if ((big + (0x7fffu - BIGX) * 0x10001u) & 0x80008000u) {
#pragma unroll 1
            for (int u = 0; u < NP; u++) {
                const uint32_t a = pick(u, va);
                float c0 = cos_bf(a & 0xffffu), c1 = cos_bf(a >> 16);
                if ((c0 != c0 || c1 != c1) && (!EDGE || pair_of(r, pos0 + u * 32) >= 0)) {
                    const uint2 i2 = pick(u, vi), o2 = pick(u, vo);
                    if (c0 != c0) slow_triplet(p, i2.x, o2.x, c0);
                    if (c1 != c1) slow_triplet(p, i2.y, o2.y, c1);
                }
                const uint32_t v = pack_bf2(c0 != c0 ? 0.f : c0, c1 != c1 ? 0.f : c1);
#pragma unroll
                for (int k = 0; k < NP; k++) if (k == u) cc[k] = v;
            }
        }
        uint32_t bin[2 * NP], x[2 * NP], y[2 * NP];
#pragma unroll
        for (int j = 0; j < 2 * NP; j++) {
            const uint32_t ii = j & 1 ? vi[j >> 1].y : vi[j >> 1].x, oo = j & 1 ? vo[j >> 1].y : vo[j >> 1].x;
            bin[j] = __umulhi(ii, p.mg1);
            y[j] = __byte_perm(bin[j] * p.k1 + ii, cc[j >> 1], j & 1 ? 0x7610 : 0x5410);
            const uint32_t bo = __umulhi(oo, p.mg2);
            x[j] = __byte_perm(bo * p.k2 + oo * 4u, bo, 0x0514);
            if (EDGE && pair_of(r, pos0 + (j >> 1) * 32) < 0) bin[j] = NG + (lane & (NDUM - 1));
        }
        if (EDGE) load_edge(r + 1);
        else {
            uint32_t dep = 0;
#pragma unroll
            for (int j = 0; j < 2 * NP; j++) dep |= x[j] | y[j];
            const int q = qn + (dep & p.zero);
#pragma unroll
            for (int u = 0; u < NP; u++) { vi[u] = ld_in(p.idx_in + q + u * 32); vo[u] = ld_in(p.idx_out + q + u * 32); va[u] = ld_in(p.angle + q + u * 32); }
        }
        const uint32_t init = h::init(R), kb = sb + h::win(R + 1), lim = init + (h::CAP << h::SH);
        TK(0)
        mbar_wait(sb + B_OPEN, ~R & 1);
        TK(1)
        bool freed = false;
        uint32_t over = 0;
#pragma unroll
        for (int g = 0; g < 2 * NP; g += 4) {
            uint32_t ret[4];
#pragma unroll
            for (int j = 0; j < 4; j++) ret[j] = atoms_add<h::CNT>(sb + bin[g + j] * 4, h::INC);
            const int mx = max(max((int)ret[0], (int)ret[1]), max((int)ret[2], (int)ret[3]));
            if (!freed && __any_sync(0xffffffffu, mx >= (int)(init + 0x10000u))) { TK(2) mbar_wait(sb + B_FREE, ~R & 1); freed = true; TK(3) }
            TK(2)
#pragma unroll
            for (int j = 0; j < 4; j++) {
                x[g + j] = and_or<1u << h::TB>(ret[j], x[g + j]);
                put_rec<h::STG>(ret[j], lim, and_xor(ret[j], 0x20000u | h::PM, bin[g + j] * 256 + kb), x[g + j], y[g + j]);
            }
            if (mx >= (int)lim) {
#pragma unroll
                for (int j = 0; j < 4; j++) if ((int)ret[j] >= (int)lim) over |= 1u << (g + j);
            }
        }
        __syncwarp();
        if (elect()) mbar_arrive(sb + B_FULL);
        R++;
        TK(4)
#pragma unroll 1
        while (over) {
            TK_CNT(7)
            const int j = __ffs(over) - 1;
            over &= over - 1;
            slow_rec1(p, pick(j, x), pick(j, y), pick(j, bin));
        }
        __syncwarp();
    };
#pragma unroll 1
    for (int q = (NB + blockIdx.x) * NPR; q < p.qfull; q += NB * NPR) step(q / (NB * NPR) - 1, q + pos0, BoolC<false>());
#pragma unroll 1
    for (int r = max(p.qfull / (NB * NPR) - 1, 0); r < RT; r++) step(r, 0, BoolC<true>());
    TK_OUT
}

__device__ __forceinline__ void stage2(const Params& p, uint32_t sb, int w, int lane, int role, uint32_t base) {
    typedef H<2> h;
    const int RT = p.rounds;
    Reader<1> rd;
    rd.init(p, sb, w, lane, role, base);
    uint2 rec[J];
    rd.load(rec);
    bar_sync(BAR_TABLE, 2 * NC * 32);
    uint32_t kb = sb + 0x10000u, am = 0x10000u | h::PM;
    TK_DECL
#pragma unroll 1
    for (int r = 0; r < RT; r++) {
        rd.check(rec, base + r, POLL_NS TK_PASS);
        TK(0)
        uint2 mv[J];
#pragma unroll
        for (int j = 0; j < J; j++) mv[j] = lds64<OFF_M>(sb + (rec[j].y & 0xffffu) * 8);
        uint32_t fl = 0;
#pragma unroll
        for (int j = 0; j < J; j++) fl |= mv[j].y;
        if (fl & 0x40000000u) {
#pragma unroll 1
            for (int j = 0; j < J; j++) {
                const uint2 v = pick(j, mv), w = pick(j, rec);
                if ((v.y & 0x40000000u) && (w.x & 0xffu) < NB) {
                    if (v.x & 0x40000000u) slow_rec1(p, w.x, w.y, lds32(sb + W_ROLE) % NG);
                    else {
                        const float c = bf_hi(w.y), s = __uint_as_float(lds32(sb + W_UNIT)) * 1024.f;
                        side_add(w.x & 0xffu, __byte_perm(w.x, 0u, 0x4413) >> 2, c * (bf_lo(v.x) * s), c * (bf_hi(v.x) * s),
                                 c * (bf_lo(v.y) * s), c * (bf_hi(v.y & 0xbfffffffu) * s));
                    }
                }
            }
#pragma unroll
            for (int j = 0; j < J; j++) if (mv[j].y & 0x40000000u) rec[j].x = NB;
        }
        uint32_t w0[J], w1[J], bin[J], ret[J];
#pragma unroll
        for (int j = 0; j < J; j++) {
            const float c = bf_hi(rec[j].y), MG = 8194.0f;
            const uint32_t x = rec[j].x;
            w0[j] = and_or<0xf000f000u>(x, __byte_perm(__float_as_uint(fmaf(c, bf_lo(mv[j].x), MG)), __float_as_uint(fmaf(c, bf_hi(mv[j].x), MG)), 0x5410));
            w1[j] = and_or<0xf000f000u>(x << 4, __byte_perm(__float_as_uint(fmaf(c, bf_lo(mv[j].y), MG)), __float_as_uint(fmaf(c, bf_hi(mv[j].y), MG)), 0x5410));
            bin[j] = x & 0xffu;
        }
        const uint32_t lim = h::init(base + r) + 0x20000u;
        rd.load(rec);
        TK(1)
        mbar_wait(sb + B_OPEN + 8, (r - 1) & 1);
        TK(2)
#pragma unroll
        for (int j = 0; j < J; j++) ret[j] = atoms_add<h::CNT>(sb + bin[j] * 4, h::INC);
        int mx = -1;
#pragma unroll
        for (int j = 0; j < J; j++) {
            w1[j] = and_or<1u << h::TB>(ret[j], w1[j]);
            put_rec<0>(ret[j], lim, and_xor(ret[j], am, bin[j] * 128 + kb), w0[j], w1[j]);
            mx = max(mx, (int)ret[j]);
        }
        __syncwarp();
        if (lane == 0) mbar_arrive(sb + B_FULL + 8);
        TK(3)
        if (mx >= (int)lim) {
#pragma unroll 1
            for (int j = 0; j < J; j++)
                if ((int)pick(j, ret) >= (int)lim) slow_rec2(p, pick(j, w0), pick(j, w1), pick(j, bin), __uint_as_float(lds32(sb + W_UNIT)));
        }
        __syncwarp();
        am = am >= 0x30000u ? 0x10000u | h::PM : am + 0x10000u;
        kb ^= am & 0x30000u;
        TK(4)
    }
    rd.finish();
    TK_OUT
}

__device__ __forceinline__ float2 acc_fix(uint32_t old, uint32_t q) {
    const uint32_t u = old + 0x40004000u, n = u + q - 0x08000800u;
    return make_float2((float)((int)(u & 0xffffu) + (int)(q & 0xffffu) - 2048 - (int)(n & 0xffffu)), (float)((int)(u >> 16) + (int)(q >> 16) - 2048 - (int)(n >> 16)));
}
__device__ __forceinline__ void stage3(const Params& p, uint32_t sb, int w, int lane, int role, uint32_t base) {
    const int RT = p.rounds;
    Reader<2> rd;
    rd.init(p, sb, w, lane, role, base);
    uint2 rec[J];
    bar_sync(BAR_TABLE, 2 * NC * 32);
    rd.load(rec);
    TK_DECL
#pragma unroll 1
    for (int r = 0; r < RT; r++) {
        rd.check(rec, base + r, r < RT - 2 ? POLL_NS3 : 100 TK_PASS);
        TK(0)
        uint32_t o0[J], o1[J];
        const uint32_t ab = sb - (H<2>::lap(base + r) >> 27 & 2u);
                auto odd = [&](uint32_t aux) { return lane & 1u; };
        uint32_t ad[J];
#pragma unroll
        for (int j = 0; j < J; j++) { ad[j] = aux_of(rec[j].x, rec[j].y); o0[j] = odd(ad[j]); }
#pragma unroll
        for (int j = 0; j < J; j++) {
            const uint32_t t = o0[j], a = ab + ad[j] * 2;
            const uint32_t v0 = (rec[j].x & 0x0fff0fffu) - 0x08000800u, v1 = (rec[j].y & 0x0fff0fffu) - 0x08000800u;
            o0[j] = t ? v1 : v0; o1[j] = t ? v0 : v1;
            if (!(rec[j].y & 0x20000000u)) {
                o0[j] = atoms_add<OFF_ACC>(a + t * 4, o0[j]);
                o1[j] = atoms_add<OFF_ACC + 4>(a - t * 4, o1[j]);
            }
        }
        uint32_t g = 0;
#pragma unroll
        for (int j = 0; j < J; j++) g |= o0[j] | o1[j];
        if (__any_sync(0xffffffffu, g & 0x80008000u)) {
#pragma unroll 1
            for (int j = 0; j < J; j++) {
                const uint2 w = pick(j, rec);
                const uint32_t aux = aux_of(w.x, w.y), t = odd(aux), p0 = pick(j, o0), p1 = pick(j, o1);
                const float2 a = acc_fix(t ? p1 : p0, w.x & 0x0fff0fffu), b = acc_fix(t ? p0 : p1, w.y & 0x0fff0fffu);
                const float unit = __uint_as_float(lds32(sb + W_UNIT));
                if (a.x != 0.f || a.y != 0.f || b.x != 0.f || b.y != 0.f)
                    side_add(lds32(sb + W_ROLE), aux >> 2, a.x * unit, a.y * unit, b.x * unit, b.y * unit);
                __syncwarp();
            }
        }
        rd.load(rec);
        TK(1)
    }
    rd.finish();
    TK_OUT
}

__device__ __forceinline__ uint32_t row_max(uint32_t x, uint32_t y) {
    const uint32_t mx = __vmaxu2(x & 0x7fff7fffu, y & 0x7fff7fffu);
    return max(mx & 0xffffu, mx >> 16);
}
constexpr int EWIN = 5;

__global__ void __launch_bounds__(NTHR, 1) fused_kernel(const Params p) {
    const int tid = threadIdx.x, lane = tid & 31;
    const int hw = __reduce_max_sync(0xffffffffu, tid >> 5);
    const uint32_t sb = __reduce_or_sync(0xffffffffu, (uint32_t)__cvta_generic_to_shared(smem));
    TKX(0)
    const uint32_t epoch = ld_rlx32(&g_base);
    uint32_t base = epoch & 7u;

    if (hw < NS1) {
        if (hw < NS1 - 1) stage1<4>(p, sb, hw * 128 + lane, lane, base);
        else stage1<NPR / 32 - (NS1 - 1) * 4>(p, sb, hw * 128 + lane, lane, base);
        __threadfence();
        bar_arrive(BAR_DONE, (NS1 + NC + 2) * 32);
    } else if (hw == W_M1) {
        if (lane == 0) {
            if (sb & 255u) __trap();
            mbar_init(sb + B_FULL, NS1); mbar_init(sb + B_OPEN, 1); mbar_init(sb + B_FREE, 1);
        }
        base = __reduce_or_sync(0xffffffffu, base);
        if (lane == 0 && (base & 1u)) { mbar_arrive(sb + B_OPEN); mbar_arrive(sb + B_FREE); }
        for (int i = lane; i < NG + NDUM; i += 32) sts32(sb + OFF_CNT1 + i * 4, H<1>::init(base) + (i < NG ? (i & 7) * 16 : 0x80000000u));
#pragma unroll 1
        for (int i = 0; i < 2; i++) Prefill<1>(lane).run(sb + OFF_H1 + H<1>::win(base + i), nulls<1>(lane, base + i));
        bar_arrive(BAR_S1, (NS1 + 1) * 32);
        bar_sync(BAR_PROBE, (2 * NC + 1) * 32);
        {
            const uint32_t raw = __ballot_sync(0xffffffffu, lane < 2 * NC && smem[OFF_PROBE + lane]), side = raw & 1u;
            uint32_t v = 0;
            if (lane < 2) asm volatile("atom.relaxed.gpu.global.add.u32 %0, [%1], %2;" : "=r"(v) : "l"(p.ring + M_CNT + lane * 4096), "r"(side ? 0x10000u : 1u) : "memory");
            const uint32_t mine = (side ? ~raw : raw) | 0x80000000u;
            if (lane == 2) asm volatile("atom.relaxed.gpu.global.cas.b32 %0, [%1], 0, %2;" : "=r"(v) : "l"(p.ring + M_PAR), "r"(mine) : "memory");
            bar_sync(BAR_HIST, (2 * NC + 1) * 32);
            uint32_t best = 0;
#pragma unroll 1
            for (int e = 11 + lane; e <= 230; e += 32) {
                uint32_t c = 0;
#pragma unroll
                for (int i = 0; i < EWIN; i++) c += lds32(sb + OFF_HIST + (e - i) * 4);
                best = max(best, c << 8 | (255 - e));
            }
            const uint32_t e = 255 - (__reduce_max_sync(0xffffffffu, best) & 255u);
            if (lane == 0) {
                const uint32_t role = side ? NB - 1 - (v >> 16) : v & 0xffffu;
                sts32(sb + W_ROLE, role); sts32(sb + W_SIDE, role < NLO ? 0u : role >= NHI ? 1u : side);
                sts32(sb + W_EXP, e); sts32(sb + W_UNIT, (e - 10) << 23); sts32(sb + W_END, (epoch | 7u) + 1u + (base + p.rounds) % 6u);
            }
            if (lane == 2) sts32(sb + W_PAR, v ? v : mine);
        }
        bar_sync(BAR_ROLE, (2 * NC + 2) * 32);
        manager<1>(p, sb, lane, __reduce_max_sync(0xffffffffu, lds32(sb + W_ROLE)), base);
        bar_arrive(BAR_H1, (NS1 + 1) * 32);
        __threadfence();
        bar_arrive(BAR_DONE, (NS1 + NC + 2) * 32);
    } else if (hw == W_M2) {
        const float wd = __bfloat162float(lane & 16 ? p.w_up[lane & 15] : p.w_down[lane & 15]);
        const float ws = __bfloat162float(p.w_sbf[lane]), wr = __bfloat162float(p.w_rbf[lane]);
        const __nv_bfloat16 cen = p.centers[lane & 7];
        if (lane == 0) { mbar_init(sb + B_FULL + 8, NC); mbar_init(sb + B_OPEN + 8, 1); }
        base = __reduce_or_sync(0xffffffffu, base);
        for (int i = lane; i < NB + NDUM; i += 32) sts32(sb + OFF_CNT2 + i * 4, H<2>::init(base) + (i < NB ? (i & 7) * 16 : 0x80000000u));
#pragma unroll 1
        for (int i = 0; i < 3; i++) Prefill<2>(lane).run(sb + H<2>::win(i), nulls<2>(lane, base + i));
        reinterpret_cast<float*>(smem + OFF_WSM)[lane] = wd;
        reinterpret_cast<float*>(smem + OFF_WG)[lane] = ws;
        reinterpret_cast<float*>(smem + OFF_WG + 128)[lane] = wr;
        reinterpret_cast<__nv_bfloat16*>(smem + OFF_WG + 256)[lane & 7] = cen;
        bar_sync(BAR_ROLE, (2 * NC + 2) * 32);
        manager<2>(p, sb, lane, __reduce_max_sync(0xffffffffu, lds32(sb + W_ROLE)), base);
        __threadfence();
        bar_sync(BAR_DONE, (NS1 + NC + 2) * 32);
        if (lane < 2) { __threadfence(); st_rlx32(reinterpret_cast<uint32_t*>(p.ring + M_FLAG + lane * 4096) + blockIdx.x, lds32(sb + W_END)); }
    } else {
        const int pw = __reduce_max_sync(0xffffffffu, hw < W_M1 ? hw - NS1 : hw - NS1 - 1), ct = pw * 32 + lane;
        constexpr int CT = 2 * NC * 32;
        const uint4 sm = __ldg(reinterpret_cast<const uint4*>(p.m) + min((ct >> 3) * (p.E >> 1) / (CT / 8) + (lane & 7), (p.E >> 1) - 1));
        if (ct < 256) sts32(sb + OFF_HIST + ct * 4, 0u);
        if (lane == 0) smem[OFF_PROBE + pw] = near_half(p.ring + (size_t)pw * PAGE + (PROBE + (blockIdx.x & 31) * 128 ^ (blockIdx.x >> 7) * 0x70000u ^ slot_off(blockIdx.x >> 5 & 3) ^ alt(pw)), p.zero);
        TKX(1)
        bar_sync(BAR_PROBE, (2 * NC + 1) * 32);
        {
            const uint32_t m0 = row_max(sm.x, sm.y), m1 = row_max(sm.z, sm.w);
            if (m0) atoms_add<OFF_HIST>(sb + (m0 >> 7) * 4, 1u);
            if (m1) atoms_add<OFF_HIST>(sb + (m1 >> 7) * 4, 1u);
        }
        bar_arrive(BAR_HIST, (2 * NC + 1) * 32);
        base = __reduce_or_sync(0xffffffffu, base);
        for (int i = ct; i < R2MAX / 2; i += CT) reinterpret_cast<uint4*>(smem + OFF_ACC)[i] = make_uint4(0x40004000u, 0x40004000u, 0x40004000u, 0x40004000u);
        bar_sync(BAR_ROLE, (2 * NC + 2) * 32);
        const int role = __reduce_max_sync(0xffffffffu, lds32(sb + W_ROLE));
        TKX(2)
        {
            const int e = lds32(sb + W_EXP), q0 = (role >= NG ? role - NG : role) * (p.R1 >> 1), nq = min(p.R1 >> 1, (p.E >> 1) - q0);
            const uint32_t sc = (uint32_t)(254 - e) * 0x800080u;
            constexpr int CH = (R1MAX / 2 + CT - 1) / CT;
            uint4 v[CH];
#pragma unroll
            for (int u = 0; u < CH; u++) v[u] = __ldg(reinterpret_cast<const uint4*>(p.m) + min(q0 + ct + u * CT, (p.E >> 1) - 1));
            auto conv = [&](uint32_t& x, uint32_t& y) {
                const uint32_t mx = row_max(x, y);
                const int d = e - (int)(mx >> 7);
                x = hmul_bf2(x, sc); y = hmul_bf2(y, sc);
                if (d >= EWIN) y |= 0x40000000u;
                if (d < 0 || (d >= EWIN && e > 127)) { x = 0x40000000u; y = x; }
                if (mx == 0) { x = 0; y = 0; }
            };
#pragma unroll
            for (int u = 0; u < CH; u++) {
                conv(v[u].x, v[u].y); conv(v[u].z, v[u].w);
                if (ct + u * CT < nq) sts128<OFF_M>(sb + (ct + u * CT) * 16, v[u]);
            }
        }
        TKX(3)
        if (hw < W_M1) {
            stage2(p, sb, pw, lane, role, base);
            __threadfence();
            bar_arrive(BAR_DONE, (NS1 + NC + 2) * 32);
        } else {
            stage3(p, sb, pw - NC, lane, role, base);
            __threadfence();
        }
    }
    TKX(4)
    epilogue(p, sb);
}

__global__ void fb_scatter(const uint2* __restrict__ m, const int* __restrict__ idx_in, const int* __restrict__ idx_out,
                           const uint16_t* __restrict__ angle, const __nv_bfloat16* __restrict__ ang_freq, int T, int e0, int e1) {
    const uint32_t fb = *reinterpret_cast<const uint16_t*>(ang_freq);
    for (long long t = blockIdx.x * (long long)blockDim.x + threadIdx.x; t < T; t += (long long)gridDim.x * blockDim.x) {
        int o = idx_out[t];
        if (o < e0 || o >= e1) continue;
        float c = bf16r(cos_bf(hmul_bf2(angle[t], fb) & 0xffffu));
        uint2 v = __ldg(m + idx_in[t]);
        red4(&g_ovf[o - e0], c * bf_lo(v.x), c * bf_hi(v.x), c * bf_lo(v.y), c * bf_hi(v.y));
    }
}
__global__ void fb_final(const Params p, int e0, int e1) {
    int e = e0 + blockIdx.x * blockDim.x + threadIdx.x;
    if (e >= e1) return;
    float4 a4 = g_ovf[e - e0];
    g_ovf[e - e0] = make_float4(0.f, 0.f, 0.f, 0.f);
    float a[4] = {a4.x, a4.y, a4.z, a4.w};
    float d = __bfloat162float(p.dist[e]);
    float g[4] = {0, 0, 0, 0}, h[4] = {0, 0, 0, 0};
    for (int r = 0; r < 8; r++) {
        float df = bf16r(d - __bfloat162float(p.centers[r]));
        float rb = bf16r(expf(bf16r(-10.0f * bf16r(df * df))));
        for (int k = 0; k < 4; k++) {
            g[k] += rb * __bfloat162float(p.w_sbf[r * 4 + k]);
            h[k] += rb * __bfloat162float(p.w_rbf[r * 4 + k]);
        }
    }
    float ag[4];
    for (int k = 0; k < 4; k++) {
        float s = 0.f;
        for (int j = 0; j < 4; j++) s += a[j] * __bfloat162float(p.w_down[j * 4 + k]);
        ag[k] = bf16r(s * g[k]);
    }
    uint2 mv = p.m[e];
    float mm[4] = {bf_lo(mv.x), bf_hi(mv.x), bf_lo(mv.y), bf_hi(mv.y)};
    __nv_bfloat16 o[4];
    for (int k = 0; k < 4; k++) {
        float u = 0.f;
        for (int j = 0; j < 4; j++) u += ag[j] * __bfloat162float(p.w_up[j * 4 + k]);
        o[k] = __float2bfloat16_rn(mm[k] + bf16r(bf16r(u) * bf16r(h[k])));
    }
    p.out[e] = *reinterpret_cast<uint2*>(o);
}

}

static bool exact_div(int E, int lo, int hi, int* R, uint32_t* magic) {
    for (int r = lo + (lo & 1); r <= hi; r += 2) {
        unsigned long long mg = ((1ull << 32) + r - 1) / r, err = mg * r - (1ull << 32);
        if (err * (unsigned long long)E < (1ull << 32)) { *R = r; *magic = (uint32_t)mg; return true; }
    }
    return false;
}

extern "C" void kernel_launch(void* const* d_in, const int* in_sizes, int n_in, void* d_out, int out_size) {
    typedef const __nv_bfloat16* B;
    Params p;
    p.m = (const uint2*)d_in[0]; p.idx_in = (const uint2*)d_in[1]; p.idx_out = (const uint2*)d_in[2]; p.dist = (B)d_in[3];
    p.angle = (const uint32_t*)d_in[4]; p.centers = (B)d_in[5]; p.ang_freq = (B)d_in[6]; p.w_rbf = (B)d_in[7]; p.w_sbf = (B)d_in[8];
    p.w_down = (B)d_in[9]; p.w_up = (B)d_in[10]; p.out = (uint2*)d_out;
    p.E = in_sizes[3]; p.T = in_sizes[1]; p.T2 = p.T >> 1; p.zero = 0;
    p.R1 = p.R2 = p.rounds = p.lastn = p.qfull = 0; p.mg1 = p.mg2 = p.k1 = p.k2 = 0;
    static int ok = -1;
    static unsigned char* ring = nullptr;
    if (ok < 0) {
        void* ra = nullptr;
        cudaGetSymbolAddress(&ra, g_ring);
        ring = reinterpret_cast<unsigned char*>(((uintptr_t)ra + PAGE - 1) & ~(uintptr_t)(PAGE - 1));
        int dev = 0, sms = 0, occ = 0;
        cudaGetDevice(&dev);
        cudaDeviceGetAttribute(&sms, cudaDevAttrMultiProcessorCount, dev);
        cudaError_t e = cudaFuncSetAttribute(fused_kernel, cudaFuncAttributeMaxDynamicSharedMemorySize, SMEM_BYTES);
        if (e == cudaSuccess) e = cudaOccupancyMaxActiveBlocksPerMultiprocessor(&occ, fused_kernel, NTHR, SMEM_BYTES);
        ok = (e == cudaSuccess && occ >= 1 && sms >= NB) ? 1 : 0;
        (void)cudaGetLastError();
    }
    p.ring = ring;
    const bool fused = ok == 1 && p.E <= EMAX && p.E >= 2 * NB && p.E % 2 == 0 && p.T >= 2 && exact_div(p.E, (p.E + NG - 1) / NG, R1MAX, &p.R1, &p.mg1) &&
                       exact_div(p.E, (p.E + NB - 1) / NB, R2MAX, &p.R2, &p.mg2);
    if (fused) {
        p.k1 = 0u - (uint32_t)p.R1; p.k2 = 0u - 4u * (uint32_t)p.R2;
        const int per = NB * NPR;
        int full = p.T2 / per, rest = p.T2 - full * per;
        p.qfull = full * per;
        p.lastn = (rest + NB - 1) / NB;
        if (p.lastn > NPR / 2) { full++; p.lastn = 0; }
        if (full < D) { full = D; p.lastn = 0; }
        p.rounds = full + 1;
        fused_kernel<<<NB, NTHR, SMEM_BYTES>>>(p);
    } else {
        for (int e0 = 0; e0 < p.E; e0 += EMAX) {
            int e1 = p.E - e0 < EMAX ? p.E : e0 + EMAX;
            fb_scatter<<<1056, 256>>>(p.m, (const int*)d_in[1], (const int*)d_in[2], (const uint16_t*)d_in[4], p.ang_freq, p.T, e0, e1);
            fb_final<<<(e1 - e0 + 255) / 256, 256>>>(p, e0, e1);
        }
    }
}
```

```cpp
#include <cuda_runtime.h>
#include <cuda_bf16.h>
#include <stdint.h>

namespace {

constexpr int NB = 132, NG = 66;
constexpr int R2MAX = 6062, R1MAX = 12124;
constexpr int EMAX = NB * R2MAX;
constexpr int NTHR = 1024;
constexpr int NS1 = 8, NC = 11, J = 6;
#define TILES 15
constexpr int NPR = TILES * 64;
constexpr int D = 3;
constexpr int WIN = 16896;
constexpr int NDUM = 16;

constexpr int OFF_ACC = WIN, OFF_BAR = OFF_ACC + R2MAX * 8;
constexpr int OFF_H1 = 0x10000 + WIN, OFF_M = OFF_H1 + WIN, OFF_WSM = OFF_M + R1MAX * 8;
constexpr int OFF_CNT1 = OFF_H1 + 0x20000 + WIN, OFF_CNT2 = OFF_CNT1 + (NG + NDUM + 2) * 4, OFF_WG = OFF_CNT2 + (NB + NDUM) * 4;
constexpr int OFF_HIST = OFF_M;
constexpr int OFF_PROBE = OFF_WSM + 128;
constexpr int SMEM_BYTES = OFF_WG + 272;
static_assert(SMEM_BYTES <= 232448 && OFF_BAR + 64 <= 0x10000 && OFF_PROBE + 32 <= 0x30000, "smem");
static_assert(OFF_BAR % 8 == 0 && OFF_WG % 16 == 0 && OFF_WSM % 16 == 0 && OFF_CNT2 % 16 == 0, "align");
static_assert(NC * J == NG && NC * 32 * 6 * 16 == 2 * WIN, "shape");

template <int HOP> struct H {
    static constexpr int S = HOP == 1 ? 32 : 16, NBIN = HOP == 1 ? NG : NB, CAP = HOP == 1 ? 48 : 32, PRE = HOP == 1 ? 16 : 4, SH = HOP == 1 ? 11 : 12;
    static constexpr int TB = HOP == 1 ? 20 : 28, CNT = HOP == 1 ? OFF_CNT1 : OFF_CNT2, STG = HOP == 1 ? OFF_H1 : 0;
    static constexpr uint32_t INC = (1u << SH) + 8u, PM = (S - 1) * 8;
    static __device__ __forceinline__ uint32_t lap(uint32_t R) { return R * (((1u << TB) + 2u) / 3u); }
    static __device__ __forceinline__ uint32_t gen(uint32_t R) { return lap(R) & 1u << TB; }
    static __device__ __forceinline__ uint32_t init(uint32_t R) { return 0x30000u | gen(R) | (lap(R) & 1u << (TB - 1) ? (1u << TB) - (1u << 18) : 0u); }
    static __device__ __forceinline__ uint32_t win(int r) { return HOP == 1 ? (r & 1) << 17 : (0x310u >> (r % 3 * 4) & 3u) << 16; }
};

constexpr uint32_t PAGE = 1u << 21;
constexpr int NPAGE = NC + 2;
__device__ __align__(256) unsigned char g_ring[(size_t)(NPAGE + 1) * PAGE];
constexpr int MISC = 0xa0000;
constexpr int M_CNT = MISC + 1024, M_PAR = MISC + 1088;
constexpr int M_FLAG = MISC + 2048;
constexpr int PROBE = MISC + 0x40000;
struct Ring {
    uint64_t main, mid;
    uint32_t par;
    __device__ __forceinline__ Ring(const unsigned char* ring, uint32_t pars, int k) {
        main = reinterpret_cast<uint64_t>(ring) + ((uint64_t)k << 20);
        par = pars >> (k >> 1) & 1u;
        mid = reinterpret_cast<uint64_t>(ring) + (uint64_t)NC * PAGE + (((k >> 3 << 20) + (k >> 2 & 1) * 0x11000u + (k & 1) * 2048) ^ (k >> 1 & 1) * 0x3000u ^ (pars >> (NC + (k >> 4)) & 1u) << 12);
    }
};
constexpr int NLO = 60, NHI = 72;
__host__ __device__ constexpr uint32_t src_off(int j) { return (j % 3) << 14 | (j / 3) << 18; }
__device__ __forceinline__ uint32_t slot_off(uint32_t s) { return (0xa930u >> s * 4 & 15u) << 16; }
__device__ __forceinline__ uint32_t slot_steps(uint32_t R) { return (uint32_t)(0x30a09030aull >> (2 - R % 3) * 8) & 0xffffffu; }
__device__ __forceinline__ void slot_next(uint32_t& a, uint32_t st) { a ^= st & 0xf0000u; }
__device__ __forceinline__ uint32_t slot_rot(uint32_t st) { return __byte_perm(st, 0u, 0x4102); }
constexpr int RPAD = 6064, DROW = 6144;
__device__ __align__(128) uint8_t g_dirty[NB * DROW];
__device__ uint32_t g_base = 3;
__device__ __align__(128) float4 g_ovf[NB * RPAD];

struct Params {
    const uint2* m; const uint2* idx_in; const uint2* idx_out; const __nv_bfloat16* dist; const uint32_t* angle;
    const __nv_bfloat16* centers; const __nv_bfloat16* ang_freq; const __nv_bfloat16* w_rbf; const __nv_bfloat16* w_sbf;
    const __nv_bfloat16* w_down; const __nv_bfloat16* w_up; uint2* out; unsigned char* ring;
    int E, T, T2, R1, R2, rounds, lastn, qfull; uint32_t mg1, mg2, k1, k2, zero;
};

__device__ __forceinline__ float bf16r(float x) { return __bfloat162float(__float2bfloat16_rn(x)); }
__device__ __forceinline__ float bf_lo(uint32_t v) { return __uint_as_float(v << 16); }
__device__ __forceinline__ float bf_hi(uint32_t v) { return __uint_as_float(v & 0xffff0000u); }
__device__ __forceinline__ void red4(float4* a, float x, float y, float z, float w) {
    asm volatile("red.global.add.v4.f32 [%0], {%1,%2,%3,%4};" ::"l"(a), "f"(x), "f"(y), "f"(z), "f"(w) : "memory");
}
__device__ __forceinline__ void bar_sync(int id, int n) { __syncwarp(); asm volatile("bar.sync %0, %1;" ::"r"(id), "r"(n) : "memory"); }
__device__ __forceinline__ void bar_arrive(int id, int n) { __syncwarp(); asm volatile("bar.arrive %0, %1;" ::"r"(id), "r"(n) : "memory"); }
template <int OFF> __device__ __forceinline__ uint32_t atoms_add(uint32_t addr, uint32_t v) {
    uint32_t r; asm volatile("atom.shared.add.u32 %0, [%1+%3], %2;" : "=r"(r) : "r"(addr), "r"(v), "n"(OFF) : "memory"); return r;
}
__device__ __forceinline__ void sts64(uint32_t addr, uint32_t x, uint32_t y) {
    asm volatile("st.shared.v2.u32 [%0], {%1,%2};" ::"r"(addr), "r"(x), "r"(y) : "memory");
}
__device__ __forceinline__ void sts32(uint32_t addr, uint32_t x) { asm volatile("st.shared.u32 [%0], %1;" ::"r"(addr), "r"(x) : "memory"); }
template <int OFF = 0> __device__ __forceinline__ uint2 lds64(uint32_t addr) {
    uint2 v; asm volatile("ld.shared.v2.u32 {%0,%1}, [%2+%3];" : "=r"(v.x), "=r"(v.y) : "r"(addr), "n"(OFF) : "memory"); return v;
}
__device__ __forceinline__ uint32_t lds32(uint32_t addr) {
    uint32_t v; asm volatile("ld.shared.u32 %0, [%1];" : "=r"(v) : "r"(addr) : "memory"); return v;
}
__device__ __forceinline__ uint32_t ld_rlx32(const uint32_t* p) {
    uint32_t v; asm volatile("ld.relaxed.gpu.global.u32 %0, [%1];" : "=r"(v) : "l"(p) : "memory"); return v;
}
__device__ __forceinline__ uint2 ld_rlx64(const void* p) {
    uint2 v; asm volatile("ld.relaxed.gpu.global.v2.u32 {%0,%1}, [%2];" : "=r"(v.x), "=r"(v.y) : "l"(p) : "memory"); return v;
}
__device__ __forceinline__ float4 ld_rlx128f(const float4* p) {
    float4 v; asm volatile("ld.relaxed.gpu.global.v4.f32 {%0,%1,%2,%3}, [%4];" : "=f"(v.x), "=f"(v.y), "=f"(v.z), "=f"(v.w) : "l"(p) : "memory"); return v;
}
__device__ __forceinline__ void take3(float4* p, uint32_t mask, float4 (&v)[3]) {
    asm volatile("{ .reg .b128 a, b, c; .reg .b64 x, y; .reg .pred q0, q1, q2; .reg .b32 t;\n"
                 "mov.b64 x, 0; mov.b128 a, {x, x}; mov.b128 b, {x, x}; mov.b128 c, {x, x};\n"
                 "and.b32 t, %13, 1; setp.ne.u32 q0, t, 0; and.b32 t, %13, 2; setp.ne.u32 q1, t, 0; and.b32 t, %13, 4; setp.ne.u32 q2, t, 0;\n"
                 "@q0 atom.relaxed.gpu.global.exch.b128 a, [%12], a; @q1 atom.relaxed.gpu.global.exch.b128 b, [%12+16384], b;\n"
                 "@q2 atom.relaxed.gpu.global.exch.b128 c, [%12+32768], c;\n"
                 "mov.b128 {x, y}, a; mov.b64 {%0,%1}, x; mov.b64 {%2,%3}, y; mov.b128 {x, y}, b; mov.b64 {%4,%5}, x; mov.b64 {%6,%7}, y;\n"
                 "mov.b128 {x, y}, c; mov.b64 {%8,%9}, x; mov.b64 {%10,%11}, y; }"
                 : "=f"(v[0].x), "=f"(v[0].y), "=f"(v[0].z), "=f"(v[0].w), "=f"(v[1].x), "=f"(v[1].y), "=f"(v[1].z), "=f"(v[1].w),
                   "=f"(v[2].x), "=f"(v[2].y), "=f"(v[2].z), "=f"(v[2].w) : "l"(p), "r"(mask) : "memory");
}
__device__ __forceinline__ void st_rlx32(uint32_t* p, uint32_t v) { asm volatile("st.relaxed.gpu.global.u32 [%0], %1;" ::"l"(p), "r"(v) : "memory"); }
__device__ __forceinline__ uint32_t hmul_bf2(uint32_t a, uint32_t b) {
    uint32_t r; asm("mul.rn.bf16x2 %0, %1, %2;" : "=r"(r) : "r"(a), "r"(b)); return r;
}
__device__ __forceinline__ uint32_t hsub_bf2(uint32_t a, uint32_t b) {
    uint32_t r; asm("sub.rn.bf16x2 %0, %1, %2;" : "=r"(r) : "r"(a), "r"(b)); return r;
}
constexpr int SPIN_LIMIT = 1 << 22;

__constant__ uint32_t c_inv2pi[8] = {0u, 0x28be60dbu, 0x9391054au, 0x7f09d5f4u, 0x7d4d3770u, 0x36d8a566u, 0x4f10e410u, 0x7f9458eau};
constexpr uint32_t BIGX = 0x4280u;
__device__ __forceinline__ float cos_big(uint32_t xb) {
    uint32_t e = (xb >> 7) & 0xffu, M = (xb & 0x7fu) | 0x80u;
    uint32_t pp = e - 102u;
    uint32_t wi = pp >> 5;
    uint32_t t0 = c_inv2pi[wi], t1 = c_inv2pi[wi + 1], t2 = c_inv2pi[wi + 2];
    uint32_t f = M * __funnelshift_l(t1, t0, pp) + __umulhi(M, __funnelshift_l(t2, t1, pp));
    float c = __cosf((float)(int)f * 1.4629180792671596e-9f);
    return e == 255u ? __uint_as_float(0x7fc00000u) : c;
}
__device__ __forceinline__ float cos_bf(uint32_t xb) {
    return (xb & 0x7fffu) > BIGX ? cos_big(xb) : __cosf(__uint_as_float(xb << 16));
}
__device__ __forceinline__ uint32_t pack_bf2(float lo, float hi) {
    uint32_t r; asm("cvt.rn.bf16x2.f32 %0, %1, %2;" : "=r"(r) : "f"(hi), "f"(lo)); return r;
}
template <int N> __device__ __forceinline__ uint32_t pick(int k, const uint32_t (&a)[N]) {
    uint32_t v = a[0];
#pragma unroll
    for (int i = 1; i < N; i++) if (k == i) v = a[i];
    return v;
}
template <int N> __device__ __forceinline__ uint2 pick(int k, const uint2 (&a)[N]) {
    uint2 v = a[0];
#pragma unroll
    for (int i = 1; i < N; i++) if (k == i) v = a[i];
    return v;
}
__device__ __forceinline__ void side_add(uint32_t bin, uint32_t row, float a, float b, float c, float d) {
    red4(&g_ovf[bin * RPAD + row], a, b, c, d);
    g_dirty[bin * DROW + row] = 1;
}
__device__ __forceinline__ void slow_triplet(const Params& p, uint32_t ii, uint32_t oo, float c) {
    const uint2 v = __ldg(p.m + ii);
    const uint32_t bo = __umulhi(oo, p.mg2);
    side_add(bo, oo - bo * p.R2, c * bf_lo(v.x), c * bf_hi(v.x), c * bf_lo(v.y), c * bf_hi(v.y));
}
__device__ __forceinline__ void slow_rec1(const Params& p, uint32_t x, uint32_t y, uint32_t bin) {
    const uint2 v = __ldg(p.m + bin * p.R1 + (y & 0xffffu));
    const float c = bf_hi(y);
    side_add(x & 0xffu, __byte_perm(x, 0u, 0x4413) >> 2, c * bf_lo(v.x), c * bf_hi(v.x), c * bf_lo(v.y), c * bf_hi(v.y));
}
__device__ __forceinline__ uint32_t aux_of(uint32_t w0, uint32_t w1) {
    uint32_t u; asm("lop3.b32 %0, %1, %2, 0xf000f000, 0xe4;" : "=r"(u) : "r"(w0), "r"(w1 >> 4));
    return __byte_perm(u, 0u, 0x4413);
}
__device__ __forceinline__ void slow_rec2(const Params& p, uint32_t w0, uint32_t w1, uint32_t bin, float unit) {
    side_add(bin, aux_of(w0, w1) >> 2, (float)((int)(w0 & 0xfffu) - 2048) * unit, (float)((int)(w0 >> 16 & 0xfffu) - 2048) * unit,
             (float)((int)(w1 & 0xfffu) - 2048) * unit, (float)((int)(w1 >> 16 & 0xfffu) - 2048) * unit);
}
template <uint32_t M> __device__ __forceinline__ uint32_t and_or(uint32_t a, uint32_t c) {
    uint32_t r; asm("lop3.b32 %0, %1, %2, %3, 0xea;" : "=r"(r) : "r"(a), "n"(M), "r"(c)); return r;
}
__device__ __forceinline__ uint32_t and_xor(uint32_t a, uint32_t m, uint32_t c) {
    uint32_t r; asm("lop3.b32 %0, %1, %2, %3, 0x6a;" : "=r"(r) : "r"(a), "r"(m), "r"(c)); return r;
}
__device__ __forceinline__ uint2 ld_in(const uint2* a) {
    uint2 v; asm volatile("ld.global.nc.L1::no_allocate.v2.u32 {%0,%1}, [%2];" : "=r"(v.x), "=r"(v.y) : "l"(a)); return v;
}
__device__ __forceinline__ uint32_t ld_in(const uint32_t* a) {
    uint32_t v; asm volatile("ld.global.nc.L1::no_allocate.u32 %0, [%1];" : "=r"(v) : "l"(a)); return v;
}
template <int OFF> __device__ __forceinline__ void put_rec(uint32_t ret, uint32_t lim, uint32_t addr, uint32_t x, uint32_t y) {
    asm volatile("{ .reg .pred q; setp.lt.u32 q, %0, %1; @q st.shared.v2.u32 [%2+%5], {%3,%4}; }" ::"r"(ret), "r"(lim), "r"(addr), "r"(x), "r"(y), "n"(OFF) : "memory");
}
__device__ __forceinline__ uint32_t mbar_try(uint32_t mb, uint32_t parity) {
    uint32_t ok;
    asm volatile("{ .reg .pred q; mbarrier.try_wait.parity.shared::cta.b64 q, [%1], %2; selp.u32 %0, 1, 0, q; }" : "=r"(ok) : "r"(mb), "r"(parity) : "memory");
    return ok;
}
__device__ __forceinline__ void mbar_wait(uint32_t mb, uint32_t parity) {
    if (!mbar_try(mb, parity)) {
        int it = 0;
        while (!mbar_try(mb, parity)) if (++it > SPIN_LIMIT) __trap();
    }
}
__device__ __forceinline__ void mbar_init(uint32_t mb, uint32_t n) { asm volatile("mbarrier.init.shared::cta.b64 [%0], %1;" ::"r"(mb), "r"(n) : "memory"); }
__device__ __forceinline__ void mbar_arrive(uint32_t mb) { asm volatile("mbarrier.arrive.shared::cta.b64 _, [%0];" ::"r"(mb) : "memory"); }
constexpr int B_FULL = OFF_BAR, B_OPEN = OFF_BAR + 16, B_FREE = OFF_BAR + 32;
constexpr int W_END = OFF_BAR + 40, W_SIDE = OFF_BAR + 44, W_PAR = OFF_BAR + 48, W_ROLE = OFF_BAR + 52, W_EXP = OFF_BAR + 56, W_UNIT = OFF_BAR + 60;
enum { BAR_S1 = 1, BAR_PROBE, BAR_HIST, BAR_ROLE, BAR_TABLE, BAR_H1, BAR_DONE };
constexpr int W_M1 = NS1 + NC, W_M2 = 31;

extern __shared__ __align__(1024) unsigned char smem[];
#define TK_DECL
#define TK(i)
#define TK_CNT(i)
#define TK_OUT
#define TK_ARG
#define TK_PASS
#define TKX(i)
#define TKY(i)

constexpr int NR = (R2MAX + NTHR - 1) / NTHR;
__device__ __forceinline__ void gates(const Params& p, int e0, int e1, int e2, uint4* gh) {
    constexpr int NH = 3;
    const int e[NH] = {e0, e1, e2};
    uint32_t dd[NH];
    float g[NH][4], h[NH][4];
#pragma unroll
    for (int u = 0; u < NH; u++) {
        dd[u] = reinterpret_cast<const uint16_t*>(p.dist)[min(e[u], p.E - 1)] * 0x10001u;
#pragma unroll
        for (int k = 0; k < 4; k++) { g[u][k] = 0.f; h[u][k] = 0.f; }
    }
#pragma unroll 1
    for (int r2 = 0; r2 < 4; r2++) {
        const uint32_t cen = reinterpret_cast<const uint32_t*>(smem + OFF_WG + 256)[r2];
        uint32_t rb[NH];
#pragma unroll
        for (int u = 0; u < NH; u++) {
            const uint32_t df = hsub_bf2(dd[u], cen);
            const uint32_t ar = hmul_bf2(hmul_bf2(df, df), 0xc120c120u);
            rb[u] = pack_bf2(__expf(bf_lo(ar)), __expf(bf_hi(ar)));
        }
#pragma unroll
        for (int i = 0; i < 2; i++) {
            const float4 ws = reinterpret_cast<const float4*>(smem + OFF_WG)[r2 * 2 + i], wr = reinterpret_cast<const float4*>(smem + OFF_WG + 128)[r2 * 2 + i];
#pragma unroll
            for (int u = 0; u < NH; u++) {
                const float x = i ? bf_hi(rb[u]) : bf_lo(rb[u]);
                g[u][0] += x * ws.x; g[u][1] += x * ws.y; g[u][2] += x * ws.z; g[u][3] += x * ws.w;
                h[u][0] += x * wr.x; h[u][1] += x * wr.y; h[u][2] += x * wr.z; h[u][3] += x * wr.w;
            }
        }
    }
#pragma unroll
    for (int u = 0; u < NH; u++)
        gh[u] = make_uint4(pack_bf2(g[u][0], g[u][1]), pack_bf2(g[u][2], g[u][3]), pack_bf2(h[u][0], h[u][1]), pack_bf2(h[u][2], h[u][3]));
}
__device__ __forceinline__ void prefetch_l2(const void* a) { asm volatile("prefetch.global.L2 [%0];" ::"l"(a)); }
__device__ __forceinline__ uint4* gate_slot(int k) { return reinterpret_cast<uint4*>(smem + OFF_H1 + (k >= WIN / 16 ? 0x20000 - WIN : 0)) + k; }
__device__ __forceinline__ void wait_flags(const Params& p, uint32_t sb, int lane, uint32_t need) {
    const unsigned char* f = p.ring + M_FLAG + (lds32(sb + W_SIDE) << 12);
    int it = 0;
    while (true) {
        const float4 a = ld_rlx128f(reinterpret_cast<const float4*>(f) + lane);
        const uint32_t b = ld_rlx32(reinterpret_cast<const uint32_t*>(f) + 128 + (lane & 3));
        const uint32_t d = (__float_as_uint(a.x) ^ need) | (__float_as_uint(a.y) ^ need) | (__float_as_uint(a.z) ^ need) | (__float_as_uint(a.w) ^ need) | (b ^ need);
        if (__all_sync(0xffffffffu, d == 0)) break;
        __nanosleep(50);
        if (++it > SPIN_LIMIT) __trap();
    }
    __threadfence();
}
__device__ __forceinline__ void epilogue(const Params& p, uint32_t sb) {
    int tid;
    asm volatile("mov.u32 %0, %%tid.x;" : "=r"(tid));
    const int role = lds32(sb + W_ROLE), row0 = role * p.R2, nrows = min(p.R2, p.E - row0), hw = tid >> 5;
    const bool s3 = hw > W_M1 && hw < W_M2;
    constexpr int T3 = (W_M1 + 1) * 32, N3 = NC * 32;
    uint4 gh[NR];
    if (hw < NS1) {
        if (tid * 64 < nrows) prefetch_l2(p.dist + row0 + tid * 64);
        for (int i = tid * 16; i < nrows; i += NS1 * 32 * 16) prefetch_l2(p.m + row0 + i);
    }
    if (!s3) gates(p, row0 + tid + 3 * NTHR, row0 + tid + 4 * NTHR, row0 + tid + 5 * NTHR, gh + 3);
    if (hw < NS1) {
        bar_sync(BAR_H1, (NS1 + 1) * 32);
#pragma unroll 1
        for (int k0 = tid; k0 < NR * N3; k0 += 3 * NS1 * 32) {
            int k[3], e[3];
#pragma unroll
            for (int u = 0; u < 3; u++) { k[u] = k0 + u * NS1 * 32; e[u] = row0 + T3 + k[u] + k[u] / N3 * (NTHR - N3); }
            gates(p, e[0], e[1], e[2], gh);
#pragma unroll
            for (int u = 0; u < 3; u++) if (k[u] < NR * N3) *gate_slot(k[u]) = gh[u];
        }
#pragma unroll
        for (int i = tid; i < DROW / 8; i += NS1 * 32) {
            const uint2 f = ld_rlx64(g_dirty + role * DROW + i * 8);
            if (f.x | f.y) prefetch_l2(g_ovf + role * RPAD + i * 8);
        }
    }
    if (!s3) gates(p, row0 + tid, row0 + tid + NTHR, row0 + tid + 2 * NTHR, gh);
    if (hw == W_M1) wait_flags(p, sb, tid & 31, lds32(sb + W_END));
    TKX(5)
    bar_sync(0, NTHR);
    TKX(6)
    uint32_t dirty = 0;
#pragma unroll
    for (int it = 0; it < NR; it++) {
        uint32_t f;
        asm volatile("ld.relaxed.gpu.global.u8 %0, [%1];" : "=r"(f) : "l"(g_dirty + role * DROW + tid + it * NTHR) : "memory");
        dirty |= f << it;
    }
    if (s3) {
#pragma unroll
        for (int it = 0; it < NR; it++) gh[it] = *gate_slot(tid - T3 + it * N3);
    }
    if (hw == W_M1 && blockIdx.x == 0) {
        if (tid == W_M1 * 32) g_base = lds32(sb + W_END);
        if (tid < W_M1 * 32 + 3) *reinterpret_cast<uint32_t*>(p.ring + (tid & 2 ? M_PAR : M_CNT + (tid & 1) * 4096)) = 0;
    }
    const float unit = *reinterpret_cast<const float*>(smem + W_UNIT);
    const float4* w4 = reinterpret_cast<const float4*>(smem + OFF_WSM);
#pragma unroll
    for (int i0 = 0; i0 < NR; i0 += 3) {
        uint2 mv[3];
        float4 o[3];
#pragma unroll
        for (int u = 0; u < 3; u++) mv[u] = __ldg(p.m + min(row0 + tid + (i0 + u) * NTHR, p.E - 1));
        take3(&g_ovf[role * RPAD + tid + i0 * NTHR], dirty >> i0, o);
#pragma unroll
        for (int u = 0; u < 3; u++) {
            const int it = i0 + u, i = tid + it * NTHR;
            if (dirty >> it & 1) g_dirty[role * DROW + i] = 0;
            if (i < nrows) {
                const uint2 ac = reinterpret_cast<const uint2*>(smem + OFF_ACC)[i];
                const uint32_t u0 = ac.x + 0x40004000u, u1 = ac.y + 0x40004000u;
                const float a[4] = {(float)((int)(u0 & 0xffffu) - 0x8000) * unit + o[u].x, (float)((int)(u0 >> 16) - 0x8000) * unit + o[u].y,
                                    (float)((int)(u1 & 0xffffu) - 0x8000) * unit + o[u].z, (float)((int)(u1 >> 16) - 0x8000) * unit + o[u].w};
                float sd[4] = {0, 0, 0, 0}, uu[4] = {0, 0, 0, 0};
#pragma unroll
                for (int j = 0; j < 4; j++) {
                    float4 w = w4[j];
                    sd[0] += a[j] * w.x; sd[1] += a[j] * w.y; sd[2] += a[j] * w.z; sd[3] += a[j] * w.w;
                }
                const uint32_t a01 = pack_bf2(sd[0] * bf_lo(gh[it].x), sd[1] * bf_hi(gh[it].x)), a23 = pack_bf2(sd[2] * bf_lo(gh[it].y), sd[3] * bf_hi(gh[it].y));
                const float ag[4] = {bf_lo(a01), bf_hi(a01), bf_lo(a23), bf_hi(a23)};
#pragma unroll
                for (int j = 0; j < 4; j++) {
                    float4 w = w4[4 + j];
                    uu[0] += ag[j] * w.x; uu[1] += ag[j] * w.y; uu[2] += ag[j] * w.z; uu[3] += ag[j] * w.w;
                }
                const uint32_t t01 = hmul_bf2(pack_bf2(uu[0], uu[1]), gh[it].z);
                const uint32_t t23 = hmul_bf2(pack_bf2(uu[2], uu[3]), gh[it].w);
                uint2 q;
                asm("add.rn.bf16x2 %0, %1, %2;" : "=r"(q.x) : "r"(mv[u].x), "r"(t01));
                asm("add.rn.bf16x2 %0, %1, %2;" : "=r"(q.y) : "r"(mv[u].y), "r"(t23));
                p.out[row0 + i] = q;
            }
        }
        if (i0 == 0) { TKY(3) }
    }
}

template <int HOP> __device__ __forceinline__ uint4 nulls(int lane, uint32_t R) {
    const uint32_t i = lane & 7;
    if (HOP == 1) {
        const uint32_t x = (NB + 2 * i) | H<1>::gen(R), y = (OFF_CNT2 - OFF_M) / 8;
        return make_uint4(x, y, x + 1, y);
    }
    return make_uint4(0x08000800u, 0x28000800u | H<2>::gen(R), 0x08000800u, 0x28000800u | H<2>::gen(R));
}
template <int OFF> __device__ __forceinline__ void sts128(uint32_t a, const uint4& v) {
    asm volatile("st.shared.v4.u32 [%0+%5], {%1,%2,%3,%4};" ::"r"(a), "r"(v.x), "r"(v.y), "r"(v.z), "r"(v.w), "n"(OFF) : "memory");
}
template <int HOP> struct Prefill {
    uint32_t a0, a1;
    __device__ __forceinline__ Prefill(int lane) {
        const uint32_t q = lane >> 3, i = lane & 7, b = q + (i & 4), c = (q & 1) + (q & 2) * 4 + (i & 6);
        a0 = HOP == 1 ? q * 256 + ((8 + q + i) & 15) * 16 : b * 128 + ((4 + b + (i & 3)) & 7) * 16;
        a1 = HOP == 1 ? q * 256 + 1024 + ((12 + q + i) & 15) * 16 : c * 128 + ((2 + c + (i & 1)) & 7) * 16;
    }
    __device__ __forceinline__ void run(uint32_t win, const uint4& v) const {
#pragma unroll 1
        for (uint32_t w = win; w < win + 16384; w += 8192) {
            sts128<0>(w + a0, v); sts128<2048>(w + a0, v); sts128<4096>(w + a0, v); sts128<6144>(w + a0, v);
            sts128<0>(w + a1, v); sts128<2048>(w + a1, v); sts128<4096>(w + a1, v); sts128<6144>(w + a1, v);
            if (HOP == 2) { sts128<1024>(w + a0, v); sts128<3072>(w + a0, v); sts128<5120>(w + a0, v); sts128<7168>(w + a0, v); }
        }
        if (a0 < 512) sts128<16384>(win + a0, v);
        if (HOP == 2 && a1 < 512) sts128<16384>(win + a1, v);
    }
};
__device__ __forceinline__ bool elect() {
    uint32_t q; asm volatile("{ .reg .pred q; elect.sync _|q, 0xffffffff; selp.u32 %0, 1, 0, q; }" : "=r"(q)); return q;
}
__device__ __forceinline__ const unsigned char* mk_ptr(uint32_t lo, uint32_t hi) { return reinterpret_cast<const unsigned char*>((uint64_t)hi << 32 | lo); }
__device__ __forceinline__ void bulk_store(uint32_t lo, uint32_t hi, uint32_t src, uint32_t n) {
    asm volatile("cp.async.bulk.global.shared::cta.bulk_group [%0], [%1], %2;" ::"l"(mk_ptr(lo, hi)), "r"(src), "r"(n) : "memory");
}
template <int HOP>
__device__ __forceinline__ void manager(const Params& p, uint32_t sb, int lane, int role, uint32_t base) {
    typedef H<HOP> h;
    constexpr int V = h::NBIN / 32, PB = h::S * 8;
    const int RT = p.rounds, lo = HOP == 1 && role >= NG ? NG : 0, hi = lo + h::NBIN;
    const int w = (role - lo) / (HOP * J), j = (role - lo - w * HOP * J) / HOP;
    const Ring rg(p.ring, __reduce_or_sync(0xffffffffu, lds32(sb + W_PAR)), 2 * w + HOP - 1);
    const uint32_t side = lds32(sb + W_SIDE), dhi = rg.main >> 32, mhi = rg.mid >> 32;
    const uint32_t c0 = HOP == 2 ? role & 1 : 0, up = (HOP == 1 && lo) ^ rg.par ^ c0;
    uint32_t dA = ((uint32_t)rg.main + src_off(j) + (c0 << 16) + (up ? 4096 : 12288)) ^ slot_off(base % 3);
    uint32_t dM = ((uint32_t)rg.mid + src_off(j) + c0 * 1024) ^ slot_off(base % 3);
    const int a0 = max(64, lo), b1 = min(68, hi);
    int n0 = (min(NHI, hi) - a0) * PB, a1 = (max(NLO, lo) - lo) * PB;
    const unsigned char* cr = reinterpret_cast<const unsigned char*>(rg.main) + MISC + ((side ^ rg.par) << 12) + lo * 4;
    const unsigned char* cr0 = cr + lane * V * 4, *cr1 = cr + (32 * V + min(lane, V - 1)) * 4;
    const uint32_t ca0 = sb + h::CNT + lane * V * 4, ca1 = sb + h::CNT + (32 * V + min(lane, V + NDUM - 1)) * 4;
    const uint32_t rot0 = (lane * V & 7) * 16, rot1 = lane < V ? lane * 16 : 0x80000000u;
    const Prefill<HOP> pf(lane);
    uint4 nul = nulls<HOP>(lane, base + HOP);
    uint32_t st = slot_steps(base);
    uint32_t init = h::init(base), prim = sb + h::STG + (HOP == 1 ? h::win(base) : 0u);
    uint32_t cs[5];
    auto sample = [&]() {
        if (V == 2) asm volatile("ld.relaxed.gpu.global.v2.u32 {%0,%1}, [%2];" : "=r"(cs[0]), "=r"(cs[1]) : "l"(cr0) : "memory");
        else asm volatile("ld.relaxed.gpu.global.v4.u32 {%0,%1,%2,%3}, [%4];" : "=r"(cs[0]), "=r"(cs[1]), "=r"(cs[2]), "=r"(cs[3]) : "l"(cr0) : "memory");
        cs[V] = ld_rlx32(reinterpret_cast<const uint32_t*>(cr1));
    };
    sample();
    uint32_t c[5];
    TK_DECL
#pragma unroll 1
    for (int r = 0;; r++) {
        const uint32_t R = base + r, ninit = h::init(R + 1), done = prim;
        TK(5)
        mbar_wait(sb + B_FULL + (HOP - 1) * 8, r & 1);
        TK(0)
        if (V == 2) asm volatile("ld.shared.v2.u32 {%0,%1}, [%2];" : "=r"(c[0]), "=r"(c[1]) : "r"(ca0) : "memory");
        else asm volatile("ld.shared.v4.u32 {%0,%1,%2,%3}, [%4];" : "=r"(c[0]), "=r"(c[1]), "=r"(c[2]), "=r"(c[3]) : "r"(ca0) : "memory");
        c[V] = lds32(ca1);
        uint32_t nc[5], low = c[V];
#pragma unroll
        for (int k = 0; k <= V; k++) {
            const uint32_t z = ninit + (k < V ? rot0 + k * 16 : rot1);
            nc[k] = min(max(c[k] + (ninit - init - h::S * h::INC), z), z + (h::CAP - h::S) * h::INC);
            low = min(low, c[k]);
        }
        if (V == 2) sts64(ca0, nc[0], nc[1]); else sts128<0>(ca0, make_uint4(nc[0], nc[1], nc[2], nc[3]));
        sts32(ca1, nc[V]);
        __syncwarp();
        if (lane == 0) mbar_arrive(sb + B_OPEN + (HOP - 1) * 8);
        TK(1)
        if (low < init + (h::PRE << h::SH) && r != RT - 1) {
            const uint32_t gb = init & 1u << h::TB, vx = HOP == 1 ? NB | gb : 0x08000800u, vy = HOP == 1 ? nul.y : 0x28000800u | gb;
#pragma unroll 1
            for (int k = 0; k <= V; k++) {
                const uint32_t bin = k < V ? lane * V + k : 32 * V + lane;
#pragma unroll 1
                for (uint32_t x = pick(k, c); x < init + (h::PRE << h::SH); x += h::INC) sts64(prim + bin * PB + (x & h::PM), vx, vy);
            }
        }
        __syncwarp();
        TK(2)
        asm volatile("fence.proxy.async.shared::cta;" ::: "memory");
        TK(6)
        if (r >= D) {
            int it = 0;
            while (true) {
                uint32_t bad = 0;
#pragma unroll
                for (int k = 0; k <= V; k++) bad |= cs[k] - (R - D + 1);
                if (!__any_sync(0xffffffffu, bad >> 20)) break;
                if (++it > SPIN_LIMIT) __trap();
                if (it > 1) __nanosleep(100);
                sample();
            }
        }
        TK(3)
        const bool last = r == RT - 2 - HOP;
        if (elect()) {
            const uint32_t dB = (HOP == 1 ? dA ^ 0x10000u : dA) + (up ? 8192 : -8192), sm = prim + (lo ? 2 * PB : 0);
            bulk_store(dA, dhi, sm, 8192);
            bulk_store(dB, dhi, HOP == 1 ? sm + 8192 : prim + 68 * PB, 8192);
            if (n0 > 0) bulk_store(dM + (a0 - 64) * PB, mhi, prim + (a0 - lo) * PB, n0);
            if (a1 < (b1 - lo) * PB) bulk_store((dM ^ 4096u) + (uint32_t)((lo - NLO) * PB + a1), mhi, prim + a1, (b1 - lo) * PB - a1);
            asm volatile("cp.async.bulk.commit_group;" ::: "memory");
            asm volatile("cp.async.bulk.wait_group.read 0;" ::: "memory");
            if (HOP == 1 && !last) mbar_arrive(sb + B_FREE);
        }
        __syncwarp();
        TK(4)
        prim = HOP == 1 ? prim ^ 0x20000u : prim >= sb + 0x30000u ? sb : prim + (prim - sb) + 0x10000u;
        if (r == RT - 1) break;
        if (h::lap(R + HOP) & 1u << (h::TB - 1)) {
            if (HOP == 1) { nul.x ^= 1u << h::TB; nul.z ^= 1u << h::TB; }
            else { nul.y ^= 1u << h::TB; nul.w ^= 1u << h::TB; }
        }
        if (!last) pf.run(done, nul);
        else {
#pragma unroll 1
            for (uint32_t a = done + lane * 16; a < done + WIN; a += 512) sts128<0>(a, nul);
            __syncwarp();
            if (HOP == 1 && lane == 0) mbar_arrive(sb + B_FREE);
        }
        if (r == D - 1 || r == RT - D - 1) {
            uint32_t n = NHI, m = NLO;
            if (r < RT - D - 1) {
                int it = 0;
                while (true) {
                    n = ld_rlx32(reinterpret_cast<const uint32_t*>(p.ring + M_CNT + (side << 12)));
                    if ((n & 0xffffu) + (n >> 16) == NB) break;
                    if (++it > SPIN_LIMIT) __trap();
                }
                m = n = min(max(__reduce_or_sync(0xffffffffu, n) & 0xffffu, (uint32_t)NLO), (uint32_t)NHI);
            }
            n0 = (min((int)n, hi) - a0) * PB;
            a1 = (max((int)m, lo) - lo) * PB;
        }
        sample();
        slot_next(dA, st); slot_next(dM, st);
        st = slot_rot(st);
        init = ninit;
    }
#pragma unroll 1
    for (int k = 0; k <= V; k++) {
        const uint32_t bin = k < V ? lane * V + k : 32 * V + lane, n = bin < h::NBIN ? min((pick(k, c) - init) >> h::SH, (uint32_t)h::CAP) : 0u;
#pragma unroll 1
        for (uint32_t x = h::S; x < n; x++) {
            const uint2 w = lds64(prim + bin * PB + ((x + (bin & 7) * 2) & (h::S - 1)) * 8);
            if (HOP == 1) slow_rec1(p, w.x, w.y, bin);
            else slow_rec2(p, w.x, w.y, bin, __uint_as_float(lds32(sb + W_UNIT)));
        }
    }
    asm volatile("cp.async.bulk.wait_group 0;" ::: "memory");
    TK_OUT
}

#define POLL_NS 200
#define POLL_NS3 1500
template <int HOP> struct Reader {
    uint32_t lo, hi, st;
    uint32_t* cred;
    __device__ __forceinline__ void init(const Params& p, uint32_t sb, int w, int lane, int role, uint32_t base) {
        constexpr int PB = H<HOP>::S * 8;
        const int first = HOP == 1 ? (role >= NG ? NG : 0) + w * J : w * 2 * J;
        const Ring rg(p.ring, lds32(sb + W_PAR), 2 * w + HOP - 1);
        const uint32_t side = lds32(sb + W_SIDE);
        const bool mid = side ? role < 68 : role >= 64;
        const uint32_t i = role - (side ? (mid ? NLO : 68) : (mid ? 64 : 0));
        const uint32_t c = HOP == 1 ? i >> 5 : lane >> 4, in = HOP == 1 ? (i & 31) * PB + lane * 8 : i * PB + (lane & 15) * 8;
        lo = (in + (mid ? ((uint32_t)rg.mid ^ side << 12) + c * 1024 : (uint32_t)rg.main + (c << 16) + (side ^ rg.par ^ c ? 4096 : 12288))) ^ slot_off(base % 3);
        hi = __reduce_or_sync(0xffffffffu, (uint32_t)((mid ? rg.mid : rg.main) >> 32));
        st = slot_steps(base);
        const bool both = first >= NLO && first < NHI;
        cred = lane < 1 + both ? reinterpret_cast<uint32_t*>(rg.main + MISC + (((both ? lane : first >= NG) ^ rg.par) << 12)) + role : nullptr;
    }
    template <int K> __device__ __forceinline__ void load1(uint2& v) const {
        asm volatile("ld.relaxed.gpu.global.v2.u32 {%0,%1}, [%2+%3];" : "=r"(v.x), "=r"(v.y) : "l"(mk_ptr(lo, hi)), "n"(src_off(K)) : "memory");
    }
    template <int K> __device__ __forceinline__ void again(uint2& v, uint32_t want) const {
        asm volatile("{ .reg .pred q; .reg .u32 t; xor.b32 t, %4, %3; and.b32 t, t, %5; setp.ne.u32 q, t, 0;\n"
                     "@q ld.relaxed.gpu.global.v2.u32 {%0,%1}, [%2+%6]; }"
                     : "+r"(v.x), "+r"(v.y) : "l"(mk_ptr(lo, hi)), "r"(want), "r"(HOP == 1 ? v.x : v.y), "n"(1u << H<HOP>::TB), "n"(src_off(K)) : "memory");
    }
    __device__ __forceinline__ void load(uint2 (&rec)[J]) const {
        load1<0>(rec[0]); load1<1>(rec[1]); load1<2>(rec[2]); load1<3>(rec[3]); load1<4>(rec[4]); load1<5>(rec[5]);
    }
    __device__ __forceinline__ void check(uint2 (&rec)[J], uint32_t R, uint32_t ns TK_ARG) {
        constexpr uint32_t BIT = 1u << H<HOP>::TB;
        const uint32_t want = H<HOP>::lap(R);
        int it = 0;
        while (true) {
            uint32_t bad = 0;
#pragma unroll
            for (int j = 0; j < J; j++) bad |= (HOP == 1 ? rec[j].x : rec[j].y) ^ want;
            if (!__any_sync(0xffffffffu, bad & BIT)) break;
            if (++it > SPIN_LIMIT) __trap();
            __nanosleep(ns);
            TK_CNT(7)
            again<0>(rec[0], want); again<1>(rec[1], want); again<2>(rec[2], want); again<3>(rec[3], want); again<4>(rec[4], want); again<5>(rec[5], want);
        }
        if (cred) st_rlx32(cred, R + 1);
        slot_next(lo, st);
        st = slot_rot(st);
    }
    __device__ __forceinline__ void finish() const { if (cred) st_rlx32(cred, 0u); }
};

#define NPROBE 9
__device__ __forceinline__ uint32_t near_half(unsigned char* pair, uint32_t zero) {
#pragma unroll
    for (int i = 0; i < 4; i++) *reinterpret_cast<uint4*>(pair + (i >> 1) * 4096 + (i & 1) * 16) = make_uint4(0u, 0u, 0u, 0u);
    uint32_t best[2] = {~0u, ~0u}, v = 0, prev = 0;
    asm volatile("red.relaxed.gpu.global.add.u32 [%0], 1;" ::"l"(pair + 4096) : "memory");
#pragma unroll
    for (int t = 0; t <= NPROBE; t++) {
        uint32_t now;
        asm volatile("atom.relaxed.gpu.global.add.u32 %0, [%1], 1;" : "=r"(v) : "l"(pair + (t & 1) * 4096 + (v & zero)) : "memory");
        asm volatile("mov.u32 %0, %%clock;" : "=r"(now) :: "memory");
        if (t > 1) best[(t - 1) & 1] = min(best[(t - 1) & 1], now - prev);
        prev = now;
    }
    return (best[1] < best[0] ? 1u : 0u) | (v & zero);
}
template <bool B> struct BoolC { static constexpr bool value = B; };

template <int NP>
__device__ __forceinline__ void stage1(const Params& p, uint32_t sb, const int pos0, int lane, uint32_t base) {
    typedef H<1> h;
    const int RT = p.rounds;
    uint32_t ff = *reinterpret_cast<const uint16_t*>(p.ang_freq) * 0x10001u;
    auto pair_of = [&](int r, int pos) {
        const int q = r < RT - 1 ? (r * NB + blockIdx.x) * NPR + pos : (RT - 1) * NB * NPR + blockIdx.x * p.lastn + pos;
        return (r < RT - 1 || (r == RT - 1 && pos < p.lastn)) && q < p.T2 ? q : -1;
    };
    uint2 vi[NP], vo[NP]; uint32_t va[NP];
    auto load_edge = [&](int r) {
#pragma unroll
        for (int u = 0; u < NP; u++) {
            const int q = max(pair_of(r, pos0 + u * 32), 0);
            vi[u] = ld_in(p.idx_in + q); vo[u] = ld_in(p.idx_out + q); va[u] = ld_in(p.angle + q);
        }
    };
    load_edge(0);
    if (blockIdx.x == 0 && pos0 == 0 && (p.T & 1)) {
        const int t = p.T - 1;
        slow_triplet(p, reinterpret_cast<const uint32_t*>(p.idx_in)[t], reinterpret_cast<const uint32_t*>(p.idx_out)[t],
                     bf16r(cos_bf(hmul_bf2(reinterpret_cast<const uint16_t*>(p.angle)[t], ff) & 0xffffu)));
    }
    for (int i = threadIdx.x * 16; i < p.R2 && blockIdx.x * p.R2 + i < p.E; i += NS1 * 32 * 16) prefetch_l2(p.m + blockIdx.x * p.R2 + i);
    uint32_t R = __reduce_or_sync(0xffffffffu, base);
    ff = __reduce_or_sync(0xffffffffu, ff);
    bar_sync(BAR_S1, (NS1 + 1) * 32);
    TK_DECL
    auto step = [&](const int r, const int qn, auto edge) {
        constexpr bool EDGE = decltype(edge)::value;
        uint32_t cc[NP], big = 0;
#pragma unroll
        for (int u = 0; u < NP; u++) {
            va[u] = hmul_bf2(va[u], ff);
            cc[u] = pack_bf2(__cosf(bf_lo(va[u])), __cosf(bf_hi(va[u])));
            big = __vmaxu2(big, va[u] & 0x7fff7fffu);
        }
        if ((big + (0x7fffu - BIGX) * 0x10001u) & 0x80008000u) {
#pragma unroll 1
            for (int u = 0; u < NP; u++) {
                const uint32_t a = pick(u, va);
                float c0 = cos_bf(a & 0xffffu), c1 = cos_bf(a >> 16);
                if ((c0 != c0 || c1 != c1) && (!EDGE || pair_of(r, pos0 + u * 32) >= 0)) {
                    const uint2 i2 = pick(u, vi), o2 = pick(u, vo);
                    if (c0 != c0) slow_triplet(p, i2.x, o2.x, c0);
                    if (c1 != c1) slow_triplet(p, i2.y, o2.y, c1);
                }
                const uint32_t v = pack_bf2(c0 != c0 ? 0.f : c0, c1 != c1 ? 0.f : c1);
#pragma unroll
                for (int k = 0; k < NP; k++) if (k == u) cc[k] = v;
            }
        }
        uint32_t bin[2 * NP], x[2 * NP], y[2 * NP];
#pragma unroll
        for (int j = 0; j < 2 * NP; j++) {
            const uint32_t ii = j & 1 ? vi[j >> 1].y : vi[j >> 1].x, oo = j & 1 ? vo[j >> 1].y : vo[j >> 1].x;
            bin[j] = __umulhi(ii, p.mg1);
            y[j] = __byte_perm(bin[j] * p.k1 + ii, cc[j >> 1], j & 1 ? 0x7610 : 0x5410);
            const uint32_t bo = __umulhi(oo, p.mg2);
            x[j] = __byte_perm(bo * p.k2 + oo * 4u, bo, 0x0514);
            if (EDGE && pair_of(r, pos0 + (j >> 1) * 32) < 0) bin[j] = NG + (lane & (NDUM - 1));
        }
        if (EDGE) load_edge(r + 1);
        else {
            uint32_t dep = 0;
#pragma unroll
            for (int j = 0; j < 2 * NP; j++) dep |= x[j] | y[j];
            const int q = qn + (dep & p.zero);
#pragma unroll
            for (int u = 0; u < NP; u++) { vi[u] = ld_in(p.idx_in + q + u * 32); vo[u] = ld_in(p.idx_out + q + u * 32); va[u] = ld_in(p.angle + q + u * 32); }
        }
        const uint32_t init = h::init(R), kb = sb + h::win(R + 1), lim = init + (h::CAP << h::SH);
        TK(0)
        mbar_wait(sb + B_OPEN, ~R & 1);
        TK(1)
        bool freed = false;
        uint32_t over = 0;
#pragma unroll
        for (int g = 0; g < 2 * NP; g += 4) {
            uint32_t ret[4];
#pragma unroll
            for (int j = 0; j < 4; j++) ret[j] = atoms_add<h::CNT>(sb + bin[g + j] * 4, h::INC);
            const int mx = max(max((int)ret[0], (int)ret[1]), max((int)ret[2], (int)ret[3]));
            if (!freed && __any_sync(0xffffffffu, mx >= (int)(init + 0x10000u))) { TK(2) mbar_wait(sb + B_FREE, ~R & 1); freed = true; TK(3) }
            TK(2)
#pragma unroll
            for (int j = 0; j < 4; j++) {
                x[g + j] = and_or<1u << h::TB>(ret[j], x[g + j]);
                put_rec<h::STG>(ret[j], lim, and_xor(ret[j], 0x20000u | h::PM, bin[g + j] * 256 + kb), x[g + j], y[g + j]);
            }
            if (mx >= (int)lim) {
#pragma unroll
                for (int j = 0; j < 4; j++) if ((int)ret[j] >= (int)lim) over |= 1u << (g + j);
            }
        }
        __syncwarp();
        if (elect()) mbar_arrive(sb + B_FULL);
        R++;
        TK(4)
#pragma unroll 1
        while (over) {
            TK_CNT(7)
            const int j = __ffs(over) - 1;
            over &= over - 1;
            slow_rec1(p, pick(j, x), pick(j, y), pick(j, bin));
        }
        __syncwarp();
    };
#pragma unroll 1
    for (int q = (NB + blockIdx.x) * NPR; q < p.qfull; q += NB * NPR) step(q / (NB * NPR) - 1, q + pos0, BoolC<false>());
#pragma unroll 1
    for (int r = max(p.qfull / (NB * NPR) - 1, 0); r < RT; r++) step(r, 0, BoolC<true>());
    TK_OUT
}

__device__ __forceinline__ void stage2(const Params& p, uint32_t sb, int w, int lane, int role, uint32_t base) {
    typedef H<2> h;
    const int RT = p.rounds;
    Reader<1> rd;
    rd.init(p, sb, w, lane, role, base);
    uint2 rec[J];
    rd.load(rec);
    bar_sync(BAR_TABLE, 2 * NC * 32);
    uint32_t kb = sb + 0x10000u, am = 0x10000u | h::PM;
    TK_DECL
#pragma unroll 1
    for (int r = 0; r < RT; r++) {
        rd.check(rec, base + r, POLL_NS TK_PASS);
        TK(0)
        uint2 mv[J];
#pragma unroll
        for (int j = 0; j < J; j++) mv[j] = lds64<OFF_M>(sb + (rec[j].y & 0xffffu) * 8);
        uint32_t fl = 0;
#pragma unroll
        for (int j = 0; j < J; j++) fl |= mv[j].y;
        if (fl & 0x40000000u) {
#pragma unroll 1
            for (int j = 0; j < J; j++) {
                const uint2 v = pick(j, mv), w = pick(j, rec);
                if ((v.y & 0x40000000u) && (w.x & 0xffu) < NB) {
                    if (v.x & 0x40000000u) slow_rec1(p, w.x, w.y, lds32(sb + W_ROLE) % NG);
                    else {
                        const float c = bf_hi(w.y), s = __uint_as_float(lds32(sb + W_UNIT)) * 1024.f;
                        side_add(w.x & 0xffu, __byte_perm(w.x, 0u, 0x4413) >> 2, c * (bf_lo(v.x) * s), c * (bf_hi(v.x) * s),
                                 c * (bf_lo(v.y) * s), c * (bf_hi(v.y & 0xbfffffffu) * s));
                    }
                }
            }
#pragma unroll
            for (int j = 0; j < J; j++) if (mv[j].y & 0x40000000u) rec[j].x = NB;
        }
        uint32_t w0[J], w1[J], bin[J], ret[J];
#pragma unroll
        for (int j = 0; j < J; j++) {
            const float c = bf_hi(rec[j].y), MG = 8194.0f;
            const uint32_t x = rec[j].x;
            w0[j] = and_or<0xf000f000u>(x, __byte_perm(__float_as_uint(fmaf(c, bf_lo(mv[j].x), MG)), __float_as_uint(fmaf(c, bf_hi(mv[j].x), MG)), 0x5410));
            w1[j] = and_or<0xf000f000u>(x << 4, __byte_perm(__float_as_uint(fmaf(c, bf_lo(mv[j].y), MG)), __float_as_uint(fmaf(c, bf_hi(mv[j].y), MG)), 0x5410));
            bin[j] = x & 0xffu;
        }
        const uint32_t lim = h::init(base + r) + 0x20000u;
        rd.load(rec);
        TK(1)
        mbar_wait(sb + B_OPEN + 8, (r - 1) & 1);
        TK(2)
#pragma unroll
        for (int j = 0; j < J; j++) ret[j] = atoms_add<h::CNT>(sb + bin[j] * 4, h::INC);
        int mx = -1;
#pragma unroll
        for (int j = 0; j < J; j++) {
            w1[j] = and_or<1u << h::TB>(ret[j], w1[j]);
            put_rec<0>(ret[j], lim, and_xor(ret[j], am, bin[j] * 128 + kb), w0[j], w1[j]);
            mx = max(mx, (int)ret[j]);
        }
        __syncwarp();
        if (lane == 0) mbar_arrive(sb + B_FULL + 8);
        TK(3)
        if (mx >= (int)lim) {
#pragma unroll 1
            for (int j = 0; j < J; j++)
                if ((int)pick(j, ret) >= (int)lim) slow_rec2(p, pick(j, w0), pick(j, w1), pick(j, bin), __uint_as_float(lds32(sb + W_UNIT)));
        }
        __syncwarp();
        am = am >= 0x30000u ? 0x10000u | h::PM : am + 0x10000u;
        kb ^= am & 0x30000u;
        TK(4)
    }
    rd.finish();
    TK_OUT
}

__device__ __forceinline__ float2 acc_fix(uint32_t old, uint32_t q) {
    const uint32_t u = old + 0x40004000u, n = u + q - 0x08000800u;
    return make_float2((float)((int)(u & 0xffffu) + (int)(q & 0xffffu) - 2048 - (int)(n & 0xffffu)), (float)((int)(u >> 16) + (int)(q >> 16) - 2048 - (int)(n >> 16)));
}
__device__ __forceinline__ void stage3(const Params& p, uint32_t sb, int w, int lane, int role, uint32_t base) {
    const int RT = p.rounds;
    Reader<2> rd;
    rd.init(p, sb, w, lane, role, base);
    uint2 rec[J];
    bar_sync(BAR_TABLE, 2 * NC * 32);
    rd.load(rec);
    TK_DECL
#pragma unroll 1
    for (int r = 0; r < RT; r++) {
        rd.check(rec, base + r, r < RT - 2 ? POLL_NS3 : 100 TK_PASS);
        TK(0)
        uint32_t o0[J], o1[J];
        const uint32_t ab = sb - (H<2>::lap(base + r) >> 27 & 2u);
                auto odd = [&](uint32_t aux) { return lane & 1u; };
        uint32_t ad[J];
#pragma unroll
        for (int j = 0; j < J; j++) { ad[j] = aux_of(rec[j].x, rec[j].y); o0[j] = odd(ad[j]); }
#pragma unroll
        for (int j = 0; j < J; j++) {
            const uint32_t t = o0[j], a = ab + ad[j] * 2;
            const uint32_t v0 = (rec[j].x & 0x0fff0fffu) - 0x08000800u, v1 = (rec[j].y & 0x0fff0fffu) - 0x08000800u;
            o0[j] = t ? v1 : v0; o1[j] = t ? v0 : v1;
            if (!(rec[j].y & 0x20000000u)) {
                o0[j] = atoms_add<OFF_ACC>(a + t * 4, o0[j]);
                o1[j] = atoms_add<OFF_ACC + 4>(a - t * 4, o1[j]);
            }
        }
        uint32_t g = 0;
#pragma unroll
        for (int j = 0; j < J; j++) g |= o0[j] | o1[j];
        if (__any_sync(0xffffffffu, g & 0x80008000u)) {
#pragma unroll 1
            for (int j = 0; j < J; j++) {
                const uint2 w = pick(j, rec);
                const uint32_t aux = aux_of(w.x, w.y), t = odd(aux), p0 = pick(j, o0), p1 = pick(j, o1);
                const float2 a = acc_fix(t ? p1 : p0, w.x & 0x0fff0fffu), b = acc_fix(t ? p0 : p1, w.y & 0x0fff0fffu);
                const float unit = __uint_as_float(lds32(sb + W_UNIT));
                if (a.x != 0.f || a.y != 0.f || b.x != 0.f || b.y != 0.f)
                    side_add(lds32(sb + W_ROLE), aux >> 2, a.x * unit, a.y * unit, b.x * unit, b.y * unit);
                __syncwarp();
            }
        }
        rd.load(rec);
        TK(1)
    }
    rd.finish();
    TK_OUT
}

__device__ __forceinline__ uint32_t row_max(uint32_t x, uint32_t y) {
    const uint32_t mx = __vmaxu2(x & 0x7fff7fffu, y & 0x7fff7fffu);
    return max(mx & 0xffffu, mx >> 16);
}
constexpr int EWIN = 5;

__global__ void __launch_bounds__(NTHR, 1) fused_kernel(const Params p) {
    const int tid = threadIdx.x, lane = tid & 31;
    const int hw = __reduce_max_sync(0xffffffffu, tid >> 5);
    const uint32_t sb = __reduce_or_sync(0xffffffffu, (uint32_t)__cvta_generic_to_shared(smem));
    TKX(0)
    const uint32_t epoch = ld_rlx32(&g_base);
    uint32_t base = epoch & 7u;

    if (hw < NS1) {
        if (hw < NS1 - 1) stage1<4>(p, sb, hw * 128 + lane, lane, base);
        else stage1<NPR / 32 - (NS1 - 1) * 4>(p, sb, hw * 128 + lane, lane, base);
        __threadfence();
        bar_arrive(BAR_DONE, (NS1 + NC + 2) * 32);
    } else if (hw == W_M1) {
        if (lane == 0) {
            if (sb & 255u) __trap();
            mbar_init(sb + B_FULL, NS1); mbar_init(sb + B_OPEN, 1); mbar_init(sb + B_FREE, 1);
        }
        base = __reduce_or_sync(0xffffffffu, base);
        if (lane == 0 && (base & 1u)) { mbar_arrive(sb + B_OPEN); mbar_arrive(sb + B_FREE); }
        for (int i = lane; i < NG + NDUM; i += 32) sts32(sb + OFF_CNT1 + i * 4, H<1>::init(base) + (i < NG ? (i & 7) * 16 : 0x80000000u));
#pragma unroll 1
        for (int i = 0; i < 2; i++) Prefill<1>(lane).run(sb + OFF_H1 + H<1>::win(base + i), nulls<1>(lane, base + i));
        bar_arrive(BAR_S1, (NS1 + 1) * 32);
        bar_sync(BAR_PROBE, (2 * NC + 1) * 32);
        {
            const uint32_t raw = __ballot_sync(0xffffffffu, lane < 2 * NC && smem[OFF_PROBE + lane]), side = raw & 1u;
            uint32_t v = 0;
            if (lane < 2) asm volatile("atom.relaxed.gpu.global.add.u32 %0, [%1], %2;" : "=r"(v) : "l"(p.ring + M_CNT + lane * 4096), "r"(side ? 0x10000u : 1u) : "memory");
            const uint32_t mine = (side ? ~raw : raw) | 0x80000000u;
            if (lane == 2) asm volatile("atom.relaxed.gpu.global.cas.b32 %0, [%1], 0, %2;" : "=r"(v) : "l"(p.ring + M_PAR), "r"(mine) : "memory");
            bar_sync(BAR_HIST, (2 * NC + 1) * 32);
            uint32_t best = 0;
#pragma unroll 1
            for (int e = 11 + lane; e <= 230; e += 32) {
                uint32_t c = 0;
#pragma unroll
                for (int i = 0; i < EWIN; i++) c += lds32(sb + OFF_HIST + (e - i) * 4);
                best = max(best, c << 8 | (255 - e));
            }
            const uint32_t e = 255 - (__reduce_max_sync(0xffffffffu, best) & 255u);
            if (lane == 0) {
                const uint32_t role = side ? NB - 1 - (v >> 16) : v & 0xffffu;
                sts32(sb + W_ROLE, role); sts32(sb + W_SIDE, role < NLO ? 0u : role >= NHI ? 1u : side);
                sts32(sb + W_EXP, e); sts32(sb + W_UNIT, (e - 10) << 23); sts32(sb + W_END, (epoch | 7u) + 1u + (base + p.rounds) % 6u);
            }
            if (lane == 2) sts32(sb + W_PAR, v ? v : mine);
        }
        bar_sync(BAR_ROLE, (2 * NC + 2) * 32);
        manager<1>(p, sb, lane, __reduce_max_sync(0xffffffffu, lds32(sb + W_ROLE)), base);
        bar_arrive(BAR_H1, (NS1 + 1) * 32);
        __threadfence();
        bar_arrive(BAR_DONE, (NS1 + NC + 2) * 32);
    } else if (hw == W_M2) {
        const float wd = __bfloat162float(lane & 16 ? p.w_up[lane & 15] : p.w_down[lane & 15]);
        const float ws = __bfloat162float(p.w_sbf[lane]), wr = __bfloat162float(p.w_rbf[lane]);
        const __nv_bfloat16 cen = p.centers[lane & 7];
        if (lane == 0) { mbar_init(sb + B_FULL + 8, NC); mbar_init(sb + B_OPEN + 8, 1); }
        base = __reduce_or_sync(0xffffffffu, base);
        for (int i = lane; i < NB + NDUM; i += 32) sts32(sb + OFF_CNT2 + i * 4, H<2>::init(base) + (i < NB ? (i & 7) * 16 : 0x80000000u));
#pragma unroll 1
        for (int i = 0; i < 3; i++) Prefill<2>(lane).run(sb + H<2>::win(i), nulls<2>(lane, base + i));
        reinterpret_cast<float*>(smem + OFF_WSM)[lane] = wd;
        reinterpret_cast<float*>(smem + OFF_WG)[lane] = ws;
        reinterpret_cast<float*>(smem + OFF_WG + 128)[lane] = wr;
        reinterpret_cast<__nv_bfloat16*>(smem + OFF_WG + 256)[lane & 7] = cen;
        bar_sync(BAR_ROLE, (2 * NC + 2) * 32);
        manager<2>(p, sb, lane, __reduce_max_sync(0xffffffffu, lds32(sb + W_ROLE)), base);
        __threadfence();
        bar_sync(BAR_DONE, (NS1 + NC + 2) * 32);
        if (lane < 2) { __threadfence(); st_rlx32(reinterpret_cast<uint32_t*>(p.ring + M_FLAG + lane * 4096) + blockIdx.x, lds32(sb + W_END)); }
    } else {
        const int pw = __reduce_max_sync(0xffffffffu, hw < W_M1 ? hw - NS1 : hw - NS1 - 1), ct = pw * 32 + lane;
        constexpr int CT = 2 * NC * 32;
        const uint4 sm = __ldg(reinterpret_cast<const uint4*>(p.m) + min((ct >> 3) * (p.E >> 1) / (CT / 8) + (lane & 7), (p.E >> 1) - 1));
        if (ct < 256) sts32(sb + OFF_HIST + ct * 4, 0u);
        if (lane == 0) smem[OFF_PROBE + pw] = pw < NPAGE ? near_half(p.ring + (size_t)pw * PAGE + PROBE + (blockIdx.x & 31) * 128 + (blockIdx.x >> 5 & 3) * 16384 + (blockIdx.x >> 7 << 20), p.zero) : 0;
        TKX(1)
        bar_sync(BAR_PROBE, (2 * NC + 1) * 32);
        {
            const uint32_t m0 = row_max(sm.x, sm.y), m1 = row_max(sm.z, sm.w);
            if (m0) atoms_add<OFF_HIST>(sb + (m0 >> 7) * 4, 1u);
            if (m1) atoms_add<OFF_HIST>(sb + (m1 >> 7) * 4, 1u);
        }
        bar_arrive(BAR_HIST, (2 * NC + 1) * 32);
        base = __reduce_or_sync(0xffffffffu, base);
        for (int i = ct; i < R2MAX / 2; i += CT) reinterpret_cast<uint4*>(smem + OFF_ACC)[i] = make_uint4(0x40004000u, 0x40004000u, 0x40004000u, 0x40004000u);
        bar_sync(BAR_ROLE, (2 * NC + 2) * 32);
        const int role = __reduce_max_sync(0xffffffffu, lds32(sb + W_ROLE));
        TKX(2)
        {
            const int e = lds32(sb + W_EXP), q0 = (role >= NG ? role - NG : role) * (p.R1 >> 1), nq = min(p.R1 >> 1, (p.E >> 1) - q0);
            const uint32_t sc = (uint32_t)(254 - e) * 0x800080u;
            constexpr int CH = (R1MAX / 2 + CT - 1) / CT;
            uint4 v[CH];
#pragma unroll
            for (int u = 0; u < CH; u++) v[u] = __ldg(reinterpret_cast<const uint4*>(p.m) + min(q0 + ct + u * CT, (p.E >> 1) - 1));
            auto conv = [&](uint32_t& x, uint32_t& y) {
                const uint32_t mx = row_max(x, y);
                const int d = e - (int)(mx >> 7);
                x = hmul_bf2(x, sc); y = hmul_bf2(y, sc);
                if (d >= EWIN) y |= 0x40000000u;
                if (d < 0 || (d >= EWIN && e > 127)) { x = 0x40000000u; y = x; }
                if (mx == 0) { x = 0; y = 0; }
            };
#pragma unroll
            for (int u = 0; u < CH; u++) {
                conv(v[u].x, v[u].y); conv(v[u].z, v[u].w);
                if (ct + u * CT < nq) sts128<OFF_M>(sb + (ct + u * CT) * 16, v[u]);
            }
        }
        TKX(3)
        if (hw < W_M1) {
            stage2(p, sb, pw, lane, role, base);
            __threadfence();
            bar_arrive(BAR_DONE, (NS1 + NC + 2) * 32);
        } else {
            stage3(p, sb, pw - NC, lane, role, base);
            __threadfence();
        }
    }
    TKX(4)
    epilogue(p, sb);
}

__global__ void fb_scatter(const uint2* __restrict__ m, const int* __restrict__ idx_in, const int* __restrict__ idx_out,
                           const uint16_t* __restrict__ angle, const __nv_bfloat16* __restrict__ ang_freq, int T, int e0, int e1) {
    const uint32_t fb = *reinterpret_cast<const uint16_t*>(ang_freq);
    for (long long t = blockIdx.x * (long long)blockDim.x + threadIdx.x; t < T; t += (long long)gridDim.x * blockDim.x) {
        int o = idx_out[t];
        if (o < e0 || o >= e1) continue;
        float c = bf16r(cos_bf(hmul_bf2(angle[t], fb) & 0xffffu));
        uint2 v = __ldg(m + idx_in[t]);
        red4(&g_ovf[o - e0], c * bf_lo(v.x), c * bf_hi(v.x), c * bf_lo(v.y), c * bf_hi(v.y));
    }
}
__global__ void fb_final(const Params p, int e0, int e1) {
    int e = e0 + blockIdx.x * blockDim.x + threadIdx.x;
    if (e >= e1) return;
    float4 a4 = g_ovf[e - e0];
    g_ovf[e - e0] = make_float4(0.f, 0.f, 0.f, 0.f);
    float a[4] = {a4.x, a4.y, a4.z, a4.w};
    float d = __bfloat162float(p.dist[e]);
    float g[4] = {0, 0, 0, 0}, h[4] = {0, 0, 0, 0};
    for (int r = 0; r < 8; r++) {
        float df = bf16r(d - __bfloat162float(p.centers[r]));
        float rb = bf16r(expf(bf16r(-10.0f * bf16r(df * df))));
        for (int k = 0; k < 4; k++) {
            g[k] += rb * __bfloat162float(p.w_sbf[r * 4 + k]);
            h[k] += rb * __bfloat162float(p.w_rbf[r * 4 + k]);
        }
    }
    float ag[4];
    for (int k = 0; k < 4; k++) {
        float s = 0.f;
        for (int j = 0; j < 4; j++) s += a[j] * __bfloat162float(p.w_down[j * 4 + k]);
        ag[k] = bf16r(s * g[k]);
    }
    uint2 mv = p.m[e];
    float mm[4] = {bf_lo(mv.x), bf_hi(mv.x), bf_lo(mv.y), bf_hi(mv.y)};
    __nv_bfloat16 o[4];
    for (int k = 0; k < 4; k++) {
        float u = 0.f;
        for (int j = 0; j < 4; j++) u += ag[j] * __bfloat162float(p.w_up[j * 4 + k]);
        o[k] = __float2bfloat16_rn(mm[k] + bf16r(bf16r(u) * bf16r(h[k])));
    }
    p.out[e] = *reinterpret_cast<uint2*>(o);
}

}

static bool exact_div(int E, int lo, int hi, int* R, uint32_t* magic) {
    for (int r = lo + (lo & 1); r <= hi; r += 2) {
        unsigned long long mg = ((1ull << 32) + r - 1) / r, err = mg * r - (1ull << 32);
        if (err * (unsigned long long)E < (1ull << 32)) { *R = r; *magic = (uint32_t)mg; return true; }
    }
    return false;
}

extern "C" void kernel_launch(void* const* d_in, const int* in_sizes, int n_in, void* d_out, int out_size) {
    typedef const __nv_bfloat16* B;
    Params p;
    p.m = (const uint2*)d_in[0]; p.idx_in = (const uint2*)d_in[1]; p.idx_out = (const uint2*)d_in[2]; p.dist = (B)d_in[3];
    p.angle = (const uint32_t*)d_in[4]; p.centers = (B)d_in[5]; p.ang_freq = (B)d_in[6]; p.w_rbf = (B)d_in[7]; p.w_sbf = (B)d_in[8];
    p.w_down = (B)d_in[9]; p.w_up = (B)d_in[10]; p.out = (uint2*)d_out;
    p.E = in_sizes[3]; p.T = in_sizes[1]; p.T2 = p.T >> 1; p.zero = 0;
    p.R1 = p.R2 = p.rounds = p.lastn = p.qfull = 0; p.mg1 = p.mg2 = p.k1 = p.k2 = 0;
    static int ok = -1;
    static unsigned char* ring = nullptr;
    if (ok < 0) {
        void* ra = nullptr;
        cudaGetSymbolAddress(&ra, g_ring);
        ring = reinterpret_cast<unsigned char*>(((uintptr_t)ra + PAGE - 1) & ~(uintptr_t)(PAGE - 1));
        int dev = 0, sms = 0, occ = 0;
        cudaGetDevice(&dev);
        cudaDeviceGetAttribute(&sms, cudaDevAttrMultiProcessorCount, dev);
        cudaError_t e = cudaFuncSetAttribute(fused_kernel, cudaFuncAttributeMaxDynamicSharedMemorySize, SMEM_BYTES);
        if (e == cudaSuccess) e = cudaOccupancyMaxActiveBlocksPerMultiprocessor(&occ, fused_kernel, NTHR, SMEM_BYTES);
        ok = (e == cudaSuccess && occ >= 1 && sms >= NB) ? 1 : 0;
        (void)cudaGetLastError();
    }
    p.ring = ring;
    const bool fused = ok == 1 && p.E <= EMAX && p.E >= 2 * NB && p.E % 2 == 0 && p.T >= 2 && exact_div(p.E, (p.E + NG - 1) / NG, R1MAX, &p.R1, &p.mg1) &&
                       exact_div(p.E, (p.E + NB - 1) / NB, R2MAX, &p.R2, &p.mg2);
    if (fused) {
        p.k1 = 0u - (uint32_t)p.R1; p.k2 = 0u - 4u * (uint32_t)p.R2;
        const int per = NB * NPR;
        int full = p.T2 / per, rest = p.T2 - full * per;
        p.qfull = full * per;
        p.lastn = (rest + NB - 1) / NB;
        if (p.lastn > NPR / 2) { full++; p.lastn = 0; }
        if (full < D) { full = D; p.lastn = 0; }
        p.rounds = full + 1;
        fused_kernel<<<NB, NTHR, SMEM_BYTES>>>(p);
    } else {
        for (int e0 = 0; e0 < p.E; e0 += EMAX) {
            int e1 = p.E - e0 < EMAX ? p.E : e0 + EMAX;
            fb_scatter<<<1056, 256>>>(p.m, (const int*)d_in[1], (const int*)d_in[2], (const uint16_t*)d_in[4], p.ang_freq, p.T, e0, e1);
            fb_final<<<(e1 - e0 + 255) / 256, 256>>>(p, e0, e1);
        }
    }
}
```

```cpp
#include <cuda_runtime.h>
#include <cuda_bf16.h>
#include <stdint.h>

namespace {

constexpr int NB = 132, NG = 66;
constexpr int R2MAX = 6062, R1MAX = 12124;
constexpr int EMAX = NB * R2MAX;
constexpr int NTHR = 1024;
constexpr int NS1 = 8, NC = 11, J = 6;
#define TILES 15
constexpr int NPR = TILES * 64;
constexpr int D = 3;
constexpr int WIN = 16896;
constexpr int NDUM = 16;
constexpr uint32_t DUMMY = 0xc0000000u;

constexpr int OFF_ACC = WIN, OFF_BAR = OFF_ACC + R2MAX * 8;
constexpr int OFF_H1 = 0x10000 + WIN, OFF_M = OFF_H1 + WIN, OFF_WSM = OFF_M + R1MAX * 8;
constexpr int OFF_CNT1 = OFF_H1 + 0x20000 + WIN, OFF_CNT2 = OFF_CNT1 + (NG + NDUM + 2) * 4, W_RND = OFF_CNT2 + (NB + NDUM) * 4, OFF_WG = W_RND + 16;
constexpr int OFF_HIST = OFF_M;
constexpr int OFF_PROBE = OFF_WSM + 128;
constexpr int SMEM_BYTES = OFF_WG + 272;
static_assert(SMEM_BYTES <= 232448 && OFF_BAR + 64 <= 0x10000 && OFF_PROBE + 32 <= 0x30000, "smem");
static_assert(OFF_BAR % 8 == 0 && OFF_WG % 16 == 0 && OFF_WSM % 16 == 0 && OFF_CNT2 % 16 == 0, "align");
static_assert(NC * J == NG && NC * 32 * 6 * 16 == 2 * WIN, "shape");

template <int HOP> struct H {
    static constexpr int S = HOP == 1 ? 32 : 16, NBIN = HOP == 1 ? NG : NB, CAP = HOP == 1 ? 48 : 32, SH = HOP == 1 ? 11 : 12;
    static constexpr int TB = HOP == 1 ? 20 : 28, CNT = HOP == 1 ? OFF_CNT1 : OFF_CNT2, STG = HOP == 1 ? OFF_H1 : 0;
    static constexpr uint32_t INC = (1u << SH) + 8u, PM = (S - 1) * 8, TAG = 7u << TB;
    static __device__ __forceinline__ uint32_t tag(uint32_t R) { return R << TB & TAG; }
    static __device__ __forceinline__ uint32_t init(uint32_t R) { return tag(R) | ((1u << TB) - 0x10000u); }
    static __device__ __forceinline__ uint32_t mark(uint32_t R, uint32_t line) { return ((HOP == 1 ? R >> 1 : R) + line) & 3u; }
    static __device__ __forceinline__ uint32_t win(int r) { return HOP == 1 ? (r & 1) << 17 : (0x310u >> (r % 3 * 4) & 3u) << 16; }
};

constexpr uint32_t PAGE = 1u << 21;
constexpr int NPAGE = NC + 2;
__device__ __align__(256) unsigned char g_ring[(size_t)(NPAGE + 1) * PAGE];
constexpr int MISC = 0xa0000;
constexpr int M_CNT = MISC + 1024, M_PAR = MISC + 1088;
constexpr int M_FLAG = MISC + 2048;
constexpr int PROBE = MISC + 0x40000;
#define CSTR 16384
__device__ __forceinline__ uint32_t cred_off(uint32_t role) { return role * 4 + min(role >> 5, 3u) * (CSTR - 128); }
struct Ring {
    uint64_t main, mid;
    uint32_t par;
    __device__ __forceinline__ Ring(const unsigned char* ring, uint32_t pars, int k) {
        main = reinterpret_cast<uint64_t>(ring) + ((uint64_t)k << 20);
        par = pars >> (k >> 1) & 1u;
        mid = reinterpret_cast<uint64_t>(ring) + (uint64_t)NC * PAGE + (((k >> 3 << 20) + (k >> 2 & 1) * 0x11000u + (k & 1) * 2048) ^ (k >> 1 & 1) * 0x3000u ^ (pars >> (NC + (k >> 4)) & 1u) << 12);
    }
};
constexpr int NLO = 60, NHI = 72;
__host__ __device__ constexpr uint32_t src_off(int j) { return (j % 3) << 14 | (j / 3) << 18; }
__device__ __forceinline__ uint32_t slot_off(uint32_t s) { return (0xa930u >> s * 4 & 15u) << 16; }
__device__ __forceinline__ uint32_t slot_steps(uint32_t R) { return (uint32_t)(0x30a09030aull >> (2 - R % 3) * 8) & 0xffffffu; }
__device__ __forceinline__ void slot_next(uint32_t& a, uint32_t st) { a ^= st & 0xf0000u; }
__device__ __forceinline__ uint32_t slot_rot(uint32_t st) { return __byte_perm(st, 0u, 0x4102); }
constexpr int RPAD = 6064, DROW = 6144;
__device__ __align__(128) uint8_t g_dirty[NB * DROW];
__device__ uint32_t g_base = 1;
__device__ __align__(128) float4 g_ovf[NB * RPAD];

struct Params {
    const uint2* m; const uint2* idx_in; const uint2* idx_out; const __nv_bfloat16* dist; const uint32_t* angle;
    const __nv_bfloat16* centers; const __nv_bfloat16* ang_freq; const __nv_bfloat16* w_rbf; const __nv_bfloat16* w_sbf;
    const __nv_bfloat16* w_down; const __nv_bfloat16* w_up; uint2* out; unsigned char* ring;
    int E, T, T2, R1, R2, rounds, lastn, qfull; uint32_t mg1, mg2, k1, k2, zero;
};

__device__ __forceinline__ float bf16r(float x) { return __bfloat162float(__float2bfloat16_rn(x)); }
__device__ __forceinline__ float bf_lo(uint32_t v) { return __uint_as_float(v << 16); }
__device__ __forceinline__ float bf_hi(uint32_t v) { return __uint_as_float(v & 0xffff0000u); }
__device__ __forceinline__ void red4(float4* a, float x, float y, float z, float w) {
    asm volatile("red.global.add.v4.f32 [%0], {%1,%2,%3,%4};" ::"l"(a), "f"(x), "f"(y), "f"(z), "f"(w) : "memory");
}
__device__ __forceinline__ void bar_sync(int id, int n) { __syncwarp(); asm volatile("bar.sync %0, %1;" ::"r"(id), "r"(n) : "memory"); }
__device__ __forceinline__ void bar_arrive(int id, int n) { __syncwarp(); asm volatile("bar.arrive %0, %1;" ::"r"(id), "r"(n) : "memory"); }
template <int OFF> __device__ __forceinline__ uint32_t atoms_add(uint32_t addr, uint32_t v) {
    uint32_t r; asm volatile("atom.shared.add.u32 %0, [%1+%3], %2;" : "=r"(r) : "r"(addr), "r"(v), "n"(OFF) : "memory"); return r;
}
__device__ __forceinline__ void sts64(uint32_t addr, uint32_t x, uint32_t y) {
    asm volatile("st.shared.v2.u32 [%0], {%1,%2};" ::"r"(addr), "r"(x), "r"(y) : "memory");
}
__device__ __forceinline__ void sts32(uint32_t addr, uint32_t x) { asm volatile("st.shared.u32 [%0], %1;" ::"r"(addr), "r"(x) : "memory"); }
template <int OFF = 0> __device__ __forceinline__ uint2 lds64(uint32_t addr) {
    uint2 v; asm volatile("ld.shared.v2.u32 {%0,%1}, [%2+%3];" : "=r"(v.x), "=r"(v.y) : "r"(addr), "n"(OFF) : "memory"); return v;
}
__device__ __forceinline__ uint32_t lds32(uint32_t addr) {
    uint32_t v; asm volatile("ld.shared.u32 %0, [%1];" : "=r"(v) : "r"(addr) : "memory"); return v;
}
__device__ __forceinline__ uint32_t ld_rlx32(const uint32_t* p) {
    uint32_t v; asm volatile("ld.relaxed.gpu.global.u32 %0, [%1];" : "=r"(v) : "l"(p) : "memory"); return v;
}
__device__ __forceinline__ uint2 ld_rlx64(const void* p) {
    uint2 v; asm volatile("ld.relaxed.gpu.global.v2.u32 {%0,%1}, [%2];" : "=r"(v.x), "=r"(v.y) : "l"(p) : "memory"); return v;
}
__device__ __forceinline__ float4 ld_rlx128f(const float4* p) {
    float4 v; asm volatile("ld.relaxed.gpu.global.v4.f32 {%0,%1,%2,%3}, [%4];" : "=f"(v.x), "=f"(v.y), "=f"(v.z), "=f"(v.w) : "l"(p) : "memory"); return v;
}
__device__ __forceinline__ void take3(float4* p, uint32_t mask, float4 (&v)[3]) {
    asm volatile("{ .reg .b128 a, b, c; .reg .b64 x, y; .reg .pred q0, q1, q2; .reg .b32 t;\n"
                 "mov.b64 x, 0; mov.b128 a, {x, x}; mov.b128 b, {x, x}; mov.b128 c, {x, x};\n"
                 "and.b32 t, %13, 1; setp.ne.u32 q0, t, 0; and.b32 t, %13, 2; setp.ne.u32 q1, t, 0; and.b32 t, %13, 4; setp.ne.u32 q2, t, 0;\n"
                 "@q0 atom.relaxed.gpu.global.exch.b128 a, [%12], a; @q1 atom.relaxed.gpu.global.exch.b128 b, [%12+16384], b;\n"
                 "@q2 atom.relaxed.gpu.global.exch.b128 c, [%12+32768], c;\n"
                 "mov.b128 {x, y}, a; mov.b64 {%0,%1}, x; mov.b64 {%2,%3}, y; mov.b128 {x, y}, b; mov.b64 {%4,%5}, x; mov.b64 {%6,%7}, y;\n"
                 "mov.b128 {x, y}, c; mov.b64 {%8,%9}, x; mov.b64 {%10,%11}, y; }"
                 : "=f"(v[0].x), "=f"(v[0].y), "=f"(v[0].z), "=f"(v[0].w), "=f"(v[1].x), "=f"(v[1].y), "=f"(v[1].z), "=f"(v[1].w),
                   "=f"(v[2].x), "=f"(v[2].y), "=f"(v[2].z), "=f"(v[2].w) : "l"(p), "r"(mask) : "memory");
}
__device__ __forceinline__ void st_rlx32(uint32_t* p, uint32_t v) { asm volatile("st.relaxed.gpu.global.u32 [%0], %1;" ::"l"(p), "r"(v) : "memory"); }
__device__ __forceinline__ uint32_t hmul_bf2(uint32_t a, uint32_t b) {
    uint32_t r; asm("mul.rn.bf16x2 %0, %1, %2;" : "=r"(r) : "r"(a), "r"(b)); return r;
}
__device__ __forceinline__ uint32_t hsub_bf2(uint32_t a, uint32_t b) {
    uint32_t r; asm("sub.rn.bf16x2 %0, %1, %2;" : "=r"(r) : "r"(a), "r"(b)); return r;
}
constexpr int SPIN_LIMIT = 1 << 22;

__constant__ uint32_t c_inv2pi[8] = {0u, 0x28be60dbu, 0x9391054au, 0x7f09d5f4u, 0x7d4d3770u, 0x36d8a566u, 0x4f10e410u, 0x7f9458eau};
constexpr uint32_t BIGX = 0x4280u;
__device__ __forceinline__ float cos_big(uint32_t xb) {
    uint32_t e = (xb >> 7) & 0xffu, M = (xb & 0x7fu) | 0x80u;
    uint32_t pp = e - 102u;
    uint32_t wi = pp >> 5;
    uint32_t t0 = c_inv2pi[wi], t1 = c_inv2pi[wi + 1], t2 = c_inv2pi[wi + 2];
    uint32_t f = M * __funnelshift_l(t1, t0, pp) + __umulhi(M, __funnelshift_l(t2, t1, pp));
    float c = __cosf((float)(int)f * 1.4629180792671596e-9f);
    return e == 255u ? __uint_as_float(0x7fc00000u) : c;
}
__device__ __forceinline__ float cos_bf(uint32_t xb) {
    return (xb & 0x7fffu) > BIGX ? cos_big(xb) : __cosf(__uint_as_float(xb << 16));
}
__device__ __forceinline__ uint32_t pack_bf2(float lo, float hi) {
    uint32_t r; asm("cvt.rn.bf16x2.f32 %0, %1, %2;" : "=r"(r) : "f"(hi), "f"(lo)); return r;
}
template <int N> __device__ __forceinline__ uint32_t pick(int k, const uint32_t (&a)[N]) {
    uint32_t v = a[0];
#pragma unroll
    for (int i = 1; i < N; i++) if (k == i) v = a[i];
    return v;
}
template <int N> __device__ __forceinline__ uint2 pick(int k, const uint2 (&a)[N]) {
    uint2 v = a[0];
#pragma unroll
    for (int i = 1; i < N; i++) if (k == i) v = a[i];
    return v;
}
__device__ __forceinline__ void side_add(uint32_t bin, uint32_t row, float a, float b, float c, float d) {
    red4(&g_ovf[bin * RPAD + row], a, b, c, d);
    g_dirty[bin * DROW + row] = 1;
}
__device__ __forceinline__ void slow_triplet(const Params& p, uint32_t ii, uint32_t oo, float c) {
    const uint2 v = __ldg(p.m + ii);
    const uint32_t bo = __umulhi(oo, p.mg2);
    side_add(bo, oo - bo * p.R2, c * bf_lo(v.x), c * bf_hi(v.x), c * bf_lo(v.y), c * bf_hi(v.y));
}
__device__ __forceinline__ void slow_rec1(const Params& p, uint32_t x, uint32_t y, uint32_t bin) {
    const uint2 v = __ldg(p.m + bin * p.R1 + (y & 0xffffu));
    const float c = bf_hi(y);
    side_add(x & 0xffu, __byte_perm(x, 0u, 0x4413) >> 3, c * bf_lo(v.x), c * bf_hi(v.x), c * bf_lo(v.y), c * bf_hi(v.y));
}
__device__ __forceinline__ uint32_t aux_of(uint32_t w0, uint32_t w1, uint32_t k = 0) {
    uint32_t u; asm("lop3.b32 %0, %1, %2, 0xf000f000, 0xe4;" : "=r"(u) : "r"(w0), "r"((w1 >> 4) + k));
    return __byte_perm(u, 0u, 0x4413);
}
__device__ __forceinline__ void slow_rec2(const Params& p, uint32_t w0, uint32_t w1, uint32_t bin, float unit) {
    side_add(bin, aux_of(w0, w1) >> 3, (float)((int)(w0 & 0xfffu) - 2048) * unit, (float)((int)(w0 >> 16 & 0xfffu) - 2048) * unit,
             (float)((int)(w1 & 0xfffu) - 2048) * unit, (float)((int)(w1 >> 16 & 0xfffu) - 2048) * unit);
}
template <uint32_t M> __device__ __forceinline__ uint32_t and_or(uint32_t a, uint32_t c) {
    uint32_t r; asm("lop3.b32 %0, %1, %2, %3, 0xea;" : "=r"(r) : "r"(a), "n"(M), "r"(c)); return r;
}
template <uint32_t M> __device__ __forceinline__ uint32_t xor_and(uint32_t a, uint32_t c) {
    uint32_t r; asm("lop3.b32 %0, %1, %2, %3, 0x48;" : "=r"(r) : "r"(a), "n"(M), "r"(c)); return r;
}
__device__ __forceinline__ uint32_t mux(uint32_t a, uint32_t b, uint32_t m) {
    uint32_t r; asm("lop3.b32 %0, %1, %2, %3, 0xd8;" : "=r"(r) : "r"(a), "r"(b), "r"(m)); return r;
}
__device__ __forceinline__ uint32_t and_xor(uint32_t a, uint32_t m, uint32_t c) {
    uint32_t r; asm("lop3.b32 %0, %1, %2, %3, 0x6a;" : "=r"(r) : "r"(a), "r"(m), "r"(c)); return r;
}
__device__ __forceinline__ uint2 ld_in(const uint2* a) {
    uint2 v; asm volatile("ld.global.nc.L1::no_allocate.v2.u32 {%0,%1}, [%2];" : "=r"(v.x), "=r"(v.y) : "l"(a)); return v;
}
__device__ __forceinline__ uint32_t ld_in(const uint32_t* a) {
    uint32_t v; asm volatile("ld.global.nc.L1::no_allocate.u32 %0, [%1];" : "=r"(v) : "l"(a)); return v;
}
template <int OFF> __device__ __forceinline__ void put_rec(uint32_t ret, uint32_t lim, uint32_t addr, uint32_t x, uint32_t y) {
    asm volatile("{ .reg .pred q; setp.lt.u32 q, %0, %1; @q st.shared.v2.u32 [%2+%5], {%3,%4}; }" ::"r"(ret), "r"(lim), "r"(addr), "r"(x), "r"(y), "n"(OFF) : "memory");
}
__device__ __forceinline__ uint32_t mbar_try(uint32_t mb, uint32_t parity) {
    uint32_t ok;
    asm volatile("{ .reg .pred q; mbarrier.try_wait.parity.shared::cta.b64 q, [%1], %2; selp.u32 %0, 1, 0, q; }" : "=r"(ok) : "r"(mb), "r"(parity) : "memory");
    return ok;
}
__device__ __forceinline__ void mbar_wait(uint32_t mb, uint32_t parity) {
    if (!mbar_try(mb, parity)) {
        int it = 0;
        while (!mbar_try(mb, parity)) if (++it > SPIN_LIMIT) __trap();
    }
}
__device__ __forceinline__ void mbar_init(uint32_t mb, uint32_t n) { asm volatile("mbarrier.init.shared::cta.b64 [%0], %1;" ::"r"(mb), "r"(n) : "memory"); }
__device__ __forceinline__ void mbar_arrive(uint32_t mb) { asm volatile("mbarrier.arrive.shared::cta.b64 _, [%0];" ::"r"(mb) : "memory"); }
constexpr int B_FULL = OFF_BAR, B_OPEN = OFF_BAR + 16, B_FREE = OFF_BAR + 32;
constexpr int W_END = OFF_BAR + 40, W_SIDE = OFF_BAR + 44, W_PAR = OFF_BAR + 48, W_ROLE = OFF_BAR + 52, W_EXP = OFF_BAR + 56, W_UNIT = OFF_BAR + 60;
enum { BAR_S1 = 1, BAR_PROBE, BAR_HIST, BAR_ROLE, BAR_TABLE, BAR_H1, BAR_DONE };
constexpr int W_M1 = NS1 + NC, W_M2 = 31;

extern __shared__ __align__(1024) unsigned char smem[];
#define TK_DECL
#define TK(i)
#define TK_CNT(i)
#define TK_OUT
#define TK_ARG
#define TK_PASS
#define TKX(i)
#define TKY(i)

constexpr int NR = (R2MAX + NTHR - 1) / NTHR;
__device__ __forceinline__ void gates(const Params& p, int e0, int e1, int e2, uint4* gh) {
    constexpr int NH = 3;
    const int e[NH] = {e0, e1, e2};
    uint32_t dd[NH];
    float g[NH][4], h[NH][4];
#pragma unroll
    for (int u = 0; u < NH; u++) {
        dd[u] = reinterpret_cast<const uint16_t*>(p.dist)[min(e[u], p.E - 1)] * 0x10001u;
#pragma unroll
        for (int k = 0; k < 4; k++) { g[u][k] = 0.f; h[u][k] = 0.f; }
    }
#pragma unroll 1
    for (int r2 = 0; r2 < 4; r2++) {
        const uint32_t cen = reinterpret_cast<const uint32_t*>(smem + OFF_WG + 256)[r2];
        uint32_t rb[NH];
#pragma unroll
        for (int u = 0; u < NH; u++) {
            const uint32_t df = hsub_bf2(dd[u], cen);
            const uint32_t ar = hmul_bf2(hmul_bf2(df, df), 0xc120c120u);
            rb[u] = pack_bf2(__expf(bf_lo(ar)), __expf(bf_hi(ar)));
        }
#pragma unroll
        for (int i = 0; i < 2; i++) {
            const float4 ws = reinterpret_cast<const float4*>(smem + OFF_WG)[r2 * 2 + i], wr = reinterpret_cast<const float4*>(smem + OFF_WG + 128)[r2 * 2 + i];
#pragma unroll
            for (int u = 0; u < NH; u++) {
                const float x = i ? bf_hi(rb[u]) : bf_lo(rb[u]);
                g[u][0] += x * ws.x; g[u][1] += x * ws.y; g[u][2] += x * ws.z; g[u][3] += x * ws.w;
                h[u][0] += x * wr.x; h[u][1] += x * wr.y; h[u][2] += x * wr.z; h[u][3] += x * wr.w;
            }
        }
    }
#pragma unroll
    for (int u = 0; u < NH; u++)
        gh[u] = make_uint4(pack_bf2(g[u][0], g[u][1]), pack_bf2(g[u][2], g[u][3]), pack_bf2(h[u][0], h[u][1]), pack_bf2(h[u][2], h[u][3]));
}
__device__ __forceinline__ void prefetch_l2(const void* a) { asm volatile("prefetch.global.L2 [%0];" ::"l"(a)); }
__device__ __forceinline__ uint4* gate_slot(int k) { return reinterpret_cast<uint4*>(smem + OFF_H1 + (k >= WIN / 16 ? 0x20000 - WIN : 0)) + k; }
__device__ __forceinline__ void wait_flags(const Params& p, uint32_t sb, int lane, uint32_t need) {
    const unsigned char* f = p.ring + M_FLAG + (lds32(sb + W_SIDE) << 12);
    int it = 0;
    while (true) {
        const float4 a = ld_rlx128f(reinterpret_cast<const float4*>(f) + lane);
        const uint32_t b = ld_rlx32(reinterpret_cast<const uint32_t*>(f) + 128 + (lane & 3));
        const uint32_t d = (__float_as_uint(a.x) ^ need) | (__float_as_uint(a.y) ^ need) | (__float_as_uint(a.z) ^ need) | (__float_as_uint(a.w) ^ need) | (b ^ need);
        if (__all_sync(0xffffffffu, d == 0)) break;
        __nanosleep(50);
        if (++it > SPIN_LIMIT) __trap();
    }
    __threadfence();
}
__device__ __forceinline__ void epilogue(const Params& p, uint32_t sb) {
    int tid;
    asm volatile("mov.u32 %0, %%tid.x;" : "=r"(tid));
    const int role = lds32(sb + W_ROLE), row0 = role * p.R2, nrows = min(p.R2, p.E - row0), hw = tid >> 5;
    const bool s3 = hw > W_M1 && hw < W_M2;
    constexpr int T3 = (W_M1 + 1) * 32, N3 = NC * 32;
    uint4 gh[NR];
    if (hw < NS1) {
        if (tid * 64 < nrows) prefetch_l2(p.dist + row0 + tid * 64);
        for (int i = tid * 16; i < nrows; i += NS1 * 32 * 16) prefetch_l2(p.m + row0 + i);
    }
    if (!s3) gates(p, row0 + tid + 3 * NTHR, row0 + tid + 4 * NTHR, row0 + tid + 5 * NTHR, gh + 3);
    if (hw < NS1) {
        bar_sync(BAR_H1, (NS1 + 1) * 32);
#pragma unroll 1
        for (int k0 = tid; k0 < NR * N3; k0 += 3 * NS1 * 32) {
            int k[3], e[3];
#pragma unroll
            for (int u = 0; u < 3; u++) { k[u] = k0 + u * NS1 * 32; e[u] = row0 + T3 + k[u] + k[u] / N3 * (NTHR - N3); }
            gates(p, e[0], e[1], e[2], gh);
#pragma unroll
            for (int u = 0; u < 3; u++) if (k[u] < NR * N3) *gate_slot(k[u]) = gh[u];
        }
#pragma unroll
        for (int i = tid; i < DROW / 8; i += NS1 * 32) {
            const uint2 f = ld_rlx64(g_dirty + role * DROW + i * 8);
            if (f.x | f.y) prefetch_l2(g_ovf + role * RPAD + i * 8);
        }
    }
    if (!s3) gates(p, row0 + tid, row0 + tid + NTHR, row0 + tid + 2 * NTHR, gh);
    if (hw == W_M1) wait_flags(p, sb, tid & 31, lds32(sb + W_END));
    TKX(5)
    bar_sync(0, NTHR);
    TKX(6)
    uint32_t dirty = 0;
#pragma unroll
    for (int it = 0; it < NR; it++) {
        uint32_t f;
        asm volatile("ld.relaxed.gpu.global.u8 %0, [%1];" : "=r"(f) : "l"(g_dirty + role * DROW + tid + it * NTHR) : "memory");
        dirty |= f << it;
    }
    if (s3) {
#pragma unroll
        for (int it = 0; it < NR; it++) gh[it] = *gate_slot(tid - T3 + it * N3);
    }
    if (hw == W_M1 && blockIdx.x == 0) {
        if (tid == W_M1 * 32) g_base = lds32(sb + W_END);
        if (tid < W_M1 * 32 + 3) *reinterpret_cast<uint32_t*>(p.ring + (tid & 2 ? M_PAR : M_CNT + (tid & 1) * 4096)) = 0;
    }
    const float unit = *reinterpret_cast<const float*>(smem + W_UNIT);
    const float4* w4 = reinterpret_cast<const float4*>(smem + OFF_WSM);
#pragma unroll
    for (int i0 = 0; i0 < NR; i0 += 3) {
        uint2 mv[3];
        float4 o[3];
#pragma unroll
        for (int u = 0; u < 3; u++) mv[u] = __ldg(p.m + min(row0 + tid + (i0 + u) * NTHR, p.E - 1));
        take3(&g_ovf[role * RPAD + tid + i0 * NTHR], dirty >> i0, o);
#pragma unroll
        for (int u = 0; u < 3; u++) {
            const int it = i0 + u, i = tid + it * NTHR;
            if (dirty >> it & 1) g_dirty[role * DROW + i] = 0;
            if (i < nrows) {
                const uint2 ac = reinterpret_cast<const uint2*>(smem + OFF_ACC)[i];
                const uint32_t u0 = ac.x + 0x40004000u, u1 = ac.y + 0x40004000u;
                const float a[4] = {(float)((int)(u0 & 0xffffu) - 0x8000) * unit + o[u].x, (float)((int)(u0 >> 16) - 0x8000) * unit + o[u].y,
                                    (float)((int)(u1 & 0xffffu) - 0x8000) * unit + o[u].z, (float)((int)(u1 >> 16) - 0x8000) * unit + o[u].w};
                float sd[4] = {0, 0, 0, 0}, uu[4] = {0, 0, 0, 0};
#pragma unroll
                for (int j = 0; j < 4; j++) {
                    float4 w = w4[j];
                    sd[0] += a[j] * w.x; sd[1] += a[j] * w.y; sd[2] += a[j] * w.z; sd[3] += a[j] * w.w;
                }
                const uint32_t a01 = pack_bf2(sd[0] * bf_lo(gh[it].x), sd[1] * bf_hi(gh[it].x)), a23 = pack_bf2(sd[2] * bf_lo(gh[it].y), sd[3] * bf_hi(gh[it].y));
                const float ag[4] = {bf_lo(a01), bf_hi(a01), bf_lo(a23), bf_hi(a23)};
#pragma unroll
                for (int j = 0; j < 4; j++) {
                    float4 w = w4[4 + j];
                    uu[0] += ag[j] * w.x; uu[1] += ag[j] * w.y; uu[2] += ag[j] * w.z; uu[3] += ag[j] * w.w;
                }
                const uint32_t t01 = hmul_bf2(pack_bf2(uu[0], uu[1]), gh[it].z);
                const uint32_t t23 = hmul_bf2(pack_bf2(uu[2], uu[3]), gh[it].w);
                uint2 q;
                asm("add.rn.bf16x2 %0, %1, %2;" : "=r"(q.x) : "r"(mv[u].x), "r"(t01));
                asm("add.rn.bf16x2 %0, %1, %2;" : "=r"(q.y) : "r"(mv[u].y), "r"(t23));
                p.out[row0 + i] = q;
            }
        }
        if (i0 == 0) { TKY(3) }
    }
}

template <int HOP> __device__ __forceinline__ uint2 null_rec(int lane, uint32_t R) {
    if (HOP == 1) return make_uint2(0x800000u | H<1>::tag(R), (OFF_CNT1 - OFF_M) / 8);
    return make_uint2(0x08000800u | lane << 28, 0x08000800u | H<2>::tag(R));
}
template <int OFF> __device__ __forceinline__ void sts128(uint32_t a, const uint4& v) {
    asm volatile("st.shared.v4.u32 [%0+%5], {%1,%2,%3,%4};" ::"r"(a), "r"(v.x), "r"(v.y), "r"(v.z), "r"(v.w), "n"(OFF) : "memory");
}
template <int HOP> __device__ __forceinline__ void fill(uint32_t win, int lane, uint32_t R) {
    const uint2 v = null_rec<HOP>(lane, R);
#pragma unroll 11
    for (int i = 0; i < WIN / 512; i++) sts128<0>(win + lane * 16 + i * 512, make_uint4(v.x, v.y, v.x, v.y));
}
template <int HOP> __device__ __forceinline__ void reset(uint32_t win, int lane, uint32_t R) {
    const uint2 v = null_rec<HOP>(lane, R);
    const uint32_t a = win + lane * 32 + H<HOP>::mark(R, lane >> 2) * 8;
#pragma unroll
    for (int i = 0; i < 16; i++) sts64(a + i * 1024, v.x, v.y);
    if (lane < 16) sts64(a + 16384, v.x, v.y);
}
__device__ __forceinline__ bool elect() {
    uint32_t q; asm volatile("{ .reg .pred q; elect.sync _|q, 0xffffffff; selp.u32 %0, 1, 0, q; }" : "=r"(q)); return q;
}
__device__ __forceinline__ const unsigned char* mk_ptr(uint32_t lo, uint32_t hi) { return reinterpret_cast<const unsigned char*>((uint64_t)hi << 32 | lo); }
__device__ __forceinline__ void bulk_store(uint32_t lo, uint32_t hi, uint32_t src, uint32_t n) {
    asm volatile("cp.async.bulk.global.shared::cta.bulk_group [%0], [%1], %2;" ::"l"(mk_ptr(lo, hi)), "r"(src), "r"(n) : "memory");
}
#define CRED_NS 100
#define CRED_SKIP 1
#define LAG 0
template <int HOP>
__device__ __forceinline__ void manager(const Params& p, uint32_t sb, int lane, int role, uint32_t base) {
    typedef H<HOP> h;
    constexpr int V = h::NBIN / 32, PB = h::S * 8;
    const int RT = p.rounds, lo = HOP == 1 && role >= NG ? NG : 0, hi = lo + h::NBIN;
    const int w = (role - lo) / (HOP * J), j = (role - lo - w * HOP * J) / HOP;
    const Ring rg(p.ring, __reduce_or_sync(0xffffffffu, lds32(sb + W_PAR)), 2 * w + HOP - 1);
    const uint32_t side = lds32(sb + W_SIDE), dhi = rg.main >> 32, mhi = rg.mid >> 32;
    const uint32_t c0 = HOP == 2 ? role & 1 : 0, up = (HOP == 1 && lo) ^ rg.par ^ c0;
    uint32_t dA = ((uint32_t)rg.main + src_off(j) + (c0 << 16) + (up ? 4096 : 12288)) ^ slot_off(base % 3);
    uint32_t dM = ((uint32_t)rg.mid + src_off(j) + c0 * 1024) ^ slot_off(base % 3);
    const int a0 = max(64, lo), b1 = min(68, hi);
    int n0 = (min(NHI, hi) - a0) * PB, a1 = (max(NLO, lo) - lo) * PB;
    const unsigned char* cr = reinterpret_cast<const unsigned char*>(rg.main) + MISC + ((side ^ rg.par) << 12);
    const unsigned char* cr0 = cr + cred_off(lo + lane * V), *cr1 = cr + cred_off(lo + 32 * V + min(lane, V - 1));
    const uint32_t ca0 = sb + h::CNT + lane * V * 4, ca1 = sb + h::CNT + (32 * V + min(lane, V + NDUM)) * 4;
    const uint32_t rot0 = (lane * V & 7) * 16, rot1 = lane * 16;
    uint32_t st = slot_steps(base);
    uint32_t init = h::init(base), prim = sb + h::STG + (HOP == 1 ? h::win(base) : 0u);
    uint32_t cs[5];
    auto sample = [&]() {
        if (V == 2) asm volatile("ld.relaxed.gpu.global.v2.u32 {%0,%1}, [%2];" : "=r"(cs[0]), "=r"(cs[1]) : "l"(cr0) : "memory");
        else asm volatile("ld.relaxed.gpu.global.v4.u32 {%0,%1,%2,%3}, [%4];" : "=r"(cs[0]), "=r"(cs[1]), "=r"(cs[2]), "=r"(cs[3]) : "l"(cr0) : "memory");
        cs[V] = ld_rlx32(reinterpret_cast<const uint32_t*>(cr1));
    };
    sample();
    uint32_t c[5];
    TK_DECL
#pragma unroll 1
    for (int r = 0;; r++) {
        const uint32_t R = base + r, ninit = h::init(R + 1), done = prim;
        TK(5)
        mbar_wait(sb + B_FULL + (HOP - 1) * 8, r & 1);
        TK(0)
        if (V == 2) asm volatile("ld.shared.v2.u32 {%0,%1}, [%2];" : "=r"(c[0]), "=r"(c[1]) : "r"(ca0) : "memory");
        else asm volatile("ld.shared.v4.u32 {%0,%1,%2,%3}, [%4];" : "=r"(c[0]), "=r"(c[1]), "=r"(c[2]), "=r"(c[3]) : "r"(ca0) : "memory");
        c[V] = lds32(ca1);
        uint32_t nc[5];
#pragma unroll
        for (int k = 0; k <= V; k++) {
            const uint32_t z = ninit + (k < V ? rot0 + k * 16 : rot1);
            nc[k] = min(max(c[k] + (ninit - init - h::S * h::INC), z), z + (h::CAP - h::S) * h::INC);
        }
        if (V == 2) sts64(ca0, nc[0], nc[1]); else sts128<0>(ca0, make_uint4(nc[0], nc[1], nc[2], nc[3]));
        sts32(ca1, lane < V ? nc[V] : lane < V + NDUM ? DUMMY : r);
        __syncwarp();
        if (lane == 0) mbar_arrive(sb + B_OPEN + (HOP - 1) * 8);
        TK(1)
        TK(2)
        asm volatile("fence.proxy.async.shared::cta;" ::: "memory");
        TK(6)
        if (r >= D) {
            int it = 0;
            while (true) {
                uint32_t bad = 0;
#pragma unroll
                for (int k = 0; k <= V; k++) bad |= cs[k] - (R - D + 1);
                if (!__any_sync(0xffffffffu, bad >> 20)) break;
                if (++it > SPIN_LIMIT) __trap();
                if (it > CRED_SKIP) __nanosleep(CRED_NS);
                sample();
            }
        }
        TK(3)
        if (elect()) {
            const uint32_t dB = (HOP == 1 ? dA ^ 0x10000u : dA) + (up ? 8192 : -8192), sm = prim + (lo ? 2 * PB : 0);
            bulk_store(dA, dhi, sm, 8192);
            bulk_store(dB, dhi, HOP == 1 ? sm + 8192 : prim + 68 * PB, 8192);
            if (n0 > 0) bulk_store(dM + (a0 - 64) * PB, mhi, prim + (a0 - lo) * PB, n0);
            if (a1 < (b1 - lo) * PB) bulk_store((dM ^ 4096u) + (uint32_t)((lo - NLO) * PB + a1), mhi, prim + a1, (b1 - lo) * PB - a1);
            asm volatile("cp.async.bulk.commit_group;" ::: "memory");
            asm volatile("cp.async.bulk.wait_group.read 0;" ::: "memory");
        }
        __syncwarp();
        TK(4)
        prim = HOP == 1 ? prim ^ 0x20000u : prim >= sb + 0x30000u ? sb : prim + (prim - sb) + 0x10000u;
        if (r == RT - 1) break;
        reset<HOP>(done, lane, R + HOP + 1);
        if (HOP == 1) {
            __syncwarp();
            if (lane == 0) mbar_arrive(sb + B_FREE);
        }
        if (r == D - 1 || r == RT - D - 1) {
            uint32_t n = NHI, m = NLO;
            if (r < RT - D - 1) {
                int it = 0;
                while (true) {
                    n = ld_rlx32(reinterpret_cast<const uint32_t*>(p.ring + M_CNT + (side << 12)));
                    if ((n & 0xffffu) + (n >> 16) == NB) break;
                    if (++it > SPIN_LIMIT) __trap();
                }
                m = n = min(max(__reduce_or_sync(0xffffffffu, n) & 0xffffu, (uint32_t)NLO), (uint32_t)NHI);
            }
            n0 = (min((int)n, hi) - a0) * PB;
            a1 = (max((int)m, lo) - lo) * PB;
        }
        sample();
        slot_next(dA, st); slot_next(dM, st);
        st = slot_rot(st);
        init = ninit;
    }
#pragma unroll 1
    for (int k = 0; k <= V; k++) {
        const uint32_t bin = k < V ? lane * V + k : 32 * V + lane, n = bin < h::NBIN ? min((pick(k, c) - init) >> h::SH, (uint32_t)h::CAP) : 0u;
#pragma unroll 1
        for (uint32_t x = h::S; x < n; x++) {
            const uint2 w = lds64(prim + bin * PB + ((x + (bin & 7) * 2) & (h::S - 1)) * 8);
            if (HOP == 1) slow_rec1(p, w.x, w.y, bin);
            else slow_rec2(p, w.x, w.y, bin, __uint_as_float(lds32(sb + W_UNIT)));
        }
    }
    asm volatile("cp.async.bulk.wait_group 0;" ::: "memory");
    TK_OUT
}

#define POLL_NS 200
#define POLL_NS3 1500
template <int HOP> struct Reader {
    uint32_t lo, hi, st, line;
    uint32_t* cred;
    __device__ __forceinline__ void init(const Params& p, uint32_t sb, int w, int lane, int role, uint32_t base) {
        constexpr int PB = H<HOP>::S * 8;
        const int first = HOP == 1 ? (role >= NG ? NG : 0) + w * J : w * 2 * J;
        const Ring rg(p.ring, lds32(sb + W_PAR), 2 * w + HOP - 1);
        const uint32_t side = lds32(sb + W_SIDE);
        const bool mid = side ? role < 68 : role >= 64;
        const uint32_t i = role - (side ? (mid ? NLO : 68) : (mid ? 64 : 0));
        const uint32_t c = HOP == 1 ? i >> 5 : lane >> 4, in = HOP == 1 ? (i & 31) * PB + lane * 8 : i * PB + (lane & 15) * 8;
        lo = (in + (mid ? ((uint32_t)rg.mid ^ side << 12) + c * 1024 : (uint32_t)rg.main + (c << 16) + (side ^ rg.par ^ c ? 4096 : 12288))) ^ slot_off(base % 3);
        hi = __reduce_or_sync(0xffffffffu, (uint32_t)((mid ? rg.mid : rg.main) >> 32));
        st = slot_steps(base);
        line = HOP == 1 ? 2 * (role % NG) : role;
        const bool both = first >= NLO && first < NHI;
        cred = lane < 1 + both ? reinterpret_cast<uint32_t*>(rg.main + MISC + (((both ? lane : first >= NG) ^ rg.par) << 12) + cred_off(role)) : nullptr;
    }
    template <int K> __device__ __forceinline__ void load1(uint2& v) const {
        asm volatile("ld.relaxed.gpu.global.v2.u32 {%0,%1}, [%2+%3];" : "=r"(v.x), "=r"(v.y) : "l"(mk_ptr(lo, hi)), "n"(src_off(K)) : "memory");
    }
    template <int K> __device__ __forceinline__ void again(uint2& v, uint32_t want, uint32_t mask) const {
        if (__ballot_sync(0xffffffffu, xor_and<H<HOP>::TAG>(HOP == 1 ? v.x : v.y, want)) & mask) load1<K>(v);
    }
    __device__ __forceinline__ void load(uint2 (&rec)[J]) const {
        load1<0>(rec[0]); load1<1>(rec[1]); load1<2>(rec[2]); load1<3>(rec[3]); load1<4>(rec[4]); load1<5>(rec[5]);
    }
    __device__ __forceinline__ void check(uint2 (&rec)[J], uint32_t R, uint32_t ns TK_ARG) {
        const uint32_t want = H<HOP>::tag(R);
        const uint32_t mask = 0x1111u << H<HOP>::mark(R, line) | 0x11110000u << H<HOP>::mark(R, line + 2 - HOP);
        int it = 0;
        while (true) {
            uint32_t bad = 0;
#pragma unroll
            for (int j = 0; j < J; j++) bad |= (HOP == 1 ? rec[j].x : rec[j].y) ^ want;
            if (!(__ballot_sync(0xffffffffu, bad & H<HOP>::TAG) & mask)) break;
            if (++it > SPIN_LIMIT) __trap();
            __nanosleep(ns);
            TK_CNT(7)
            again<0>(rec[0], want, mask); again<1>(rec[1], want, mask); again<2>(rec[2], want, mask);
            again<3>(rec[3], want, mask); again<4>(rec[4], want, mask); again<5>(rec[5], want, mask);
        }
        if (cred) st_rlx32(cred, R + 1);
        slot_next(lo, st);
        st = slot_rot(st);
    }
    __device__ __forceinline__ void finish() const { if (cred) st_rlx32(cred, 0u); }
};

#define NPROBE 9
__device__ __forceinline__ uint32_t near_half(unsigned char* pair, uint32_t zero) {
#pragma unroll
    for (int i = 0; i < 4; i++) *reinterpret_cast<uint4*>(pair + (i >> 1) * 4096 + (i & 1) * 16) = make_uint4(0u, 0u, 0u, 0u);
    uint32_t best[2] = {~0u, ~0u}, v = 0, prev = 0;
    asm volatile("red.relaxed.gpu.global.add.u32 [%0], 1;" ::"l"(pair + 4096) : "memory");
#pragma unroll
    for (int t = 0; t <= NPROBE; t++) {
        uint32_t now;
        asm volatile("atom.relaxed.gpu.global.add.u32 %0, [%1], 1;" : "=r"(v) : "l"(pair + (t & 1) * 4096 + (v & zero)) : "memory");
        asm volatile("mov.u32 %0, %%clock;" : "=r"(now) :: "memory");
        if (t > 1) best[(t - 1) & 1] = min(best[(t - 1) & 1], now - prev);
        prev = now;
    }
    return (best[1] < best[0] ? 1u : 0u) | (v & zero);
}
template <bool B> struct BoolC { static constexpr bool value = B; };

template <int NP>
__device__ __forceinline__ void stage1(const Params& p, uint32_t sb, const int pos0, int lane, uint32_t base) {
    typedef H<1> h;
    const int RT = p.rounds;
    uint32_t ff = *reinterpret_cast<const uint16_t*>(p.ang_freq) * 0x10001u;
    auto pair_of = [&](int r, int pos) {
        const int q = r < RT - 1 ? (r * NB + blockIdx.x) * NPR + pos : (RT - 1) * NB * NPR + blockIdx.x * p.lastn + pos;
        return (r < RT - 1 || (r == RT - 1 && pos < p.lastn)) && q < p.T2 ? q : -1;
    };
    uint2 vi[NP], vo[NP]; uint32_t va[NP];
    auto load_edge = [&](int r) {
#pragma unroll
        for (int u = 0; u < NP; u++) {
            const int q = max(pair_of(r, pos0 + u * 32), 0);
            vi[u] = ld_in(p.idx_in + q); vo[u] = ld_in(p.idx_out + q); va[u] = ld_in(p.angle + q);
        }
    };
    load_edge(0);
    if (blockIdx.x == 0 && pos0 == 0 && (p.T & 1)) {
        const int t = p.T - 1;
        slow_triplet(p, reinterpret_cast<const uint32_t*>(p.idx_in)[t], reinterpret_cast<const uint32_t*>(p.idx_out)[t],
                     bf16r(cos_bf(hmul_bf2(reinterpret_cast<const uint16_t*>(p.angle)[t], ff) & 0xffffu)));
    }
    for (int i = threadIdx.x * 16; i < p.R2 && blockIdx.x * p.R2 + i < p.E; i += NS1 * 32 * 16) prefetch_l2(p.m + blockIdx.x * p.R2 + i);
    uint32_t R = __reduce_or_sync(0xffffffffu, base);
    ff = __reduce_or_sync(0xffffffffu, ff);
    bar_sync(BAR_S1, (NS1 + 1) * 32);
    TK_DECL
    auto step = [&](const int r, const int qn, auto edge) {
        constexpr bool EDGE = decltype(edge)::value;
        uint32_t cc[NP], big = 0;
#pragma unroll
        for (int u = 0; u < NP; u++) {
            va[u] = hmul_bf2(va[u], ff);
            cc[u] = pack_bf2(__cosf(bf_lo(va[u])), __cosf(bf_hi(va[u])));
            big = __vmaxu2(big, va[u] & 0x7fff7fffu);
        }
        if ((big + (0x7fffu - BIGX) * 0x10001u) & 0x80008000u) {
#pragma unroll 1
            for (int u = 0; u < NP; u++) {
                const uint32_t a = pick(u, va);
                float c0 = cos_bf(a & 0xffffu), c1 = cos_bf(a >> 16);
                if ((c0 != c0 || c1 != c1) && (!EDGE || pair_of(r, pos0 + u * 32) >= 0)) {
                    const uint2 i2 = pick(u, vi), o2 = pick(u, vo);
                    if (c0 != c0) slow_triplet(p, i2.x, o2.x, c0);
                    if (c1 != c1) slow_triplet(p, i2.y, o2.y, c1);
                }
                const uint32_t v = pack_bf2(c0 != c0 ? 0.f : c0, c1 != c1 ? 0.f : c1);
#pragma unroll
                for (int k = 0; k < NP; k++) if (k == u) cc[k] = v;
            }
        }
        uint32_t bin[2 * NP], x[2 * NP], y[2 * NP];
#pragma unroll
        for (int j = 0; j < 2 * NP; j++) {
            const uint32_t ii = j & 1 ? vi[j >> 1].y : vi[j >> 1].x, oo = j & 1 ? vo[j >> 1].y : vo[j >> 1].x;
            bin[j] = __umulhi(ii, p.mg1);
            y[j] = __byte_perm(bin[j] * p.k1 + ii, cc[j >> 1], j & 1 ? 0x7610 : 0x5410);
            const uint32_t bo = __umulhi(oo, p.mg2);
            x[j] = __byte_perm(bo * p.k2 + oo * 8u, bo, 0x0514);
            if (EDGE && pair_of(r, pos0 + (j >> 1) * 32) < 0) bin[j] = NG + (lane & (NDUM - 1));
        }
        if (EDGE) load_edge(r + 1);
        else {
            uint32_t dep = 0;
#pragma unroll
            for (int j = 0; j < 2 * NP; j++) dep |= x[j] | y[j];
            const int q = qn + (dep & p.zero);
#pragma unroll
            for (int u = 0; u < NP; u++) { vi[u] = ld_in(p.idx_in + q + u * 32); vo[u] = ld_in(p.idx_out + q + u * 32); va[u] = ld_in(p.angle + q + u * 32); }
        }
        const uint32_t init = h::init(R), kb = sb + h::win(R + 1), lim = init + (h::CAP << h::SH);
        TK(0)
        mbar_wait(sb + B_OPEN, ~R & 1);
        TK(1)
        bool freed = false;
        uint32_t over = 0;
#pragma unroll
        for (int g = 0; g < 2 * NP; g += 4) {
            uint32_t ret[4];
#pragma unroll
            for (int j = 0; j < 4; j++) ret[j] = atoms_add<h::CNT>(sb + bin[g + j] * 4, h::INC);
            const int mx = max(max((int)ret[0], (int)ret[1]), max((int)ret[2], (int)ret[3]));
            if (!freed && __any_sync(0xffffffffu, mx >= (int)(init + 0x10000u))) { TK(2) mbar_wait(sb + B_FREE, ~R & 1); freed = true; TK(3) }
            TK(2)
#pragma unroll
            for (int j = 0; j < 4; j++) {
                x[g + j] = and_or<h::TAG>(ret[j], x[g + j]);
                put_rec<h::STG>(ret[j], lim, and_xor(ret[j], 0x20000u | h::PM, bin[g + j] * 256 + kb), x[g + j], y[g + j]);
            }
            if (mx >= (int)lim) {
#pragma unroll
                for (int j = 0; j < 4; j++) if ((int)ret[j] >= (int)lim) over |= 1u << (g + j);
            }
        }
        __syncwarp();
        if (elect()) mbar_arrive(sb + B_FULL);
        R++;
        TK(4)
#pragma unroll 1
        while (over) {
            TK_CNT(7)
            const int j = __ffs(over) - 1;
            over &= over - 1;
            slow_rec1(p, pick(j, x), pick(j, y), pick(j, bin));
        }
        __syncwarp();
    };
#pragma unroll 1
    for (int q = (NB + blockIdx.x) * NPR; q < p.qfull; q += NB * NPR) step(q / (NB * NPR) - 1, q + pos0, BoolC<false>());
#pragma unroll 1
    for (int r = max(p.qfull / (NB * NPR) - 1, 0); r < RT; r++) step(r, 0, BoolC<true>());
    TK_OUT
}

__device__ __forceinline__ void stage2(const Params& p, uint32_t sb, int w, int lane, int role, uint32_t base) {
    typedef H<2> h;
    const int RT = p.rounds;
    Reader<1> rd;
    rd.init(p, sb, w, lane, role, base);
    uint2 rec[J];
    rd.load(rec);
    bar_sync(BAR_TABLE, 2 * NC * 32);
    uint32_t kb = sb + 0x10000u, am = 0x10000u | h::PM;
    TK_DECL
#pragma unroll 1
    for (int r = 0; r < RT; r++) {
        rd.check(rec, base + r, POLL_NS TK_PASS);
        const uint32_t want = H<1>::tag(base + r);
        TK(0)
        uint2 mv[J];
#pragma unroll
        for (int j = 0; j < J; j++) mv[j] = lds64<OFF_M>(sb + (rec[j].y & 0xffffu) * 8);
        uint32_t fl = 0;
#pragma unroll
        for (int j = 0; j < J; j++) fl |= mv[j].y;
        if (fl & 0x40000000u) {
#pragma unroll 1
            for (int j = 0; j < J; j++) {
                const uint2 v = pick(j, mv), w = pick(j, rec);
                if ((v.y & 0x40000000u) && !((w.x ^ want) & 0xf00000u)) {
                    if (v.x & 0x40000000u) slow_rec1(p, w.x, w.y, lds32(sb + W_ROLE) % NG);
                    else {
                        const float c = bf_hi(w.y), s = __uint_as_float(lds32(sb + W_UNIT)) * 1024.f;
                        side_add(w.x & 0xffu, __byte_perm(w.x, 0u, 0x4413) >> 3, c * (bf_lo(v.x) * s), c * (bf_hi(v.x) * s),
                                 c * (bf_lo(v.y) * s), c * (bf_hi(v.y & 0xbfffffffu) * s));
                    }
                }
            }
#pragma unroll
            for (int j = 0; j < J; j++) if (mv[j].y & 0x40000000u) rec[j].x = 0x800000u;
        }
        uint32_t w0[J], w1[J], bin[J], ret[J];
#pragma unroll
        for (int j = 0; j < J; j++) {
            const float c = bf_hi(rec[j].y), MG = 8194.0f;
            const uint32_t x = rec[j].x;
            w0[j] = and_or<0xf000f000u>(x, __byte_perm(__float_as_uint(fmaf(c, bf_lo(mv[j].x), MG)), __float_as_uint(fmaf(c, bf_hi(mv[j].x), MG)), 0x5410));
            w1[j] = and_or<0xf000f000u>(x << 4, __byte_perm(__float_as_uint(fmaf(c, bf_lo(mv[j].y), MG)), __float_as_uint(fmaf(c, bf_hi(mv[j].y), MG)), 0x5410));
            bin[j] = min(xor_and<0xf000ffu>(x, want), NB + (lane & (NDUM - 1)));
        }
        const uint32_t lim = h::init(base + r) + 0x20000u;
        rd.load(rec);
        TK(1)
        mbar_wait(sb + B_OPEN + 8, (r - 1) & 1);
        TK(2)
#pragma unroll
        for (int j = 0; j < J; j++) ret[j] = atoms_add<h::CNT>(sb + bin[j] * 4, h::INC);
        uint32_t mx = 0;
#pragma unroll
        for (int j = 0; j < J; j++) {
            w1[j] = and_or<h::TAG>(ret[j], w1[j]);
            put_rec<0>(ret[j], lim, and_xor(ret[j], am, bin[j] * 128 + kb), w0[j], w1[j]);
            mx = __viaddmax_u32(ret[j], 0u - DUMMY, mx);
        }
        __syncwarp();
        if (lane == 0) mbar_arrive(sb + B_FULL + 8);
        TK(3)
        if (mx >= lim - DUMMY) {
#pragma unroll 1
            for (int j = 0; j < J; j++)
                if (pick(j, ret) - DUMMY >= lim - DUMMY) slow_rec2(p, pick(j, w0), pick(j, w1), pick(j, bin), __uint_as_float(lds32(sb + W_UNIT)));
        }
        __syncwarp();
        am = am >= 0x30000u ? 0x10000u | h::PM : am + 0x10000u;
        kb ^= am & 0x30000u;
        TK(4)
    }
    rd.finish();
    TK_OUT
}

__device__ __forceinline__ float2 acc_fix(uint32_t old, uint32_t q) {
    const uint32_t u = old + 0x40004000u, n = u + q - 0x08000800u;
    return make_float2((float)((int)(u & 0xffffu) + (int)(q & 0xffffu) - 2048 - (int)(n & 0xffffu)), (float)((int)(u >> 16) + (int)(q >> 16) - 2048 - (int)(n >> 16)));
}
__device__ __forceinline__ void stage3(const Params& p, uint32_t sb, int w, int lane, int role, uint32_t base) {
    const int RT = p.rounds;
    Reader<2> rd;
    rd.init(p, sb, w, lane, role, base);
    uint2 rec[J];
    bar_sync(BAR_TABLE, 2 * NC * 32);
    TK_DECL
#pragma unroll 1
    for (int r = 0; r < RT; r++) {
        if (LAG) { const int need = min(r + 1, RT - 1); if ((int)lds32(sb + W_RND) < need) mbar_wait(sb + B_OPEN + 8, need & 1); }
        rd.load(rec);
        rd.check(rec, base + r, r < RT - 2 ? POLL_NS3 : 100 TK_PASS);
        TK(0)
        const uint32_t want = H<2>::tag(base + r), t = 0u - (lane & 1u), k = (t & 1u << 26) - (want >> 4);
        uint32_t o0[J], o1[J], g = 0;
#pragma unroll
        for (int j = 0; j < J; j++) {
            o0[j] = 0; o1[j] = 0;
            if (!xor_and<H<2>::TAG>(rec[j].y, want)) {
                const uint32_t a = aux_of(rec[j].x, rec[j].y, k);
                const uint32_t v0 = (rec[j].x & 0x0fff0fffu) - 0x08000800u, v1 = (rec[j].y & 0x0fff0fffu) - 0x08000800u;
                o0[j] = atoms_add<OFF_ACC>(sb + a, mux(v0, v1, t));
                o1[j] = atoms_add<OFF_ACC>(sb + (a ^ 4u), mux(v1, v0, t));
            }
        }
#pragma unroll
        for (int j = 0; j < J; j++) g |= o0[j] | o1[j];
        if (__any_sync(0xffffffffu, g & 0x80008000u)) {
#pragma unroll 1
            for (int j = 0; j < J; j++) {
                const uint2 w = pick(j, rec);
                const uint32_t aux = aux_of(w.x, w.y), p0 = pick(j, o0), p1 = pick(j, o1);
                const float2 a = acc_fix(t ? p1 : p0, w.x & 0x0fff0fffu), b = acc_fix(t ? p0 : p1, w.y & 0x0fff0fffu);
                const float unit = __uint_as_float(lds32(sb + W_UNIT));
                if (!((w.y ^ want) & H<2>::TAG) && (a.x != 0.f || a.y != 0.f || b.x != 0.f || b.y != 0.f))
                    side_add(lds32(sb + W_ROLE), aux >> 3, a.x * unit, a.y * unit, b.x * unit, b.y * unit);
                __syncwarp();
            }
        }
        TK(1)
    }
    rd.finish();
    TK_OUT
}

__device__ __forceinline__ uint32_t row_max(uint32_t x, uint32_t y) {
    const uint32_t mx = __vmaxu2(x & 0x7fff7fffu, y & 0x7fff7fffu);
    return max(mx & 0xffffu, mx >> 16);
}
constexpr int EWIN = 5;

__global__ void __launch_bounds__(NTHR, 1) fused_kernel(const Params p) {
    const int tid = threadIdx.x, lane = tid & 31;
    const int hw = __reduce_max_sync(0xffffffffu, tid >> 5);
    const uint32_t sb = __reduce_or_sync(0xffffffffu, (uint32_t)__cvta_generic_to_shared(smem));
    TKX(0)
    const uint32_t epoch = ld_rlx32(&g_base);
    uint32_t base = epoch & 31u;

    if (hw < NS1) {
        if (hw < NS1 - 1) stage1<4>(p, sb, hw * 128 + lane, lane, base);
        else stage1<NPR / 32 - (NS1 - 1) * 4>(p, sb, hw * 128 + lane, lane, base);
        __threadfence();
        bar_arrive(BAR_DONE, (NS1 + NC + 2) * 32);
    } else if (hw == W_M1) {
        if (lane == 0) {
            if (sb & 255u) __trap();
            mbar_init(sb + B_FULL, NS1); mbar_init(sb + B_OPEN, 1); mbar_init(sb + B_FREE, 1);
        }
        base = __reduce_or_sync(0xffffffffu, base);
        if (lane == 0 && (base & 1u)) { mbar_arrive(sb + B_OPEN); mbar_arrive(sb + B_FREE); }
        for (int i = lane; i < NG + NDUM; i += 32) sts32(sb + OFF_CNT1 + i * 4, i < NG ? H<1>::init(base) + (i & 7) * 16 : DUMMY);
#pragma unroll 1
        for (int i = 0; i < 2; i++) fill<1>(sb + OFF_H1 + H<1>::win(base + i), lane, base + i);
        bar_arrive(BAR_S1, (NS1 + 1) * 32);
        bar_sync(BAR_PROBE, (2 * NC + 1) * 32);
        {
            const uint32_t raw = __ballot_sync(0xffffffffu, lane < 2 * NC && smem[OFF_PROBE + lane]), side = raw & 1u;
            uint32_t v = 0;
            if (lane < 2) asm volatile("atom.relaxed.gpu.global.add.u32 %0, [%1], %2;" : "=r"(v) : "l"(p.ring + M_CNT + lane * 4096), "r"(side ? 0x10000u : 1u) : "memory");
            const uint32_t mine = (side ? ~raw : raw) | 0x80000000u;
            if (lane == 2) asm volatile("atom.relaxed.gpu.global.cas.b32 %0, [%1], 0, %2;" : "=r"(v) : "l"(p.ring + M_PAR), "r"(mine) : "memory");
            bar_sync(BAR_HIST, (2 * NC + 1) * 32);
            uint32_t best = 0;
#pragma unroll 1
            for (int e = 11 + lane; e <= 230; e += 32) {
                uint32_t c = 0;
#pragma unroll
                for (int i = 0; i < EWIN; i++) c += lds32(sb + OFF_HIST + (e - i) * 4);
                best = max(best, c << 8 | (255 - e));
            }
            const uint32_t e = 255 - (__reduce_max_sync(0xffffffffu, best) & 255u);
            if (lane == 0) {
                const uint32_t role = side ? NB - 1 - (v >> 16) : v & 0xffffu;
                sts32(sb + W_ROLE, role); sts32(sb + W_SIDE, role < NLO ? 0u : role >= NHI ? 1u : side);
                sts32(sb + W_EXP, e); sts32(sb + W_UNIT, (e - 10) << 23); sts32(sb + W_END, (epoch | 31u) + 1u + (base + p.rounds) % 24u);
            }
            if (lane == 2) sts32(sb + W_PAR, v ? v : mine);
        }
        bar_sync(BAR_ROLE, (2 * NC + 2) * 32);
        manager<1>(p, sb, lane, __reduce_max_sync(0xffffffffu, lds32(sb + W_ROLE)), base);
        bar_arrive(BAR_H1, (NS1 + 1) * 32);
        __threadfence();
        bar_arrive(BAR_DONE, (NS1 + NC + 2) * 32);
    } else if (hw == W_M2) {
        const float wd = __bfloat162float(lane & 16 ? p.w_up[lane & 15] : p.w_down[lane & 15]);
        const float ws = __bfloat162float(p.w_sbf[lane]), wr = __bfloat162float(p.w_rbf[lane]);
        const __nv_bfloat16 cen = p.centers[lane & 7];
        if (lane == 0) { mbar_init(sb + B_FULL + 8, NC); mbar_init(sb + B_OPEN + 8, 1); }
        base = __reduce_or_sync(0xffffffffu, base);
        for (int i = lane; i <= NB + NDUM; i += 32) sts32(sb + OFF_CNT2 + i * 4, i < NB ? H<2>::init(base) + (i & 7) * 16 : DUMMY);
#pragma unroll 1
        for (int i = 0; i < 3; i++) fill<2>(sb + H<2>::win(i), lane, base + i);
        reinterpret_cast<float*>(smem + OFF_WSM)[lane] = wd;
        reinterpret_cast<float*>(smem + OFF_WG)[lane] = ws;
        reinterpret_cast<float*>(smem + OFF_WG + 128)[lane] = wr;
        reinterpret_cast<__nv_bfloat16*>(smem + OFF_WG + 256)[lane & 7] = cen;
        bar_sync(BAR_ROLE, (2 * NC + 2) * 32);
        manager<2>(p, sb, lane, __reduce_max_sync(0xffffffffu, lds32(sb + W_ROLE)), base);
        __threadfence();
        bar_sync(BAR_DONE, (NS1 + NC + 2) * 32);
        if (lane < 2) { __threadfence(); st_rlx32(reinterpret_cast<uint32_t*>(p.ring + M_FLAG + lane * 4096) + blockIdx.x, lds32(sb + W_END)); }
    } else {
        const int pw = __reduce_max_sync(0xffffffffu, hw < W_M1 ? hw - NS1 : hw - NS1 - 1), ct = pw * 32 + lane;
        constexpr int CT = 2 * NC * 32;
        const uint4 sm = __ldg(reinterpret_cast<const uint4*>(p.m) + min((ct >> 3) * (p.E >> 1) / (CT / 8) + (lane & 7), (p.E >> 1) - 1));
        if (ct < 256) sts32(sb + OFF_HIST + ct * 4, 0u);
        if (lane == 0) smem[OFF_PROBE + pw] = pw < NPAGE ? near_half(p.ring + (size_t)pw * PAGE + PROBE + (blockIdx.x & 31) * 128 + (blockIdx.x >> 5 & 3) * 16384 + (blockIdx.x >> 7 << 20), p.zero) : 0;
        TKX(1)
        bar_sync(BAR_PROBE, (2 * NC + 1) * 32);
        {
            const uint32_t m0 = row_max(sm.x, sm.y), m1 = row_max(sm.z, sm.w);
            if (m0) atoms_add<OFF_HIST>(sb + (m0 >> 7) * 4, 1u);
            if (m1) atoms_add<OFF_HIST>(sb + (m1 >> 7) * 4, 1u);
        }
        bar_arrive(BAR_HIST, (2 * NC + 1) * 32);
        base = __reduce_or_sync(0xffffffffu, base);
        for (int i = ct; i < R2MAX / 2; i += CT) reinterpret_cast<uint4*>(smem + OFF_ACC)[i] = make_uint4(0x40004000u, 0x40004000u, 0x40004000u, 0x40004000u);
        bar_sync(BAR_ROLE, (2 * NC + 2) * 32);
        const int role = __reduce_max_sync(0xffffffffu, lds32(sb + W_ROLE));
        TKX(2)
        {
            const int e = lds32(sb + W_EXP), q0 = (role >= NG ? role - NG : role) * (p.R1 >> 1), nq = min(p.R1 >> 1, (p.E >> 1) - q0);
            const uint32_t sc = (uint32_t)(254 - e) * 0x800080u;
            constexpr int CH = (R1MAX / 2 + CT - 1) / CT;
            uint4 v[CH];
#pragma unroll
            for (int u = 0; u < CH; u++) v[u] = __ldg(reinterpret_cast<const uint4*>(p.m) + min(q0 + ct + u * CT, (p.E >> 1) - 1));
            auto conv = [&](uint32_t& x, uint32_t& y) {
                const uint32_t mx = row_max(x, y);
                const int d = e - (int)(mx >> 7);
                x = hmul_bf2(x, sc); y = hmul_bf2(y, sc);
                if (d >= EWIN) y |= 0x40000000u;
                if (d < 0 || (d >= EWIN && e > 127)) { x = 0x40000000u; y = x; }
                if (mx == 0) { x = 0; y = 0; }
            };
#pragma unroll
            for (int u = 0; u < CH; u++) {
                conv(v[u].x, v[u].y); conv(v[u].z, v[u].w);
                if (ct + u * CT < nq) sts128<OFF_M>(sb + (ct + u * CT) * 16, v[u]);
            }
        }
        TKX(3)
        if (hw < W_M1) {
            stage2(p, sb, pw, lane, role, base);
            __threadfence();
            bar_arrive(BAR_DONE, (NS1 + NC + 2) * 32);
        } else {
            stage3(p, sb, pw - NC, lane, role, base);
            __threadfence();
        }
    }
    TKX(4)
    epilogue(p, sb);
}

__global__ void fb_scatter(const uint2* __restrict__ m, const int* __restrict__ idx_in, const int* __restrict__ idx_out,
                           const uint16_t* __restrict__ angle, const __nv_bfloat16* __restrict__ ang_freq, int T, int e0, int e1) {
    const uint32_t fb = *reinterpret_cast<const uint16_t*>(ang_freq);
    for (long long t = blockIdx.x * (long long)blockDim.x + threadIdx.x; t < T; t += (long long)gridDim.x * blockDim.x) {
        int o = idx_out[t];
        if (o < e0 || o >= e1) continue;
        float c = bf16r(cos_bf(hmul_bf2(angle[t], fb) & 0xffffu));
        uint2 v = __ldg(m + idx_in[t]);
        red4(&g_ovf[o - e0], c * bf_lo(v.x), c * bf_hi(v.x), c * bf_lo(v.y), c * bf_hi(v.y));
    }
}
__global__ void fb_final(const Params p, int e0, int e1) {
    int e = e0 + blockIdx.x * blockDim.x + threadIdx.x;
    if (e >= e1) return;
    float4 a4 = g_ovf[e - e0];
    g_ovf[e - e0] = make_float4(0.f, 0.f, 0.f, 0.f);
    float a[4] = {a4.x, a4.y, a4.z, a4.w};
    float d = __bfloat162float(p.dist[e]);
    float g[4] = {0, 0, 0, 0}, h[4] = {0, 0, 0, 0};
    for (int r = 0; r < 8; r++) {
        float df = bf16r(d - __bfloat162float(p.centers[r]));
        float rb = bf16r(expf(bf16r(-10.0f * bf16r(df * df))));
        for (int k = 0; k < 4; k++) {
            g[k] += rb * __bfloat162float(p.w_sbf[r * 4 + k]);
            h[k] += rb * __bfloat162float(p.w_rbf[r * 4 + k]);
        }
    }
    float ag[4];
    for (int k = 0; k < 4; k++) {
        float s = 0.f;
        for (int j = 0; j < 4; j++) s += a[j] * __bfloat162float(p.w_down[j * 4 + k]);
        ag[k] = bf16r(s * g[k]);
    }
    uint2 mv = p.m[e];
    float mm[4] = {bf_lo(mv.x), bf_hi(mv.x), bf_lo(mv.y), bf_hi(mv.y)};
    __nv_bfloat16 o[4];
    for (int k = 0; k < 4; k++) {
        float u = 0.f;
        for (int j = 0; j < 4; j++) u += ag[j] * __bfloat162float(p.w_up[j * 4 + k]);
        o[k] = __float2bfloat16_rn(mm[k] + bf16r(bf16r(u) * bf16r(h[k])));
    }
    p.out[e] = *reinterpret_cast<uint2*>(o);
}

}

static bool exact_div(int E, int lo, int hi, int* R, uint32_t* magic) {
    for (int r = lo + (lo & 1); r <= hi; r += 2) {
        unsigned long long mg = ((1ull << 32) + r - 1) / r, err = mg * r - (1ull << 32);
        if (err * (unsigned long long)E < (1ull << 32)) { *R = r; *magic = (uint32_t)mg; return true; }
    }
    return false;
}

extern "C" void kernel_launch(void* const* d_in, const int* in_sizes, int n_in, void* d_out, int out_size) {
    typedef const __nv_bfloat16* B;
    Params p;
    p.m = (const uint2*)d_in[0]; p.idx_in = (const uint2*)d_in[1]; p.idx_out = (const uint2*)d_in[2]; p.dist = (B)d_in[3];
    p.angle = (const uint32_t*)d_in[4]; p.centers = (B)d_in[5]; p.ang_freq = (B)d_in[6]; p.w_rbf = (B)d_in[7]; p.w_sbf = (B)d_in[8];
    p.w_down = (B)d_in[9]; p.w_up = (B)d_in[10]; p.out = (uint2*)d_out;
    p.E = in_sizes[3]; p.T = in_sizes[1]; p.T2 = p.T >> 1; p.zero = 0;
    p.R1 = p.R2 = p.rounds = p.lastn = p.qfull = 0; p.mg1 = p.mg2 = p.k1 = p.k2 = 0;
    static int ok = -1;
    static unsigned char* ring = nullptr;
    if (ok < 0) {
        void* ra = nullptr;
        cudaGetSymbolAddress(&ra, g_ring);
        ring = reinterpret_cast<unsigned char*>(((uintptr_t)ra + PAGE - 1) & ~(uintptr_t)(PAGE - 1));
        int dev = 0, sms = 0, occ = 0;
        cudaGetDevice(&dev);
        cudaDeviceGetAttribute(&sms, cudaDevAttrMultiProcessorCount, dev);
        cudaError_t e = cudaFuncSetAttribute(fused_kernel, cudaFuncAttributeMaxDynamicSharedMemorySize, SMEM_BYTES);
        if (e == cudaSuccess) e = cudaOccupancyMaxActiveBlocksPerMultiprocessor(&occ, fused_kernel, NTHR, SMEM_BYTES);
        ok = (e == cudaSuccess && occ >= 1 && sms >= NB) ? 1 : 0;
        (void)cudaGetLastError();
    }
    p.ring = ring;
    const bool fused = ok == 1 && p.E <= EMAX && p.E >= 2 * NB && p.E % 2 == 0 && p.T >= 2 && exact_div(p.E, (p.E + NG - 1) / NG, R1MAX, &p.R1, &p.mg1) &&
                       exact_div(p.E, (p.E + NB - 1) / NB, R2MAX, &p.R2, &p.mg2);
    if (fused) {
        p.k1 = 0u - (uint32_t)p.R1; p.k2 = 0u - 8u * (uint32_t)p.R2;
        const int per = NB * NPR;
        int full = p.T2 / per, rest = p.T2 - full * per;
        p.qfull = full * per;
        p.lastn = (rest + NB - 1) / NB;
        if (p.lastn > NPR / 2) { full++; p.lastn = 0; }
        if (full < D) { full = D; p.lastn = 0; }
        p.rounds = full + 1;
        fused_kernel<<<NB, NTHR, SMEM_BYTES>>>(p);
    } else {
        for (int e0 = 0; e0 < p.E; e0 += EMAX) {
            int e1 = p.E - e0 < EMAX ? p.E : e0 + EMAX;
            fb_scatter<<<1056, 256>>>(p.m, (const int*)d_in[1], (const int*)d_in[2], (const uint16_t*)d_in[4], p.ang_freq, p.T, e0, e1);
            fb_final<<<(e1 - e0 + 255) / 256, 256>>>(p, e0, e1);
        }
    }
}
```

```cpp
#include <cuda_runtime.h>
#include <cuda_bf16.h>
#include <stdint.h>

namespace {

constexpr int NB = 132, NG = 66;
constexpr int R2MAX = 6062, R1MAX = 12124;
constexpr int EMAX = NB * R2MAX;
constexpr int NTHR = 1024;
constexpr int NS1 = 8, NC = 11, J = 6;
#define TILES 30
#define CAP1 64
constexpr int NPR = TILES * 32;
constexpr int D = 3;
constexpr int WIN = 16896;
constexpr int NDUM = 16;
constexpr uint32_t DUMMY = 0xc0000000u;

constexpr int OFF_ACC = WIN, OFF_BAR = OFF_ACC + R2MAX * 8;
constexpr int OFF_H1 = 0x10000 + WIN, OFF_M = OFF_H1 + WIN, OFF_WSM = OFF_M + R1MAX * 8;
constexpr int OFF_CNT1 = OFF_H1 + 0x20000 + WIN, OFF_CNT2 = OFF_CNT1 + (NG + NDUM + 2) * 4, W_RND = OFF_CNT2 + (NB + NDUM) * 4, OFF_WG = W_RND + 16;
constexpr int OFF_HIST = OFF_M;
constexpr int OFF_PROBE = OFF_WSM + 128;
constexpr int SMEM_BYTES = OFF_WG + 272;
static_assert(SMEM_BYTES <= 232448 && OFF_BAR + 64 <= 0x10000 && OFF_PROBE + 32 <= 0x30000, "smem");
static_assert(OFF_BAR % 8 == 0 && OFF_WG % 16 == 0 && OFF_WSM % 16 == 0 && OFF_CNT2 % 16 == 0, "align");
static_assert(NC * J == NG && NC * 32 * 6 * 16 == 2 * WIN, "shape");

template <int HOP> struct H {
    static constexpr int S = HOP == 1 ? 32 : 16, NBIN = HOP == 1 ? NG : NB, CAP = HOP == 1 ? CAP1 : 32, SH = HOP == 1 ? 11 : 12;
    static constexpr int TB = HOP == 1 ? 20 : 28, CNT = HOP == 1 ? OFF_CNT1 : OFF_CNT2, STG = HOP == 1 ? OFF_H1 : 0;
    static constexpr uint32_t INC = (1u << SH) + 8u, PM = (S - 1) * 8, TAG = 7u << TB;
    static __device__ __forceinline__ uint32_t tag(uint32_t R) { return R << TB & TAG; }
    static __device__ __forceinline__ uint32_t init(uint32_t R) { return tag(R) | ((1u << TB) - 0x10000u); }
    static __device__ __forceinline__ uint32_t mark(uint32_t R, uint32_t line) { return ((HOP == 1 ? R >> 1 : R) + line) & 3u; }
    static __device__ __forceinline__ uint32_t win(int r) { return HOP == 1 ? (r & 1) << 17 : (0x310u >> (r % 3 * 4) & 3u) << 16; }
};

constexpr uint32_t PAGE = 1u << 21;
constexpr int NPAGE = NC + 2;
__device__ __align__(256) unsigned char g_ring[(size_t)(NPAGE + 1) * PAGE];
constexpr int MISC = 0xa0000;
constexpr int M_CNT = MISC + 1024, M_PAR = MISC + 1088;
constexpr int M_FLAG = MISC + 2048;
constexpr int PROBE = MISC + 0x40000;
#define CSTR 16384
__device__ __forceinline__ uint32_t cred_off(uint32_t role) { return role * 4 + min(role >> 5, 3u) * (CSTR - 128); }
struct Ring {
    uint64_t main, mid;
    uint32_t par;
    __device__ __forceinline__ Ring(const unsigned char* ring, uint32_t pars, int k) {
        main = reinterpret_cast<uint64_t>(ring) + ((uint64_t)k << 20);
        par = pars >> (k >> 1) & 1u;
        mid = reinterpret_cast<uint64_t>(ring) + (uint64_t)NC * PAGE + (((k >> 3 << 20) + (k >> 2 & 1) * 0x11000u + (k & 1) * 2048) ^ (k >> 1 & 1) * 0x3000u ^ (pars >> (NC + (k >> 4)) & 1u) << 12);
    }
};
constexpr int NLO = 60, NHI = 72;
__host__ __device__ constexpr uint32_t src_off(int j) { return (j % 3) << 14 | (j / 3) << 18; }
__device__ __forceinline__ uint32_t slot_off(uint32_t s) { return (0xa930u >> s * 4 & 15u) << 16; }
__device__ __forceinline__ uint32_t slot_steps(uint32_t R) { return (uint32_t)(0x30a09030aull >> (2 - R % 3) * 8) & 0xffffffu; }
__device__ __forceinline__ void slot_next(uint32_t& a, uint32_t st) { a ^= st & 0xf0000u; }
__device__ __forceinline__ uint32_t slot_rot(uint32_t st) { return __byte_perm(st, 0u, 0x4102); }
constexpr int RPAD = 6064, DROW = 6144;
__device__ __align__(128) uint8_t g_dirty[NB * DROW];
__device__ uint32_t g_base = 1;
__device__ __align__(128) float4 g_ovf[NB * RPAD];

struct Params {
    const uint2* m; const uint2* idx_in; const uint2* idx_out; const __nv_bfloat16* dist; const uint32_t* angle;
    const __nv_bfloat16* centers; const __nv_bfloat16* ang_freq; const __nv_bfloat16* w_rbf; const __nv_bfloat16* w_sbf;
    const __nv_bfloat16* w_down; const __nv_bfloat16* w_up; uint2* out; unsigned char* ring;
    int E, T, T2, R1, R2, rounds, lastn, qfull; uint32_t mg1, mg2, k1, k2, zero;
};

__device__ __forceinline__ float bf16r(float x) { return __bfloat162float(__float2bfloat16_rn(x)); }
__device__ __forceinline__ float bf_lo(uint32_t v) { return __uint_as_float(v << 16); }
__device__ __forceinline__ float bf_hi(uint32_t v) { return __uint_as_float(v & 0xffff0000u); }
__device__ __forceinline__ void red4(float4* a, float x, float y, float z, float w) {
    asm volatile("red.global.add.v4.f32 [%0], {%1,%2,%3,%4};" ::"l"(a), "f"(x), "f"(y), "f"(z), "f"(w) : "memory");
}
__device__ __forceinline__ void bar_sync(int id, int n) { __syncwarp(); asm volatile("bar.sync %0, %1;" ::"r"(id), "r"(n) : "memory"); }
__device__ __forceinline__ void bar_arrive(int id, int n) { __syncwarp(); asm volatile("bar.arrive %0, %1;" ::"r"(id), "r"(n) : "memory"); }
template <int OFF> __device__ __forceinline__ uint32_t atoms_add(uint32_t addr, uint32_t v) {
    uint32_t r; asm volatile("atom.shared.add.u32 %0, [%1+%3], %2;" : "=r"(r) : "r"(addr), "r"(v), "n"(OFF) : "memory"); return r;
}
__device__ __forceinline__ void sts64(uint32_t addr, uint32_t x, uint32_t y) {
    asm volatile("st.shared.v2.u32 [%0], {%1,%2};" ::"r"(addr), "r"(x), "r"(y) : "memory");
}
__device__ __forceinline__ void sts32(uint32_t addr, uint32_t x) { asm volatile("st.shared.u32 [%0], %1;" ::"r"(addr), "r"(x) : "memory"); }
template <int OFF = 0> __device__ __forceinline__ uint2 lds64(uint32_t addr) {
    uint2 v; asm volatile("ld.shared.v2.u32 {%0,%1}, [%2+%3];" : "=r"(v.x), "=r"(v.y) : "r"(addr), "n"(OFF) : "memory"); return v;
}
__device__ __forceinline__ uint32_t lds32(uint32_t addr) {
    uint32_t v; asm volatile("ld.shared.u32 %0, [%1];" : "=r"(v) : "r"(addr) : "memory"); return v;
}
__device__ __forceinline__ uint32_t ld_rlx32(const uint32_t* p) {
    uint32_t v; asm volatile("ld.relaxed.gpu.global.u32 %0, [%1];" : "=r"(v) : "l"(p) : "memory"); return v;
}
__device__ __forceinline__ uint2 ld_rlx64(const void* p) {
    uint2 v; asm volatile("ld.relaxed.gpu.global.v2.u32 {%0,%1}, [%2];" : "=r"(v.x), "=r"(v.y) : "l"(p) : "memory"); return v;
}
__device__ __forceinline__ float4 ld_rlx128f(const float4* p) {
    float4 v; asm volatile("ld.relaxed.gpu.global.v4.f32 {%0,%1,%2,%3}, [%4];" : "=f"(v.x), "=f"(v.y), "=f"(v.z), "=f"(v.w) : "l"(p) : "memory"); return v;
}
__device__ __forceinline__ void take3(float4* p, uint32_t mask, float4 (&v)[3]) {
    asm volatile("{ .reg .b128 a, b, c; .reg .b64 x, y; .reg .pred q0, q1, q2; .reg .b32 t;\n"
                 "mov.b64 x, 0; mov.b128 a, {x, x}; mov.b128 b, {x, x}; mov.b128 c, {x, x};\n"
                 "and.b32 t, %13, 1; setp.ne.u32 q0, t, 0; and.b32 t, %13, 2; setp.ne.u32 q1, t, 0; and.b32 t, %13, 4; setp.ne.u32 q2, t, 0;\n"
                 "@q0 atom.relaxed.gpu.global.exch.b128 a, [%12], a; @q1 atom.relaxed.gpu.global.exch.b128 b, [%12+16384], b;\n"
                 "@q2 atom.relaxed.gpu.global.exch.b128 c, [%12+32768], c;\n"
                 "mov.b128 {x, y}, a; mov.b64 {%0,%1}, x; mov.b64 {%2,%3}, y; mov.b128 {x, y}, b; mov.b64 {%4,%5}, x; mov.b64 {%6,%7}, y;\n"
                 "mov.b128 {x, y}, c; mov.b64 {%8,%9}, x; mov.b64 {%10,%11}, y; }"
                 : "=f"(v[0].x), "=f"(v[0].y), "=f"(v[0].z), "=f"(v[0].w), "=f"(v[1].x), "=f"(v[1].y), "=f"(v[1].z), "=f"(v[1].w),
                   "=f"(v[2].x), "=f"(v[2].y), "=f"(v[2].z), "=f"(v[2].w) : "l"(p), "r"(mask) : "memory");
}
__device__ __forceinline__ void st_rlx32(uint32_t* p, uint32_t v) { asm volatile("st.relaxed.gpu.global.u32 [%0], %1;" ::"l"(p), "r"(v) : "memory"); }
__device__ __forceinline__ uint32_t hmul_bf2(uint32_t a, uint32_t b) {
    uint32_t r; asm("mul.rn.bf16x2 %0, %1, %2;" : "=r"(r) : "r"(a), "r"(b)); return r;
}
__device__ __forceinline__ uint32_t hsub_bf2(uint32_t a, uint32_t b) {
    uint32_t r; asm("sub.rn.bf16x2 %0, %1, %2;" : "=r"(r) : "r"(a), "r"(b)); return r;
}
constexpr int SPIN_LIMIT = 1 << 22;

__constant__ uint32_t c_inv2pi[8] = {0u, 0x28be60dbu, 0x9391054au, 0x7f09d5f4u, 0x7d4d3770u, 0x36d8a566u, 0x4f10e410u, 0x7f9458eau};
constexpr uint32_t BIGX = 0x4280u;
__device__ __forceinline__ float cos_big(uint32_t xb) {
    uint32_t e = (xb >> 7) & 0xffu, M = (xb & 0x7fu) | 0x80u;
    uint32_t pp = e - 102u;
    uint32_t wi = pp >> 5;
    uint32_t t0 = c_inv2pi[wi], t1 = c_inv2pi[wi + 1], t2 = c_inv2pi[wi + 2];
    uint32_t f = M * __funnelshift_l(t1, t0, pp) + __umulhi(M, __funnelshift_l(t2, t1, pp));
    float c = __cosf((float)(int)f * 1.4629180792671596e-9f);
    return e == 255u ? __uint_as_float(0x7fc00000u) : c;
}
__device__ __forceinline__ float cos_bf(uint32_t xb) {
    return (xb & 0x7fffu) > BIGX ? cos_big(xb) : __cosf(__uint_as_float(xb << 16));
}
__device__ __forceinline__ uint32_t pack_bf2(float lo, float hi) {
    uint32_t r; asm("cvt.rn.bf16x2.f32 %0, %1, %2;" : "=r"(r) : "f"(hi), "f"(lo)); return r;
}
template <int N> __device__ __forceinline__ uint32_t pick(int k, const uint32_t (&a)[N]) {
    uint32_t v = a[0];
#pragma unroll
    for (int i = 1; i < N; i++) if (k == i) v = a[i];
    return v;
}
template <int N> __device__ __forceinline__ uint2 pick(int k, const uint2 (&a)[N]) {
    uint2 v = a[0];
#pragma unroll
    for (int i = 1; i < N; i++) if (k == i) v = a[i];
    return v;
}
__device__ __forceinline__ void side_add(uint32_t bin, uint32_t row, float a, float b, float c, float d) {
    red4(&g_ovf[bin * RPAD + row], a, b, c, d);
    g_dirty[bin * DROW + row] = 1;
}
__device__ __forceinline__ void slow_triplet(const Params& p, uint32_t ii, uint32_t oo, float c) {
    const uint2 v = __ldg(p.m + ii);
    const uint32_t bo = __umulhi(oo, p.mg2);
    side_add(bo, oo - bo * p.R2, c * bf_lo(v.x), c * bf_hi(v.x), c * bf_lo(v.y), c * bf_hi(v.y));
}
__device__ __forceinline__ void slow_rec1(const Params& p, uint32_t x, uint32_t y, uint32_t bin) {
    const uint2 v = __ldg(p.m + bin * p.R1 + (y & 0xffffu));
    const float c = bf_hi(y);
    side_add(x & 0xffu, __byte_perm(x, 0u, 0x4413) >> 3, c * bf_lo(v.x), c * bf_hi(v.x), c * bf_lo(v.y), c * bf_hi(v.y));
}
__device__ __forceinline__ uint32_t aux_of(uint32_t w0, uint32_t w1, uint32_t k = 0) {
    uint32_t u; asm("lop3.b32 %0, %1, %2, 0xf000f000, 0xe4;" : "=r"(u) : "r"(w0), "r"((w1 >> 4) + k));
    return __byte_perm(u, 0u, 0x4413);
}
__device__ __forceinline__ void slow_rec2(const Params& p, uint32_t w0, uint32_t w1, uint32_t bin, float unit) {
    side_add(bin, aux_of(w0, w1) >> 3, (float)((int)(w0 & 0xfffu) - 2048) * unit, (float)((int)(w0 >> 16 & 0xfffu) - 2048) * unit,
             (float)((int)(w1 & 0xfffu) - 2048) * unit, (float)((int)(w1 >> 16 & 0xfffu) - 2048) * unit);
}
template <uint32_t M> __device__ __forceinline__ uint32_t and_or(uint32_t a, uint32_t c) {
    uint32_t r; asm("lop3.b32 %0, %1, %2, %3, 0xea;" : "=r"(r) : "r"(a), "n"(M), "r"(c)); return r;
}
template <uint32_t M> __device__ __forceinline__ uint32_t xor_and(uint32_t a, uint32_t c) {
    uint32_t r; asm("lop3.b32 %0, %1, %2, %3, 0x48;" : "=r"(r) : "r"(a), "n"(M), "r"(c)); return r;
}
__device__ __forceinline__ uint32_t mux(uint32_t a, uint32_t b, uint32_t m) {
    uint32_t r; asm("lop3.b32 %0, %1, %2, %3, 0xd8;" : "=r"(r) : "r"(a), "r"(b), "r"(m)); return r;
}
__device__ __forceinline__ uint32_t and_xor(uint32_t a, uint32_t m, uint32_t c) {
    uint32_t r; asm("lop3.b32 %0, %1, %2, %3, 0x6a;" : "=r"(r) : "r"(a), "r"(m), "r"(c)); return r;
}
__device__ __forceinline__ uint2 ld_in(const uint2* a) {
    uint2 v; asm volatile("ld.global.nc.L1::no_allocate.v2.u32 {%0,%1}, [%2];" : "=r"(v.x), "=r"(v.y) : "l"(a)); return v;
}
__device__ __forceinline__ uint32_t ld_in(const uint32_t* a) {
    uint32_t v; asm volatile("ld.global.nc.L1::no_allocate.u32 %0, [%1];" : "=r"(v) : "l"(a)); return v;
}
template <int OFF> __device__ __forceinline__ void put_rec(uint32_t ret, uint32_t lim, uint32_t addr, uint32_t x, uint32_t y) {
    asm volatile("{ .reg .pred q; setp.lt.u32 q, %0, %1; @q st.shared.v2.u32 [%2+%5], {%3,%4}; }" ::"r"(ret), "r"(lim), "r"(addr), "r"(x), "r"(y), "n"(OFF) : "memory");
}
__device__ __forceinline__ uint32_t mbar_try(uint32_t mb, uint32_t parity) {
    uint32_t ok;
    asm volatile("{ .reg .pred q; mbarrier.try_wait.parity.shared::cta.b64 q, [%1], %2; selp.u32 %0, 1, 0, q; }" : "=r"(ok) : "r"(mb), "r"(parity) : "memory");
    return ok;
}
__device__ __forceinline__ void mbar_wait(uint32_t mb, uint32_t parity) {
    if (!mbar_try(mb, parity)) {
        int it = 0;
        while (!mbar_try(mb, parity)) if (++it > SPIN_LIMIT) __trap();
    }
}
__device__ __forceinline__ void mbar_init(uint32_t mb, uint32_t n) { asm volatile("mbarrier.init.shared::cta.b64 [%0], %1;" ::"r"(mb), "r"(n) : "memory"); }
__device__ __forceinline__ void mbar_arrive(uint32_t mb) { asm volatile("mbarrier.arrive.shared::cta.b64 _, [%0];" ::"r"(mb) : "memory"); }
constexpr int B_FULL = OFF_BAR, B_OPEN = OFF_BAR + 16, B_FREE = OFF_BAR + 32;
constexpr int W_END = OFF_BAR + 40, W_SIDE = OFF_BAR + 44, W_PAR = OFF_BAR + 48, W_ROLE = OFF_BAR + 52, W_EXP = OFF_BAR + 56, W_UNIT = OFF_BAR + 60;
enum { BAR_S1 = 1, BAR_PROBE, BAR_HIST, BAR_ROLE, BAR_TABLE, BAR_H1, BAR_DONE };
constexpr int W_M1 = NS1 + NC, W_M2 = 31;

extern __shared__ __align__(1024) unsigned char smem[];
#define TK_DECL
#define TK(i)
#define TK_CNT(i)
#define TK_OUT
#define TK_ARG
#define TK_PASS
#define TKX(i)
#define TKY(i)

constexpr int NR = (R2MAX + NTHR - 1) / NTHR;
__device__ __forceinline__ void gates(const Params& p, int e0, int e1, int e2, uint4* gh) {
    constexpr int NH = 3;
    const int e[NH] = {e0, e1, e2};
    uint32_t dd[NH];
    float g[NH][4], h[NH][4];
#pragma unroll
    for (int u = 0; u < NH; u++) {
        dd[u] = reinterpret_cast<const uint16_t*>(p.dist)[min(e[u], p.E - 1)] * 0x10001u;
#pragma unroll
        for (int k = 0; k < 4; k++) { g[u][k] = 0.f; h[u][k] = 0.f; }
    }
#pragma unroll 1
    for (int r2 = 0; r2 < 4; r2++) {
        const uint32_t cen = reinterpret_cast<const uint32_t*>(smem + OFF_WG + 256)[r2];
        uint32_t rb[NH];
#pragma unroll
        for (int u = 0; u < NH; u++) {
            const uint32_t df = hsub_bf2(dd[u], cen);
            const uint32_t ar = hmul_bf2(hmul_bf2(df, df), 0xc120c120u);
            rb[u] = pack_bf2(__expf(bf_lo(ar)), __expf(bf_hi(ar)));
        }
#pragma unroll
        for (int i = 0; i < 2; i++) {
            const float4 ws = reinterpret_cast<const float4*>(smem + OFF_WG)[r2 * 2 + i], wr = reinterpret_cast<const float4*>(smem + OFF_WG + 128)[r2 * 2 + i];
#pragma unroll
            for (int u = 0; u < NH; u++) {
                const float x = i ? bf_hi(rb[u]) : bf_lo(rb[u]);
                g[u][0] += x * ws.x; g[u][1] += x * ws.y; g[u][2] += x * ws.z; g[u][3] += x * ws.w;
                h[u][0] += x * wr.x; h[u][1] += x * wr.y; h[u][2] += x * wr.z; h[u][3] += x * wr.w;
            }
        }
    }
#pragma unroll
    for (int u = 0; u < NH; u++)
        gh[u] = make_uint4(pack_bf2(g[u][0], g[u][1]), pack_bf2(g[u][2], g[u][3]), pack_bf2(h[u][0], h[u][1]), pack_bf2(h[u][2], h[u][3]));
}
__device__ __forceinline__ void prefetch_l2(const void* a) { asm volatile("prefetch.global.L2 [%0];" ::"l"(a)); }
__device__ __forceinline__ uint4* gate_slot(int k) { return reinterpret_cast<uint4*>(smem + OFF_H1 + (k >= WIN / 16 ? 0x20000 - WIN : 0)) + k; }
__device__ __forceinline__ void wait_flags(const Params& p, uint32_t sb, int lane, uint32_t need) {
    const unsigned char* f = p.ring + M_FLAG + (lds32(sb + W_SIDE) << 12);
    int it = 0;
    while (true) {
        const float4 a = ld_rlx128f(reinterpret_cast<const float4*>(f) + lane);
        const uint32_t b = ld_rlx32(reinterpret_cast<const uint32_t*>(f) + 128 + (lane & 3));
        const uint32_t d = (__float_as_uint(a.x) ^ need) | (__float_as_uint(a.y) ^ need) | (__float_as_uint(a.z) ^ need) | (__float_as_uint(a.w) ^ need) | (b ^ need);
        if (__all_sync(0xffffffffu, d == 0)) break;
        __nanosleep(50);
        if (++it > SPIN_LIMIT) __trap();
    }
    __threadfence();
}
__device__ __forceinline__ void epilogue(const Params& p, uint32_t sb) {
    int tid;
    asm volatile("mov.u32 %0, %%tid.x;" : "=r"(tid));
    const int role = lds32(sb + W_ROLE), row0 = role * p.R2, nrows = min(p.R2, p.E - row0), hw = tid >> 5;
    const bool s3 = hw > W_M1 && hw < W_M2;
    constexpr int T3 = (W_M1 + 1) * 32, N3 = NC * 32;
    uint4 gh[NR];
    if (hw < NS1) {
        if (tid * 64 < nrows) prefetch_l2(p.dist + row0 + tid * 64);
        for (int i = tid * 16; i < nrows; i += NS1 * 32 * 16) prefetch_l2(p.m + row0 + i);
    }
    if (!s3) gates(p, row0 + tid + 3 * NTHR, row0 + tid + 4 * NTHR, row0 + tid + 5 * NTHR, gh + 3);
    if (hw < NS1) {
        bar_sync(BAR_H1, (NS1 + 1) * 32);
#pragma unroll 1
        for (int k0 = tid; k0 < NR * N3; k0 += 3 * NS1 * 32) {
            int k[3], e[3];
#pragma unroll
            for (int u = 0; u < 3; u++) { k[u] = k0 + u * NS1 * 32; e[u] = row0 + T3 + k[u] + k[u] / N3 * (NTHR - N3); }
            gates(p, e[0], e[1], e[2], gh);
#pragma unroll
            for (int u = 0; u < 3; u++) if (k[u] < NR * N3) *gate_slot(k[u]) = gh[u];
        }
#pragma unroll
        for (int i = tid; i < DROW / 8; i += NS1 * 32) {
            const uint2 f = ld_rlx64(g_dirty + role * DROW + i * 8);
            if (f.x | f.y) prefetch_l2(g_ovf + role * RPAD + i * 8);
        }
    }
    if (!s3) gates(p, row0 + tid, row0 + tid + NTHR, row0 + tid + 2 * NTHR, gh);
    if (hw == W_M1) wait_flags(p, sb, tid & 31, lds32(sb + W_END));
    TKX(5)
    bar_sync(0, NTHR);
    TKX(6)
    uint32_t dirty = 0;
#pragma unroll
    for (int it = 0; it < NR; it++) {
        uint32_t f;
        asm volatile("ld.relaxed.gpu.global.u8 %0, [%1];" : "=r"(f) : "l"(g_dirty + role * DROW + tid + it * NTHR) : "memory");
        dirty |= f << it;
    }
    if (s3) {
#pragma unroll
        for (int it = 0; it < NR; it++) gh[it] = *gate_slot(tid - T3 + it * N3);
    }
    if (hw == W_M1 && blockIdx.x == 0) {
        if (tid == W_M1 * 32) g_base = lds32(sb + W_END);
        if (tid < W_M1 * 32 + 3) *reinterpret_cast<uint32_t*>(p.ring + (tid & 2 ? M_PAR : M_CNT + (tid & 1) * 4096)) = 0;
    }
    const float unit = *reinterpret_cast<const float*>(smem + W_UNIT);
    const float4* w4 = reinterpret_cast<const float4*>(smem + OFF_WSM);
#pragma unroll
    for (int i0 = 0; i0 < NR; i0 += 3) {
        uint2 mv[3];
        float4 o[3];
#pragma unroll
        for (int u = 0; u < 3; u++) mv[u] = __ldg(p.m + min(row0 + tid + (i0 + u) * NTHR, p.E - 1));
        take3(&g_ovf[role * RPAD + tid + i0 * NTHR], dirty >> i0, o);
#pragma unroll
        for (int u = 0; u < 3; u++) {
            const int it = i0 + u, i = tid + it * NTHR;
            if (dirty >> it & 1) g_dirty[role * DROW + i] = 0;
            if (i < nrows) {
                const uint2 ac = reinterpret_cast<const uint2*>(smem + OFF_ACC)[i];
                const uint32_t u0 = ac.x + 0x40004000u, u1 = ac.y + 0x40004000u;
                const float a[4] = {(float)((int)(u0 & 0xffffu) - 0x8000) * unit + o[u].x, (float)((int)(u0 >> 16) - 0x8000) * unit + o[u].y,
                                    (float)((int)(u1 & 0xffffu) - 0x8000) * unit + o[u].z, (float)((int)(u1 >> 16) - 0x8000) * unit + o[u].w};
                float sd[4] = {0, 0, 0, 0}, uu[4] = {0, 0, 0, 0};
#pragma unroll
                for (int j = 0; j < 4; j++) {
                    float4 w = w4[j];
                    sd[0] += a[j] * w.x; sd[1] += a[j] * w.y; sd[2] += a[j] * w.z; sd[3] += a[j] * w.w;
                }
                const uint32_t a01 = pack_bf2(sd[0] * bf_lo(gh[it].x), sd[1] * bf_hi(gh[it].x)), a23 = pack_bf2(sd[2] * bf_lo(gh[it].y), sd[3] * bf_hi(gh[it].y));
                const float ag[4] = {bf_lo(a01), bf_hi(a01), bf_lo(a23), bf_hi(a23)};
#pragma unroll
                for (int j = 0; j < 4; j++) {
                    float4 w = w4[4 + j];
                    uu[0] += ag[j] * w.x; uu[1] += ag[j] * w.y; uu[2] += ag[j] * w.z; uu[3] += ag[j] * w.w;
                }
                const uint32_t t01 = hmul_bf2(pack_bf2(uu[0], uu[1]), gh[it].z);
                const uint32_t t23 = hmul_bf2(pack_bf2(uu[2], uu[3]), gh[it].w);
                uint2 q;
                asm("add.rn.bf16x2 %0, %1, %2;" : "=r"(q.x) : "r"(mv[u].x), "r"(t01));
                asm("add.rn.bf16x2 %0, %1, %2;" : "=r"(q.y) : "r"(mv[u].y), "r"(t23));
                p.out[row0 + i] = q;
            }
        }
        if (i0 == 0) { TKY(3) }
    }
}

template <int HOP> __device__ __forceinline__ uint2 null_rec(int lane, uint32_t R) {
    if (HOP == 1) return make_uint2(0x800000u | H<1>::tag(R), (OFF_CNT1 - OFF_M) / 8);
    return make_uint2(0x08000800u | lane << 28, 0x08000800u | H<2>::tag(R));
}
template <int OFF> __device__ __forceinline__ void sts128(uint32_t a, const uint4& v) {
    asm volatile("st.shared.v4.u32 [%0+%5], {%1,%2,%3,%4};" ::"r"(a), "r"(v.x), "r"(v.y), "r"(v.z), "r"(v.w), "n"(OFF) : "memory");
}
template <int HOP> __device__ __forceinline__ void fill(uint32_t win, int lane, uint32_t R) {
    const uint2 v = null_rec<HOP>(lane, R);
#pragma unroll 11
    for (int i = 0; i < WIN / 512; i++) sts128<0>(win + lane * 16 + i * 512, make_uint4(v.x, v.y, v.x, v.y));
}
template <int HOP> __device__ __forceinline__ void reset(uint32_t win, int lane, uint32_t R) {
    const uint2 v = null_rec<HOP>(lane, R);
    const uint32_t a = win + lane * 32 + H<HOP>::mark(R, lane >> 2) * 8;
#pragma unroll
    for (int i = 0; i < 16; i++) sts64(a + i * 1024, v.x, v.y);
    if (lane < 16) sts64(a + 16384, v.x, v.y);
}
__device__ __forceinline__ bool elect() {
    uint32_t q; asm volatile("{ .reg .pred q; elect.sync _|q, 0xffffffff; selp.u32 %0, 1, 0, q; }" : "=r"(q)); return q;
}
__device__ __forceinline__ const unsigned char* mk_ptr(uint32_t lo, uint32_t hi) { return reinterpret_cast<const unsigned char*>((uint64_t)hi << 32 | lo); }
__device__ __forceinline__ void bulk_store(uint32_t lo, uint32_t hi, uint32_t src, uint32_t n) {
    asm volatile("cp.async.bulk.global.shared::cta.bulk_group [%0], [%1], %2;" ::"l"(mk_ptr(lo, hi)), "r"(src), "r"(n) : "memory");
}
#define CRED_NS 100
#define CRED_SKIP 1
#define LAG 0
template <int HOP>
__device__ __forceinline__ void manager(const Params& p, uint32_t sb, int lane, int role, uint32_t base) {
    typedef H<HOP> h;
    constexpr int V = h::NBIN / 32, PB = h::S * 8;
    const int RT = p.rounds, lo = HOP == 1 && role >= NG ? NG : 0, hi = lo + h::NBIN;
    const int w = (role - lo) / (HOP * J), j = (role - lo - w * HOP * J) / HOP;
    const Ring rg(p.ring, __reduce_or_sync(0xffffffffu, lds32(sb + W_PAR)), 2 * w + HOP - 1);
    const uint32_t side = lds32(sb + W_SIDE), dhi = rg.main >> 32, mhi = rg.mid >> 32;
    const uint32_t c0 = HOP == 2 ? role & 1 : 0, up = (HOP == 1 && lo) ^ rg.par ^ c0;
    uint32_t dA = ((uint32_t)rg.main + src_off(j) + (c0 << 16) + (up ? 4096 : 12288)) ^ slot_off(base % 3);
    uint32_t dM = ((uint32_t)rg.mid + src_off(j) + c0 * 1024) ^ slot_off(base % 3);
    const int a0 = max(64, lo), b1 = min(68, hi);
    int n0 = (min(NHI, hi) - a0) * PB, a1 = (max(NLO, lo) - lo) * PB;
    const unsigned char* cr = reinterpret_cast<const unsigned char*>(rg.main) + MISC + ((side ^ rg.par) << 12);
    const unsigned char* cr0 = cr + cred_off(lo + lane * V), *cr1 = cr + cred_off(lo + 32 * V + min(lane, V - 1));
    const uint32_t ca0 = sb + h::CNT + lane * V * 4, ca1 = sb + h::CNT + (32 * V + min(lane, V + NDUM)) * 4;
    const uint32_t rot0 = (lane * V & 7) * 16, rot1 = lane * 16;
    uint32_t st = slot_steps(base);
    uint32_t init = h::init(base), prim = sb + h::STG + (HOP == 1 ? h::win(base) : 0u);
    uint32_t cs[5];
    auto sample = [&]() {
        if (V == 2) asm volatile("ld.relaxed.gpu.global.v2.u32 {%0,%1}, [%2];" : "=r"(cs[0]), "=r"(cs[1]) : "l"(cr0) : "memory");
        else asm volatile("ld.relaxed.gpu.global.v4.u32 {%0,%1,%2,%3}, [%4];" : "=r"(cs[0]), "=r"(cs[1]), "=r"(cs[2]), "=r"(cs[3]) : "l"(cr0) : "memory");
        cs[V] = ld_rlx32(reinterpret_cast<const uint32_t*>(cr1));
    };
    sample();
    uint32_t c[5];
    TK_DECL
#pragma unroll 1
    for (int r = 0;; r++) {
        const uint32_t R = base + r, ninit = h::init(R + 1), done = prim;
        TK(5)
        mbar_wait(sb + B_FULL + (HOP - 1) * 8, r & 1);
        TK(0)
        if (V == 2) asm volatile("ld.shared.v2.u32 {%0,%1}, [%2];" : "=r"(c[0]), "=r"(c[1]) : "r"(ca0) : "memory");
        else asm volatile("ld.shared.v4.u32 {%0,%1,%2,%3}, [%4];" : "=r"(c[0]), "=r"(c[1]), "=r"(c[2]), "=r"(c[3]) : "r"(ca0) : "memory");
        c[V] = lds32(ca1);
        uint32_t nc[5];
#pragma unroll
        for (int k = 0; k <= V; k++) {
            const uint32_t z = ninit + (k < V ? rot0 + k * 16 : rot1);
            nc[k] = min(max(c[k] + (ninit - init - h::S * h::INC), z), z + (h::CAP - h::S) * h::INC);
        }
        if (V == 2) sts64(ca0, nc[0], nc[1]); else sts128<0>(ca0, make_uint4(nc[0], nc[1], nc[2], nc[3]));
        sts32(ca1, lane < V ? nc[V] : lane < V + NDUM ? DUMMY : r);
        __syncwarp();
        if (lane == 0) mbar_arrive(sb + B_OPEN + (HOP - 1) * 8);
        TK(1)
        TK(2)
        asm volatile("fence.proxy.async.shared::cta;" ::: "memory");
        TK(6)
        if (r >= D) {
            int it = 0;
            while (true) {
                uint32_t bad = 0;
#pragma unroll
                for (int k = 0; k <= V; k++) bad |= cs[k] - (R - D + 1);
                if (!__any_sync(0xffffffffu, bad >> 20)) break;
                if (++it > SPIN_LIMIT) __trap();
                if (it > CRED_SKIP) __nanosleep(CRED_NS);
                sample();
            }
        }
        TK(3)
        if (elect()) {
            const uint32_t dB = (HOP == 1 ? dA ^ 0x10000u : dA) + (up ? 8192 : -8192), sm = prim + (lo ? 2 * PB : 0);
            bulk_store(dA, dhi, sm, 8192);
            bulk_store(dB, dhi, HOP == 1 ? sm + 8192 : prim + 68 * PB, 8192);
            if (n0 > 0) bulk_store(dM + (a0 - 64) * PB, mhi, prim + (a0 - lo) * PB, n0);
            if (a1 < (b1 - lo) * PB) bulk_store((dM ^ 4096u) + (uint32_t)((lo - NLO) * PB + a1), mhi, prim + a1, (b1 - lo) * PB - a1);
            asm volatile("cp.async.bulk.commit_group;" ::: "memory");
            asm volatile("cp.async.bulk.wait_group.read 0;" ::: "memory");
        }
        __syncwarp();
        TK(4)
        prim = HOP == 1 ? prim ^ 0x20000u : prim >= sb + 0x30000u ? sb : prim + (prim - sb) + 0x10000u;
        if (r == RT - 1) break;
        reset<HOP>(done, lane, R + HOP + 1);
        if (HOP == 1) {
            __syncwarp();
            if (lane == 0) mbar_arrive(sb + B_FREE);
        }
        if (r == D - 1 || r == RT - D - 1) {
            uint32_t n = NHI, m = NLO;
            if (r < RT - D - 1) {
                int it = 0;
                while (true) {
                    n = ld_rlx32(reinterpret_cast<const uint32_t*>(p.ring + M_CNT + (side << 12)));
                    if ((n & 0xffffu) + (n >> 16) == NB) break;
                    if (++it > SPIN_LIMIT) __trap();
                }
                m = n = min(max(__reduce_or_sync(0xffffffffu, n) & 0xffffu, (uint32_t)NLO), (uint32_t)NHI);
            }
            n0 = (min((int)n, hi) - a0) * PB;
            a1 = (max((int)m, lo) - lo) * PB;
        }
        sample();
        slot_next(dA, st); slot_next(dM, st);
        st = slot_rot(st);
        init = ninit;
    }
#pragma unroll 1
    for (int k = 0; k <= V; k++) {
        const uint32_t bin = k < V ? lane * V + k : 32 * V + lane, n = bin < h::NBIN ? min((pick(k, c) - init) >> h::SH, (uint32_t)h::CAP) : 0u;
#pragma unroll 1
        for (uint32_t x = h::S; x < n; x++) {
            const uint2 w = lds64(prim + bin * PB + ((x + (bin & 7) * 2) & (h::S - 1)) * 8);
            if (HOP == 1) slow_rec1(p, w.x, w.y, bin);
            else slow_rec2(p, w.x, w.y, bin, __uint_as_float(lds32(sb + W_UNIT)));
        }
    }
    asm volatile("cp.async.bulk.wait_group 0;" ::: "memory");
    TK_OUT
}

#define POLL_NS 200
#define POLL_NS3 1500
template <int HOP> struct Reader {
    uint32_t lo, hi, st, line;
    uint32_t* cred;
    __device__ __forceinline__ void init(const Params& p, uint32_t sb, int w, int lane, int role, uint32_t base) {
        constexpr int PB = H<HOP>::S * 8;
        const int first = HOP == 1 ? (role >= NG ? NG : 0) + w * J : w * 2 * J;
        const Ring rg(p.ring, lds32(sb + W_PAR), 2 * w + HOP - 1);
        const uint32_t side = lds32(sb + W_SIDE);
        const bool mid = side ? role < 68 : role >= 64;
        const uint32_t i = role - (side ? (mid ? NLO : 68) : (mid ? 64 : 0));
        const uint32_t c = HOP == 1 ? i >> 5 : lane >> 4, in = HOP == 1 ? (i & 31) * PB + lane * 8 : i * PB + (lane & 15) * 8;
        lo = (in + (mid ? ((uint32_t)rg.mid ^ side << 12) + c * 1024 : (uint32_t)rg.main + (c << 16) + (side ^ rg.par ^ c ? 4096 : 12288))) ^ slot_off(base % 3);
        hi = __reduce_or_sync(0xffffffffu, (uint32_t)((mid ? rg.mid : rg.main) >> 32));
        st = slot_steps(base);
        line = HOP == 1 ? 2 * (role % NG) : role;
        const bool both = first >= NLO && first < NHI;
        cred = lane < 1 + both ? reinterpret_cast<uint32_t*>(rg.main + MISC + (((both ? lane : first >= NG) ^ rg.par) << 12) + cred_off(role)) : nullptr;
    }
    template <int K> __device__ __forceinline__ void load1(uint2& v) const {
        asm volatile("ld.relaxed.gpu.global.v2.u32 {%0,%1}, [%2+%3];" : "=r"(v.x), "=r"(v.y) : "l"(mk_ptr(lo, hi)), "n"(src_off(K)) : "memory");
    }
    template <int K> __device__ __forceinline__ void again(uint2& v, uint32_t want, uint32_t mask) const {
        if (__ballot_sync(0xffffffffu, xor_and<H<HOP>::TAG>(HOP == 1 ? v.x : v.y, want)) & mask) load1<K>(v);
    }
    __device__ __forceinline__ void load(uint2 (&rec)[J]) const {
        load1<0>(rec[0]); load1<1>(rec[1]); load1<2>(rec[2]); load1<3>(rec[3]); load1<4>(rec[4]); load1<5>(rec[5]);
    }
    __device__ __forceinline__ void check(uint2 (&rec)[J], uint32_t R, uint32_t ns TK_ARG) {
        const uint32_t want = H<HOP>::tag(R);
        const uint32_t mask = 0x1111u << H<HOP>::mark(R, line) | 0x11110000u << H<HOP>::mark(R, line + 2 - HOP);
        int it = 0;
        while (true) {
            uint32_t bad = 0;
#pragma unroll
            for (int j = 0; j < J; j++) bad |= (HOP == 1 ? rec[j].x : rec[j].y) ^ want;
            if (!(__ballot_sync(0xffffffffu, bad & H<HOP>::TAG) & mask)) break;
            if (++it > SPIN_LIMIT) __trap();
            __nanosleep(ns);
            TK_CNT(7)
            again<0>(rec[0], want, mask); again<1>(rec[1], want, mask); again<2>(rec[2], want, mask);
            again<3>(rec[3], want, mask); again<4>(rec[4], want, mask); again<5>(rec[5], want, mask);
        }
        if (cred) st_rlx32(cred, R + 1);
        slot_next(lo, st);
        st = slot_rot(st);
    }
    __device__ __forceinline__ void finish() const { if (cred) st_rlx32(cred, 0u); }
};

#define NPROBE 9
__device__ __forceinline__ uint32_t near_half(unsigned char* pair, uint32_t zero) {
#pragma unroll
    for (int i = 0; i < 4; i++) *reinterpret_cast<uint4*>(pair + (i >> 1) * 4096 + (i & 1) * 16) = make_uint4(0u, 0u, 0u, 0u);
    uint32_t best[2] = {~0u, ~0u}, v = 0, prev = 0;
    asm volatile("red.relaxed.gpu.global.add.u32 [%0], 1;" ::"l"(pair + 4096) : "memory");
#pragma unroll
    for (int t = 0; t <= NPROBE; t++) {
        uint32_t now;
        asm volatile("atom.relaxed.gpu.global.add.u32 %0, [%1], 1;" : "=r"(v) : "l"(pair + (t & 1) * 4096 + (v & zero)) : "memory");
        asm volatile("mov.u32 %0, %%clock;" : "=r"(now) :: "memory");
        if (t > 1) best[(t - 1) & 1] = min(best[(t - 1) & 1], now - prev);
        prev = now;
    }
    return (best[1] < best[0] ? 1u : 0u) | (v & zero);
}
template <bool B> struct BoolC { static constexpr bool value = B; };

template <int NP>
__device__ __forceinline__ void stage1(const Params& p, uint32_t sb, const int pos0, int lane, uint32_t base) {
    typedef H<1> h;
    const int RT = p.rounds;
    uint32_t ff = *reinterpret_cast<const uint16_t*>(p.ang_freq) * 0x10001u;
    auto pair_of = [&](int r, int pos) {
        const int q = r < RT - 1 ? (r * NB + blockIdx.x) * NPR + pos : (RT - 1) * NB * NPR + blockIdx.x * p.lastn + pos;
        return (r < RT - 1 || (r == RT - 1 && pos < p.lastn)) && q < p.T2 ? q : -1;
    };
    uint2 vi[NP], vo[NP]; uint32_t va[NP];
    auto load_edge = [&](int r) {
#pragma unroll
        for (int u = 0; u < NP; u++) {
            const int q = max(pair_of(r, pos0 + u * 32), 0);
            vi[u] = ld_in(p.idx_in + q); vo[u] = ld_in(p.idx_out + q); va[u] = ld_in(p.angle + q);
        }
    };
    load_edge(0);
    if (blockIdx.x == 0 && pos0 == 0 && (p.T & 1)) {
        const int t = p.T - 1;
        slow_triplet(p, reinterpret_cast<const uint32_t*>(p.idx_in)[t], reinterpret_cast<const uint32_t*>(p.idx_out)[t],
                     bf16r(cos_bf(hmul_bf2(reinterpret_cast<const uint16_t*>(p.angle)[t], ff) & 0xffffu)));
    }
    for (int i = threadIdx.x * 16; i < p.R2 && blockIdx.x * p.R2 + i < p.E; i += NS1 * 32 * 16) prefetch_l2(p.m + blockIdx.x * p.R2 + i);
    uint32_t R = __reduce_or_sync(0xffffffffu, base);
    ff = __reduce_or_sync(0xffffffffu, ff);
    bar_sync(BAR_S1, (NS1 + 1) * 32);
    TK_DECL
    auto step = [&](const int r, const int qn, auto edge) {
        constexpr bool EDGE = decltype(edge)::value;
        uint32_t cc[NP], big = 0;
#pragma unroll
        for (int u = 0; u < NP; u++) {
            va[u] = hmul_bf2(va[u], ff);
            cc[u] = pack_bf2(__cosf(bf_lo(va[u])), __cosf(bf_hi(va[u])));
            big = __vmaxu2(big, va[u] & 0x7fff7fffu);
        }
        if ((big + (0x7fffu - BIGX) * 0x10001u) & 0x80008000u) {
#pragma unroll 1
            for (int u = 0; u < NP; u++) {
                const uint32_t a = pick(u, va);
                float c0 = cos_bf(a & 0xffffu), c1 = cos_bf(a >> 16);
                if ((c0 != c0 || c1 != c1) && (!EDGE || pair_of(r, pos0 + u * 32) >= 0)) {
                    const uint2 i2 = pick(u, vi), o2 = pick(u, vo);
                    if (c0 != c0) slow_triplet(p, i2.x, o2.x, c0);
                    if (c1 != c1) slow_triplet(p, i2.y, o2.y, c1);
                }
                const uint32_t v = pack_bf2(c0 != c0 ? 0.f : c0, c1 != c1 ? 0.f : c1);
#pragma unroll
                for (int k = 0; k < NP; k++) if (k == u) cc[k] = v;
            }
        }
        uint32_t bin[2 * NP], x[2 * NP], y[2 * NP];
#pragma unroll
        for (int j = 0; j < 2 * NP; j++) {
            const uint32_t ii = j & 1 ? vi[j >> 1].y : vi[j >> 1].x, oo = j & 1 ? vo[j >> 1].y : vo[j >> 1].x;
            bin[j] = __umulhi(ii, p.mg1);
            y[j] = __byte_perm(bin[j] * p.k1 + ii, cc[j >> 1], j & 1 ? 0x7610 : 0x5410);
            const uint32_t bo = __umulhi(oo, p.mg2);
            x[j] = __byte_perm(bo * p.k2 + oo * 8u, bo, 0x0514);
            if (EDGE && pair_of(r, pos0 + (j >> 1) * 32) < 0) bin[j] = NG + (lane & (NDUM - 1));
        }
        if (EDGE) load_edge(r + 1);
        else {
            uint32_t dep = 0;
#pragma unroll
            for (int j = 0; j < 2 * NP; j++) dep |= x[j] | y[j];
            const int q = qn + (dep & p.zero);
#pragma unroll
            for (int u = 0; u < NP; u++) { vi[u] = ld_in(p.idx_in + q + u * 32); vo[u] = ld_in(p.idx_out + q + u * 32); va[u] = ld_in(p.angle + q + u * 32); }
        }
        const uint32_t init = h::init(R), kb = sb + h::win(R + 1), lim = init + (h::CAP << h::SH);
        TK(0)
        mbar_wait(sb + B_OPEN, ~R & 1);
        TK(1)
        bool freed = false;
        uint32_t over = 0;
#pragma unroll
        for (int g = 0; g < 2 * NP; g += 4) {
            constexpr int G = 4;
            uint32_t ret[G];
            int mx = 0;
#pragma unroll
            for (int j = 0; j < G; j++) if (g + j < 2 * NP) ret[j] = atoms_add<h::CNT>(sb + bin[g + j] * 4, h::INC);
#pragma unroll
            for (int j = 0; j < G; j++) if (g + j < 2 * NP) mx = j ? max(mx, (int)ret[j]) : (int)ret[j];
            if (!freed && __any_sync(0xffffffffu, mx >= (int)(init + 0x10000u))) { TK(2) mbar_wait(sb + B_FREE, ~R & 1); freed = true; TK(3) }
            TK(2)
#pragma unroll
            for (int j = 0; j < G; j++) if (g + j < 2 * NP) {
                x[g + j] = and_or<h::TAG>(ret[j], x[g + j]);
                put_rec<h::STG>(ret[j], lim, and_xor(ret[j], 0x20000u | h::PM, bin[g + j] * 256 + kb), x[g + j], y[g + j]);
            }
            if (mx >= (int)lim) {
#pragma unroll
                for (int j = 0; j < G; j++) if (g + j < 2 * NP && (int)ret[j] >= (int)lim) over |= 1u << (g + j);
            }
        }
        __syncwarp();
        if (elect()) mbar_arrive(sb + B_FULL);
        R++;
        TK(4)
#pragma unroll 1
        while (over) {
            TK_CNT(7)
            const int j = __ffs(over) - 1;
            over &= over - 1;
            slow_rec1(p, pick(j, x), pick(j, y), pick(j, bin));
        }
        __syncwarp();
    };
#pragma unroll 1
    for (int q = (NB + blockIdx.x) * NPR; q < p.qfull; q += NB * NPR) step(q / (NB * NPR) - 1, q + pos0, BoolC<false>());
#pragma unroll 1
    for (int r = max(p.qfull / (NB * NPR) - 1, 0); r < RT; r++) step(r, 0, BoolC<true>());
    TK_OUT
}

__device__ __forceinline__ void stage2(const Params& p, uint32_t sb, int w, int lane, int role, uint32_t base) {
    typedef H<2> h;
    const int RT = p.rounds;
    Reader<1> rd;
    rd.init(p, sb, w, lane, role, base);
    uint2 rec[J];
    rd.load(rec);
    bar_sync(BAR_TABLE, 2 * NC * 32);
    uint32_t kb = sb + 0x10000u, am = 0x10000u | h::PM;
    const float unit = __uint_as_float(__reduce_or_sync(0xffffffffu, lds32(sb + W_UNIT)));
    TK_DECL
#pragma unroll 1
    for (int r = 0; r < RT; r++) {
        rd.check(rec, base + r, POLL_NS TK_PASS);
        const uint32_t want = H<1>::tag(base + r);
        TK(0)
        uint2 mv[J];
#pragma unroll
        for (int j = 0; j < J; j++) mv[j] = lds64<OFF_M>(sb + (rec[j].y & 0xffffu) * 8);
        uint32_t fl = 0;
#pragma unroll
        for (int j = 0; j < J; j++) fl |= mv[j].y;
        if (fl & 0x40000000u) {
#pragma unroll 1
            for (int j = 0; j < J; j++) {
                const uint2 v = pick(j, mv), w = pick(j, rec);
                if ((v.y & 0x40000000u) && !((w.x ^ want) & 0xf00000u)) {
                    if (v.x & 0x40000000u) slow_rec1(p, w.x, w.y, lds32(sb + W_ROLE) % NG);
                    else {
                        const float c = bf_hi(w.y), s = __uint_as_float(lds32(sb + W_UNIT)) * 1024.f;
                        side_add(w.x & 0xffu, __byte_perm(w.x, 0u, 0x4413) >> 3, c * (bf_lo(v.x) * s), c * (bf_hi(v.x) * s),
                                 c * (bf_lo(v.y) * s), c * (bf_hi(v.y & 0xbfffffffu) * s));
                    }
                }
            }
#pragma unroll
            for (int j = 0; j < J; j++) if (mv[j].y & 0x40000000u) rec[j].x = 0x800000u;
        }
        uint32_t w0[J], w1[J], bin[J], ret[J];
#pragma unroll
        for (int j = 0; j < J; j++) {
            const float c = bf_hi(rec[j].y), MG = 8194.0f;
            const uint32_t x = rec[j].x;
            w0[j] = and_or<0xf000f000u>(x, __byte_perm(__float_as_uint(fmaf(c, bf_lo(mv[j].x), MG)), __float_as_uint(fmaf(c, bf_hi(mv[j].x), MG)), 0x5410));
            w1[j] = and_or<0xf000f000u>(x << 4, __byte_perm(__float_as_uint(fmaf(c, bf_lo(mv[j].y), MG)), __float_as_uint(fmaf(c, bf_hi(mv[j].y), MG)), 0x5410));
            bin[j] = min(xor_and<0xf000ffu>(x, want), NB + (lane & (NDUM - 1)));
        }
        const uint32_t lim = h::init(base + r) + 0x20000u;
        rd.load(rec);
        TK(1)
        mbar_wait(sb + B_OPEN + 8, (r - 1) & 1);
        TK(2)
#pragma unroll
        for (int j = 0; j < J; j++) ret[j] = atoms_add<h::CNT>(sb + bin[j] * 4, h::INC);
        uint32_t mx = 0;
#pragma unroll
        for (int j = 0; j < J; j++) {
            w1[j] = and_or<h::TAG>(ret[j], w1[j]);
            put_rec<0>(ret[j], lim, and_xor(ret[j], am, bin[j] * 128 + kb), w0[j], w1[j]);
            mx = __viaddmax_u32(ret[j], 0u - DUMMY, mx);
        }
        __syncwarp();
        if (lane == 0) mbar_arrive(sb + B_FULL + 8);
        TK(3)
        if (mx >= lim - DUMMY) {
            uint32_t over = 0;
#pragma unroll
            for (int j = 0; j < J; j++) if (ret[j] - DUMMY >= lim - DUMMY) over |= 1u << j;
#pragma unroll 1
            do {
                const int j = __ffs(over) - 1;
                over &= over - 1;
                slow_rec2(p, pick(j, w0), pick(j, w1), pick(j, bin), unit);
            } while (over);
        }
        __syncwarp();
        am = am >= 0x30000u ? 0x10000u | h::PM : am + 0x10000u;
        kb ^= am & 0x30000u;
        TK(4)
    }
    rd.finish();
    TK_OUT
}

__device__ __forceinline__ float2 acc_fix(uint32_t old, uint32_t q) {
    const uint32_t u = old + 0x40004000u, n = u + q - 0x08000800u;
    return make_float2((float)((int)(u & 0xffffu) + (int)(q & 0xffffu) - 2048 - (int)(n & 0xffffu)), (float)((int)(u >> 16) + (int)(q >> 16) - 2048 - (int)(n >> 16)));
}
__device__ __forceinline__ void stage3(const Params& p, uint32_t sb, int w, int lane, int role, uint32_t base) {
    const int RT = p.rounds;
    Reader<2> rd;
    rd.init(p, sb, w, lane, role, base);
    uint2 rec[J];
    bar_sync(BAR_TABLE, 2 * NC * 32);
    TK_DECL
#pragma unroll 1
    for (int r = 0; r < RT; r++) {
        if (LAG) { const int need = min(r + 1, RT - 1); if ((int)lds32(sb + W_RND) < need) mbar_wait(sb + B_OPEN + 8, need & 1); }
        rd.load(rec);
        rd.check(rec, base + r, r < RT - 2 ? POLL_NS3 : 100 TK_PASS);
        TK(0)
        const uint32_t want = H<2>::tag(base + r), t = 0u - (lane & 1u), k = (t & 1u << 26) - (want >> 4);
        uint32_t o0[J], o1[J], g = 0;
#pragma unroll
        for (int j = 0; j < J; j++) {
            o0[j] = 0; o1[j] = 0;
            if (!xor_and<H<2>::TAG>(rec[j].y, want)) {
                const uint32_t a = aux_of(rec[j].x, rec[j].y, k);
                const uint32_t v0 = (rec[j].x & 0x0fff0fffu) - 0x08000800u, v1 = (rec[j].y & 0x0fff0fffu) - 0x08000800u;
                o0[j] = atoms_add<OFF_ACC>(sb + a, mux(v0, v1, t));
                o1[j] = atoms_add<OFF_ACC>(sb + (a ^ 4u), mux(v1, v0, t));
            }
        }
#pragma unroll
        for (int j = 0; j < J; j++) g |= o0[j] | o1[j];
        if (__any_sync(0xffffffffu, g & 0x80008000u)) {
#pragma unroll 1
            for (int j = 0; j < J; j++) {
                const uint2 w = pick(j, rec);
                const uint32_t aux = aux_of(w.x, w.y), p0 = pick(j, o0), p1 = pick(j, o1);
                const float2 a = acc_fix(t ? p1 : p0, w.x & 0x0fff0fffu), b = acc_fix(t ? p0 : p1, w.y & 0x0fff0fffu);
                const float unit = __uint_as_float(lds32(sb + W_UNIT));
                if (!((w.y ^ want) & H<2>::TAG) && (a.x != 0.f || a.y != 0.f || b.x != 0.f || b.y != 0.f))
                    side_add(lds32(sb + W_ROLE), aux >> 3, a.x * unit, a.y * unit, b.x * unit, b.y * unit);
                __syncwarp();
            }
        }
        TK(1)
    }
    rd.finish();
    TK_OUT
}

__device__ __forceinline__ uint32_t row_max(uint32_t x, uint32_t y) {
    const uint32_t mx = __vmaxu2(x & 0x7fff7fffu, y & 0x7fff7fffu);
    return max(mx & 0xffffu, mx >> 16);
}
constexpr int EWIN = 5;

__global__ void __launch_bounds__(NTHR, 1) fused_kernel(const Params p) {
    const int tid = threadIdx.x, lane = tid & 31;
    const int hw = __reduce_max_sync(0xffffffffu, tid >> 5);
    const uint32_t sb = __reduce_or_sync(0xffffffffu, (uint32_t)__cvta_generic_to_shared(smem));
    TKX(0)
    const uint32_t epoch = ld_rlx32(&g_base);
    uint32_t base = epoch & 31u;

    if (hw < NS1) {
        if (hw < NS1 - 1 || NPR == 1024) stage1<4>(p, sb, hw * 128 + lane, lane, base);
        else stage1<NPR / 32 - (NS1 - 1) * 4>(p, sb, hw * 128 + lane, lane, base);
        __threadfence();
        bar_arrive(BAR_DONE, (NS1 + NC + 2) * 32);
    } else if (hw == W_M1) {
        if (lane == 0) {
            if (sb & 255u) __trap();
            mbar_init(sb + B_FULL, NS1); mbar_init(sb + B_OPEN, 1); mbar_init(sb + B_FREE, 1);
        }
        base = __reduce_or_sync(0xffffffffu, base);
        if (lane == 0 && (base & 1u)) { mbar_arrive(sb + B_OPEN); mbar_arrive(sb + B_FREE); }
        for (int i = lane; i < NG + NDUM; i += 32) sts32(sb + OFF_CNT1 + i * 4, i < NG ? H<1>::init(base) + (i & 7) * 16 : DUMMY);
#pragma unroll 1
        for (int i = 0; i < 2; i++) fill<1>(sb + OFF_H1 + H<1>::win(base + i), lane, base + i);
        bar_arrive(BAR_S1, (NS1 + 1) * 32);
        bar_sync(BAR_PROBE, (2 * NC + 1) * 32);
        {
            const uint32_t raw = __ballot_sync(0xffffffffu, lane < 2 * NC && smem[OFF_PROBE + lane]), side = raw & 1u;
            uint32_t v = 0;
            if (lane < 2) asm volatile("atom.relaxed.gpu.global.add.u32 %0, [%1], %2;" : "=r"(v) : "l"(p.ring + M_CNT + lane * 4096), "r"(side ? 0x10000u : 1u) : "memory");
            const uint32_t mine = (side ? ~raw : raw) | 0x80000000u;
            if (lane == 2) asm volatile("atom.relaxed.gpu.global.cas.b32 %0, [%1], 0, %2;" : "=r"(v) : "l"(p.ring + M_PAR), "r"(mine) : "memory");
            bar_sync(BAR_HIST, (2 * NC + 1) * 32);
            uint32_t best = 0;
#pragma unroll 1
            for (int e = 11 + lane; e <= 230; e += 32) {
                uint32_t c = 0;
#pragma unroll
                for (int i = 0; i < EWIN; i++) c += lds32(sb + OFF_HIST + (e - i) * 4);
                best = max(best, c << 8 | (255 - e));
            }
            const uint32_t e = 255 - (__reduce_max_sync(0xffffffffu, best) & 255u);
            if (lane == 0) {
                const uint32_t role = side ? NB - 1 - (v >> 16) : v & 0xffffu;
                sts32(sb + W_ROLE, role); sts32(sb + W_SIDE, role < NLO ? 0u : role >= NHI ? 1u : side);
                sts32(sb + W_EXP, e); sts32(sb + W_UNIT, (e - 10) << 23); sts32(sb + W_END, (epoch | 31u) + 1u + (base + p.rounds) % 24u);
            }
            if (lane == 2) sts32(sb + W_PAR, v ? v : mine);
        }
        bar_sync(BAR_ROLE, (2 * NC + 2) * 32);
        manager<1>(p, sb, lane, __reduce_max_sync(0xffffffffu, lds32(sb + W_ROLE)), base);
        bar_arrive(BAR_H1, (NS1 + 1) * 32);
        __threadfence();
        bar_arrive(BAR_DONE, (NS1 + NC + 2) * 32);
    } else if (hw == W_M2) {
        const float wd = __bfloat162float(lane & 16 ? p.w_up[lane & 15] : p.w_down[lane & 15]);
        const float ws = __bfloat162float(p.w_sbf[lane]), wr = __bfloat162float(p.w_rbf[lane]);
        const __nv_bfloat16 cen = p.centers[lane & 7];
        if (lane == 0) { mbar_init(sb + B_FULL + 8, NC); mbar_init(sb + B_OPEN + 8, 1); }
        base = __reduce_or_sync(0xffffffffu, base);
        for (int i = lane; i <= NB + NDUM; i += 32) sts32(sb + OFF_CNT2 + i * 4, i < NB ? H<2>::init(base) + (i & 7) * 16 : DUMMY);
#pragma unroll 1
        for (int i = 0; i < 3; i++) fill<2>(sb + H<2>::win(i), lane, base + i);
        reinterpret_cast<float*>(smem + OFF_WSM)[lane] = wd;
        reinterpret_cast<float*>(smem + OFF_WG)[lane] = ws;
        reinterpret_cast<float*>(smem + OFF_WG + 128)[lane] = wr;
        reinterpret_cast<__nv_bfloat16*>(smem + OFF_WG + 256)[lane & 7] = cen;
        bar_sync(BAR_ROLE, (2 * NC + 2) * 32);
        manager<2>(p, sb, lane, __reduce_max_sync(0xffffffffu, lds32(sb + W_ROLE)), base);
        __threadfence();
        bar_sync(BAR_DONE, (NS1 + NC + 2) * 32);
        if (lane < 2) { __threadfence(); st_rlx32(reinterpret_cast<uint32_t*>(p.ring + M_FLAG + lane * 4096) + blockIdx.x, lds32(sb + W_END)); }
    } else {
        const int pw = __reduce_max_sync(0xffffffffu, hw < W_M1 ? hw - NS1 : hw - NS1 - 1), ct = pw * 32 + lane;
        constexpr int CT = 2 * NC * 32;
        const uint4 sm = __ldg(reinterpret_cast<const uint4*>(p.m) + min((ct >> 3) * (p.E >> 1) / (CT / 8) + (lane & 7), (p.E >> 1) - 1));
        if (ct < 256) sts32(sb + OFF_HIST + ct * 4, 0u);
        if (lane == 0) smem[OFF_PROBE + pw] = pw < NPAGE ? near_half(p.ring + (size_t)pw * PAGE + PROBE + (blockIdx.x & 31) * 128 + (blockIdx.x >> 5 & 3) * 16384 + (blockIdx.x >> 7 << 20), p.zero) : 0;
        TKX(1)
        bar_sync(BAR_PROBE, (2 * NC + 1) * 32);
        {
            const uint32_t m0 = row_max(sm.x, sm.y), m1 = row_max(sm.z, sm.w);
            if (m0) atoms_add<OFF_HIST>(sb + (m0 >> 7) * 4, 1u);
            if (m1) atoms_add<OFF_HIST>(sb + (m1 >> 7) * 4, 1u);
        }
        bar_arrive(BAR_HIST, (2 * NC + 1) * 32);
        base = __reduce_or_sync(0xffffffffu, base);
        for (int i = ct; i < R2MAX / 2; i += CT) reinterpret_cast<uint4*>(smem + OFF_ACC)[i] = make_uint4(0x40004000u, 0x40004000u, 0x40004000u, 0x40004000u);
        bar_sync(BAR_ROLE, (2 * NC + 2) * 32);
        const int role = __reduce_max_sync(0xffffffffu, lds32(sb + W_ROLE));
        TKX(2)
        {
            const int e = lds32(sb + W_EXP), q0 = (role >= NG ? role - NG : role) * (p.R1 >> 1), nq = min(p.R1 >> 1, (p.E >> 1) - q0);
            const uint32_t sc = (uint32_t)(254 - e) * 0x800080u;
            constexpr int CH = (R1MAX / 2 + CT - 1) / CT;
            uint4 v[CH];
#pragma unroll
            for (int u = 0; u < CH; u++) v[u] = __ldg(reinterpret_cast<const uint4*>(p.m) + min(q0 + ct + u * CT, (p.E >> 1) - 1));
            auto conv = [&](uint32_t& x, uint32_t& y) {
                const uint32_t mx = row_max(x, y);
                const int d = e - (int)(mx >> 7);
                x = hmul_bf2(x, sc); y = hmul_bf2(y, sc);
                if (d >= EWIN) y |= 0x40000000u;
                if (d < 0 || (d >= EWIN && e > 127)) { x = 0x40000000u; y = x; }
                if (mx == 0) { x = 0; y = 0; }
            };
#pragma unroll
            for (int u = 0; u < CH; u++) {
                conv(v[u].x, v[u].y); conv(v[u].z, v[u].w);
                if (ct + u * CT < nq) sts128<OFF_M>(sb + (ct + u * CT) * 16, v[u]);
            }
        }
        TKX(3)
        if (hw < W_M1) {
            stage2(p, sb, pw, lane, role, base);
            __threadfence();
            bar_arrive(BAR_DONE, (NS1 + NC + 2) * 32);
        } else {
            stage3(p, sb, pw - NC, lane, role, base);
            __threadfence();
        }
    }
    TKX(4)
    epilogue(p, sb);
}

__global__ void fb_scatter(const uint2* __restrict__ m, const int* __restrict__ idx_in, const int* __restrict__ idx_out,
                           const uint16_t* __restrict__ angle, const __nv_bfloat16* __restrict__ ang_freq, int T, int e0, int e1) {
    const uint32_t fb = *reinterpret_cast<const uint16_t*>(ang_freq);
    for (long long t = blockIdx.x * (long long)blockDim.x + threadIdx.x; t < T; t += (long long)gridDim.x * blockDim.x) {
        int o = idx_out[t];
        if (o < e0 || o >= e1) continue;
        float c = bf16r(cos_bf(hmul_bf2(angle[t], fb) & 0xffffu));
        uint2 v = __ldg(m + idx_in[t]);
        red4(&g_ovf[o - e0], c * bf_lo(v.x), c * bf_hi(v.x), c * bf_lo(v.y), c * bf_hi(v.y));
    }
}
__global__ void fb_final(const Params p, int e0, int e1) {
    int e = e0 + blockIdx.x * blockDim.x + threadIdx.x;
    if (e >= e1) return;
    float4 a4 = g_ovf[e - e0];
    g_ovf[e - e0] = make_float4(0.f, 0.f, 0.f, 0.f);
    float a[4] = {a4.x, a4.y, a4.z, a4.w};
    float d = __bfloat162float(p.dist[e]);
    float g[4] = {0, 0, 0, 0}, h[4] = {0, 0, 0, 0};
    for (int r = 0; r < 8; r++) {
        float df = bf16r(d - __bfloat162float(p.centers[r]));
        float rb = bf16r(expf(bf16r(-10.0f * bf16r(df * df))));
        for (int k = 0; k < 4; k++) {
            g[k] += rb * __bfloat162float(p.w_sbf[r * 4 + k]);
            h[k] += rb * __bfloat162float(p.w_rbf[r * 4 + k]);
        }
    }
    float ag[4];
    for (int k = 0; k < 4; k++) {
        float s = 0.f;
        for (int j = 0; j < 4; j++) s += a[j] * __bfloat162float(p.w_down[j * 4 + k]);
        ag[k] = bf16r(s * g[k]);
    }
    uint2 mv = p.m[e];
    float mm[4] = {bf_lo(mv.x), bf_hi(mv.x), bf_lo(mv.y), bf_hi(mv.y)};
    __nv_bfloat16 o[4];
    for (int k = 0; k < 4; k++) {
        float u = 0.f;
        for (int j = 0; j < 4; j++) u += ag[j] * __bfloat162float(p.w_up[j * 4 + k]);
        o[k] = __float2bfloat16_rn(mm[k] + bf16r(bf16r(u) * bf16r(h[k])));
    }
    p.out[e] = *reinterpret_cast<uint2*>(o);
}

}

static bool exact_div(int E, int lo, int hi, int* R, uint32_t* magic) {
    for (int r = lo + (lo & 1); r <= hi; r += 2) {
        unsigned long long mg = ((1ull << 32) + r - 1) / r, err = mg * r - (1ull << 32);
        if (err * (unsigned long long)E < (1ull << 32)) { *R = r; *magic = (uint32_t)mg; return true; }
    }
    return false;
}

extern "C" void kernel_launch(void* const* d_in, const int* in_sizes, int n_in, void* d_out, int out_size) {
    typedef const __nv_bfloat16* B;
    Params p;
    p.m = (const uint2*)d_in[0]; p.idx_in = (const uint2*)d_in[1]; p.idx_out = (const uint2*)d_in[2]; p.dist = (B)d_in[3];
    p.angle = (const uint32_t*)d_in[4]; p.centers = (B)d_in[5]; p.ang_freq = (B)d_in[6]; p.w_rbf = (B)d_in[7]; p.w_sbf = (B)d_in[8];
    p.w_down = (B)d_in[9]; p.w_up = (B)d_in[10]; p.out = (uint2*)d_out;
    p.E = in_sizes[3]; p.T = in_sizes[1]; p.T2 = p.T >> 1; p.zero = 0;
    p.R1 = p.R2 = p.rounds = p.lastn = p.qfull = 0; p.mg1 = p.mg2 = p.k1 = p.k2 = 0;
    static int ok = -1;
    static unsigned char* ring = nullptr;
    if (ok < 0) {
        void* ra = nullptr;
        cudaGetSymbolAddress(&ra, g_ring);
        ring = reinterpret_cast<unsigned char*>(((uintptr_t)ra + PAGE - 1) & ~(uintptr_t)(PAGE - 1));
        int dev = 0, sms = 0, occ = 0;
        cudaGetDevice(&dev);
        cudaDeviceGetAttribute(&sms, cudaDevAttrMultiProcessorCount, dev);
        cudaError_t e = cudaFuncSetAttribute(fused_kernel, cudaFuncAttributeMaxDynamicSharedMemorySize, SMEM_BYTES);
        if (e == cudaSuccess) e = cudaOccupancyMaxActiveBlocksPerMultiprocessor(&occ, fused_kernel, NTHR, SMEM_BYTES);
        ok = (e == cudaSuccess && occ >= 1 && sms >= NB) ? 1 : 0;
        (void)cudaGetLastError();
    }
    p.ring = ring;
    const bool fused = ok == 1 && p.E <= EMAX && p.E >= 2 * NB && p.E % 2 == 0 && p.T >= 2 && exact_div(p.E, (p.E + NG - 1) / NG, R1MAX, &p.R1, &p.mg1) &&
                       exact_div(p.E, (p.E + NB - 1) / NB, R2MAX, &p.R2, &p.mg2);
    if (fused) {
        p.k1 = 0u - (uint32_t)p.R1; p.k2 = 0u - 8u * (uint32_t)p.R2;
        const int per = NB * NPR;
        int full = p.T2 / per, rest = p.T2 - full * per;
        p.qfull = full * per;
        p.lastn = (rest + NB - 1) / NB;
        if (p.lastn > NPR / 2) { full++; p.lastn = 0; }
        if (full < D) { full = D; p.lastn = 0; }
        p.rounds = full + 1;
        fused_kernel<<<NB, NTHR, SMEM_BYTES>>>(p);
    } else {
        for (int e0 = 0; e0 < p.E; e0 += EMAX) {
            int e1 = p.E - e0 < EMAX ? p.E : e0 + EMAX;
            fb_scatter<<<1056, 256>>>(p.m, (const int*)d_in[1], (const int*)d_in[2], (const uint16_t*)d_in[4], p.ang_freq, p.T, e0, e1);
            fb_final<<<(e1 - e0 + 255) / 256, 256>>>(p, e0, e1);
        }
    }
}
```

```cpp
#include <cuda_runtime.h>
#include <cuda_bf16.h>
#include <stdint.h>

namespace {

constexpr int NB = 132, NG = 66;
constexpr int R2MAX = 6062, R1MAX = 12124;
constexpr int EMAX = NB * R2MAX;
constexpr int NTHR = 1024;
constexpr int NS1 = 8, NC = 11, J = 6;
#define TILES 30
#define DEFER 0
#define CSYNC 6
#define LDA 0x0000
#define LDO 0x0000
#define LDI 0x1111
#define G1 4
#define G3 6
#define CAP1 64
constexpr int NPR = TILES * 32;
constexpr int D = 3;
constexpr int WIN = 16896;
constexpr int NDUM = 16;
constexpr uint32_t DUMMY = 0xc0000000u;

constexpr int OFF_ACC = WIN, OFF_BAR = OFF_ACC + R2MAX * 8;
constexpr int OFF_H1 = 0x10000 + WIN, OFF_M = OFF_H1 + WIN, OFF_WSM = OFF_M + R1MAX * 8;
constexpr int OFF_CNT1 = OFF_H1 + 0x20000 + WIN, OFF_CNT2 = OFF_CNT1 + (NG + NDUM + 2) * 4, W_RND = OFF_CNT2 + (NB + NDUM) * 4, OFF_WG = W_RND + 16;
constexpr int OFF_HIST = OFF_M;
constexpr int OFF_PROBE = OFF_WSM + 128;
constexpr int SMEM_BYTES = OFF_WG + 272;
static_assert(SMEM_BYTES <= 232448 && OFF_BAR + 64 <= 0x10000 && OFF_PROBE + 32 <= 0x30000, "smem");
static_assert(OFF_BAR % 8 == 0 && OFF_WG % 16 == 0 && OFF_WSM % 16 == 0 && OFF_CNT2 % 16 == 0, "align");
static_assert(NC * J == NG && NC * 32 * 6 * 16 == 2 * WIN, "shape");

template <int HOP> struct H {
    static constexpr int S = HOP == 1 ? 32 : 16, NBIN = HOP == 1 ? NG : NB, CAP = HOP == 1 ? CAP1 : 32, SH = HOP == 1 ? 11 : 12;
    static constexpr int TB = HOP == 1 ? 20 : 28, CNT = HOP == 1 ? OFF_CNT1 : OFF_CNT2, STG = HOP == 1 ? OFF_H1 : 0;
    static constexpr uint32_t INC = (1u << SH) + 8u, PM = (S - 1) * 8, TAG = 7u << TB;
    static __device__ __forceinline__ uint32_t tag(uint32_t R) { return R << TB & TAG; }
    static __device__ __forceinline__ uint32_t init(uint32_t R) { return tag(R) | ((1u << TB) - 0x10000u); }
    static __device__ __forceinline__ uint32_t mark(uint32_t R, uint32_t line) { return ((HOP == 1 ? R >> 1 : R) + line) & 3u; }
    static __device__ __forceinline__ uint32_t win(int r) { return HOP == 1 ? (r & 1) << 17 : (0x310u >> (r % 3 * 4) & 3u) << 16; }
};

constexpr uint32_t PAGE = 1u << 21;
constexpr int NPAGE = NC + 2;
__device__ __align__(256) unsigned char g_ring[(size_t)(NPAGE + 1) * PAGE];
constexpr int MISC = 0xa0000;
constexpr int M_CNT = MISC + 1024, M_PAR = MISC + 1088;
constexpr int M_FLAG = MISC + 2048;
constexpr int PROBE = MISC + 0x40000;
#define CSTR 16384
__device__ __forceinline__ uint32_t cred_off(uint32_t role) { return role * 4 + min(role >> 5, 3u) * (CSTR - 128); }
struct Ring {
    uint64_t main, mid;
    uint32_t par;
    __device__ __forceinline__ Ring(const unsigned char* ring, uint32_t pars, int k) {
        main = reinterpret_cast<uint64_t>(ring) + ((uint64_t)k << 20);
        par = pars >> (k >> 1) & 1u;
        mid = reinterpret_cast<uint64_t>(ring) + (uint64_t)NC * PAGE + (((k >> 3 << 20) + (k >> 2 & 1) * 0x11000u + (k & 1) * 2048) ^ (k >> 1 & 1) * 0x3000u ^ (pars >> (NC + (k >> 4)) & 1u) << 12);
    }
};
constexpr int NLO = 60, NHI = 72;
__host__ __device__ constexpr uint32_t src_off(int j) { return (j % 3) << 14 | (j / 3) << 18; }
__device__ __forceinline__ uint32_t slot_off(uint32_t s) { return (0xa930u >> s * 4 & 15u) << 16; }
__device__ __forceinline__ uint32_t slot_steps(uint32_t R) { return (uint32_t)(0x30a09030aull >> (2 - R % 3) * 8) & 0xffffffu; }
__device__ __forceinline__ void slot_next(uint32_t& a, uint32_t st) { a ^= st & 0xf0000u; }
__device__ __forceinline__ uint32_t slot_rot(uint32_t st) { return __byte_perm(st, 0u, 0x4102); }
constexpr int RPAD = 6064, DROW = 6144;
__device__ __align__(128) uint8_t g_dirty[NB * DROW];
__device__ uint32_t g_base = 1;
__device__ __align__(128) float4 g_ovf[NB * RPAD];

struct Params {
    const uint2* m; const uint2* idx_in; const uint2* idx_out; const __nv_bfloat16* dist; const uint32_t* angle;
    const __nv_bfloat16* centers; const __nv_bfloat16* ang_freq; const __nv_bfloat16* w_rbf; const __nv_bfloat16* w_sbf;
    const __nv_bfloat16* w_down; const __nv_bfloat16* w_up; uint2* out; unsigned char* ring;
    int E, T, T2, R1, R2, rounds, lastn, qfull; uint32_t mg1, mg2, k1, k2, zero;
};

__device__ __forceinline__ float bf16r(float x) { return __bfloat162float(__float2bfloat16_rn(x)); }
__device__ __forceinline__ float bf_lo(uint32_t v) { return __uint_as_float(v << 16); }
__device__ __forceinline__ float bf_hi(uint32_t v) { return __uint_as_float(v & 0xffff0000u); }
__device__ __forceinline__ void red4(float4* a, float x, float y, float z, float w) {
    asm volatile("red.global.add.v4.f32 [%0], {%1,%2,%3,%4};" ::"l"(a), "f"(x), "f"(y), "f"(z), "f"(w) : "memory");
}
__device__ __forceinline__ void bar_sync(int id, int n) { __syncwarp(); asm volatile("bar.sync %0, %1;" ::"r"(id), "r"(n) : "memory"); }
__device__ __forceinline__ void bar_arrive(int id, int n) { __syncwarp(); asm volatile("bar.arrive %0, %1;" ::"r"(id), "r"(n) : "memory"); }
template <int OFF> __device__ __forceinline__ uint32_t atoms_add(uint32_t addr, uint32_t v) {
    uint32_t r; asm volatile("atom.shared.add.u32 %0, [%1+%3], %2;" : "=r"(r) : "r"(addr), "r"(v), "n"(OFF) : "memory"); return r;
}
__device__ __forceinline__ void sts64(uint32_t addr, uint32_t x, uint32_t y) {
    asm volatile("st.shared.v2.u32 [%0], {%1,%2};" ::"r"(addr), "r"(x), "r"(y) : "memory");
}
__device__ __forceinline__ void sts32(uint32_t addr, uint32_t x) { asm volatile("st.shared.u32 [%0], %1;" ::"r"(addr), "r"(x) : "memory"); }
template <int OFF = 0> __device__ __forceinline__ uint2 lds64(uint32_t addr) {
    uint2 v; asm volatile("ld.shared.v2.u32 {%0,%1}, [%2+%3];" : "=r"(v.x), "=r"(v.y) : "r"(addr), "n"(OFF) : "memory"); return v;
}
__device__ __forceinline__ uint32_t lds32(uint32_t addr) {
    uint32_t v; asm volatile("ld.shared.u32 %0, [%1];" : "=r"(v) : "r"(addr) : "memory"); return v;
}
__device__ __forceinline__ uint32_t ld_rlx32(const uint32_t* p) {
    uint32_t v; asm volatile("ld.relaxed.gpu.global.u32 %0, [%1];" : "=r"(v) : "l"(p) : "memory"); return v;
}
__device__ __forceinline__ uint2 ld_rlx64(const void* p) {
    uint2 v; asm volatile("ld.relaxed.gpu.global.v2.u32 {%0,%1}, [%2];" : "=r"(v.x), "=r"(v.y) : "l"(p) : "memory"); return v;
}
__device__ __forceinline__ float4 ld_rlx128f(const float4* p) {
    float4 v; asm volatile("ld.relaxed.gpu.global.v4.f32 {%0,%1,%2,%3}, [%4];" : "=f"(v.x), "=f"(v.y), "=f"(v.z), "=f"(v.w) : "l"(p) : "memory"); return v;
}
__device__ __forceinline__ void take3(float4* p, uint32_t mask, float4 (&v)[3]) {
    asm volatile("{ .reg .b128 a, b, c; .reg .b64 x, y; .reg .pred q0, q1, q2; .reg .b32 t;\n"
                 "mov.b64 x, 0; mov.b128 a, {x, x}; mov.b128 b, {x, x}; mov.b128 c, {x, x};\n"
                 "and.b32 t, %13, 1; setp.ne.u32 q0, t, 0; and.b32 t, %13, 2; setp.ne.u32 q1, t, 0; and.b32 t, %13, 4; setp.ne.u32 q2, t, 0;\n"
                 "@q0 atom.relaxed.gpu.global.exch.b128 a, [%12], a; @q1 atom.relaxed.gpu.global.exch.b128 b, [%12+16384], b;\n"
                 "@q2 atom.relaxed.gpu.global.exch.b128 c, [%12+32768], c;\n"
                 "mov.b128 {x, y}, a; mov.b64 {%0,%1}, x; mov.b64 {%2,%3}, y; mov.b128 {x, y}, b; mov.b64 {%4,%5}, x; mov.b64 {%6,%7}, y;\n"
                 "mov.b128 {x, y}, c; mov.b64 {%8,%9}, x; mov.b64 {%10,%11}, y; }"
                 : "=f"(v[0].x), "=f"(v[0].y), "=f"(v[0].z), "=f"(v[0].w), "=f"(v[1].x), "=f"(v[1].y), "=f"(v[1].z), "=f"(v[1].w),
                   "=f"(v[2].x), "=f"(v[2].y), "=f"(v[2].z), "=f"(v[2].w) : "l"(p), "r"(mask) : "memory");
}
__device__ __forceinline__ void st_rlx32(uint32_t* p, uint32_t v) { asm volatile("st.relaxed.gpu.global.u32 [%0], %1;" ::"l"(p), "r"(v) : "memory"); }
__device__ __forceinline__ uint32_t hmul_bf2(uint32_t a, uint32_t b) {
    uint32_t r; asm("mul.rn.bf16x2 %0, %1, %2;" : "=r"(r) : "r"(a), "r"(b)); return r;
}
__device__ __forceinline__ uint32_t hsub_bf2(uint32_t a, uint32_t b) {
    uint32_t r; asm("sub.rn.bf16x2 %0, %1, %2;" : "=r"(r) : "r"(a), "r"(b)); return r;
}
constexpr int SPIN_LIMIT = 1 << 22;

__constant__ uint32_t c_inv2pi[8] = {0u, 0x28be60dbu, 0x9391054au, 0x7f09d5f4u, 0x7d4d3770u, 0x36d8a566u, 0x4f10e410u, 0x7f9458eau};
constexpr uint32_t BIGX = 0x4280u;
__device__ __forceinline__ float cos_big(uint32_t xb) {
    uint32_t e = (xb >> 7) & 0xffu, M = (xb & 0x7fu) | 0x80u;
    uint32_t pp = e - 102u;
    uint32_t wi = pp >> 5;
    uint32_t t0 = c_inv2pi[wi], t1 = c_inv2pi[wi + 1], t2 = c_inv2pi[wi + 2];
    uint32_t f = M * __funnelshift_l(t1, t0, pp) + __umulhi(M, __funnelshift_l(t2, t1, pp));
    float c = __cosf((float)(int)f * 1.4629180792671596e-9f);
    return e == 255u ? __uint_as_float(0x7fc00000u) : c;
}
__device__ __forceinline__ float cos_bf(uint32_t xb) {
    return (xb & 0x7fffu) > BIGX ? cos_big(xb) : __cosf(__uint_as_float(xb << 16));
}
__device__ __forceinline__ uint32_t pack_bf2(float lo, float hi) {
    uint32_t r; asm("cvt.rn.bf16x2.f32 %0, %1, %2;" : "=r"(r) : "f"(hi), "f"(lo)); return r;
}
template <int N> __device__ __forceinline__ uint32_t pick(int k, const uint32_t (&a)[N]) {
    uint32_t v = a[0];
#pragma unroll
    for (int i = 1; i < N; i++) if (k == i) v = a[i];
    return v;
}
template <int N> __device__ __forceinline__ uint2 pick(int k, const uint2 (&a)[N]) {
    uint2 v = a[0];
#pragma unroll
    for (int i = 1; i < N; i++) if (k == i) v = a[i];
    return v;
}
__device__ __forceinline__ void side_add(uint32_t bin, uint32_t row, float a, float b, float c, float d) {
    red4(&g_ovf[bin * RPAD + row], a, b, c, d);
    g_dirty[bin * DROW + row] = 1;
}
__device__ __forceinline__ void slow_triplet(const Params& p, uint32_t ii, uint32_t oo, float c) {
    const uint2 v = __ldg(p.m + ii);
    const uint32_t bo = __umulhi(oo, p.mg2);
    side_add(bo, oo - bo * p.R2, c * bf_lo(v.x), c * bf_hi(v.x), c * bf_lo(v.y), c * bf_hi(v.y));
}
__device__ __forceinline__ void slow_rec1(const Params& p, uint32_t x, uint32_t y, uint32_t bin) {
    const uint2 v = __ldg(p.m + bin * p.R1 + (y & 0xffffu));
    const float c = bf_hi(y);
    side_add(x & 0xffu, __byte_perm(x, 0u, 0x4413) >> 3, c * bf_lo(v.x), c * bf_hi(v.x), c * bf_lo(v.y), c * bf_hi(v.y));
}
__device__ __forceinline__ uint32_t aux_of(uint32_t w0, uint32_t w1, uint32_t k = 0) {
    uint32_t u; asm("lop3.b32 %0, %1, %2, 0xf000f000, 0xe4;" : "=r"(u) : "r"(w0), "r"((w1 >> 4) + k));
    return __byte_perm(u, 0u, 0x4413);
}
__device__ __forceinline__ void slow_rec2(const Params& p, uint32_t w0, uint32_t w1, uint32_t bin, float unit) {
    side_add(bin, aux_of(w0, w1) >> 3, (float)((int)(w0 & 0xfffu) - 2048) * unit, (float)((int)(w0 >> 16 & 0xfffu) - 2048) * unit,
             (float)((int)(w1 & 0xfffu) - 2048) * unit, (float)((int)(w1 >> 16 & 0xfffu) - 2048) * unit);
}
template <uint32_t M> __device__ __forceinline__ uint32_t and_or(uint32_t a, uint32_t c) {
    uint32_t r; asm("lop3.b32 %0, %1, %2, %3, 0xea;" : "=r"(r) : "r"(a), "n"(M), "r"(c)); return r;
}
template <uint32_t M> __device__ __forceinline__ uint32_t xor_and(uint32_t a, uint32_t c) {
    uint32_t r; asm("lop3.b32 %0, %1, %2, %3, 0x48;" : "=r"(r) : "r"(a), "n"(M), "r"(c)); return r;
}
__device__ __forceinline__ uint32_t mux(uint32_t a, uint32_t b, uint32_t m) {
    uint32_t r; asm("lop3.b32 %0, %1, %2, %3, 0xd8;" : "=r"(r) : "r"(a), "r"(b), "r"(m)); return r;
}
__device__ __forceinline__ uint32_t and_xor(uint32_t a, uint32_t m, uint32_t c) {
    uint32_t r; asm("lop3.b32 %0, %1, %2, %3, 0x6a;" : "=r"(r) : "r"(a), "r"(m), "r"(c)); return r;
}
__device__ __forceinline__ uint2 ld_in(const uint2* a) {
    uint2 v; asm volatile("ld.global.nc.L1::no_allocate.v2.u32 {%0,%1}, [%2];" : "=r"(v.x), "=r"(v.y) : "l"(a)); return v;
}
__device__ __forceinline__ uint32_t ld_in(const uint32_t* a) {
    uint32_t v; asm volatile("ld.global.nc.L1::no_allocate.u32 %0, [%1];" : "=r"(v) : "l"(a)); return v;
}
template <int OFF> __device__ __forceinline__ void put_rec(uint32_t ret, uint32_t lim, uint32_t addr, uint32_t x, uint32_t y) {
    asm volatile("{ .reg .pred q; setp.lt.u32 q, %0, %1; @q st.shared.v2.u32 [%2+%5], {%3,%4}; }" ::"r"(ret), "r"(lim), "r"(addr), "r"(x), "r"(y), "n"(OFF) : "memory");
}
__device__ __forceinline__ uint32_t mbar_try(uint32_t mb, uint32_t parity) {
    uint32_t ok;
    asm volatile("{ .reg .pred q; mbarrier.try_wait.parity.shared::cta.b64 q, [%1], %2; selp.u32 %0, 1, 0, q; }" : "=r"(ok) : "r"(mb), "r"(parity) : "memory");
    return ok;
}
__device__ __forceinline__ void mbar_wait(uint32_t mb, uint32_t parity) {
    if (!mbar_try(mb, parity)) {
        int it = 0;
        while (!mbar_try(mb, parity)) if (++it > SPIN_LIMIT) __trap();
    }
}
__device__ __forceinline__ void mbar_init(uint32_t mb, uint32_t n) { asm volatile("mbarrier.init.shared::cta.b64 [%0], %1;" ::"r"(mb), "r"(n) : "memory"); }
__device__ __forceinline__ void mbar_arrive(uint32_t mb) { asm volatile("mbarrier.arrive.shared::cta.b64 _, [%0];" ::"r"(mb) : "memory"); }
constexpr int B_FULL = OFF_BAR, B_OPEN = OFF_BAR + 16, B_FREE = OFF_BAR + 32;
constexpr int W_END = OFF_BAR + 40, W_SIDE = OFF_BAR + 44, W_PAR = OFF_BAR + 48, W_ROLE = OFF_BAR + 52, W_EXP = OFF_BAR + 56, W_UNIT = OFF_BAR + 60;
enum { BAR_S1 = 1, BAR_PROBE, BAR_HIST, BAR_ROLE, BAR_TABLE, BAR_H1, BAR_DONE };
constexpr int W_M1 = NS1 + NC, W_M2 = 31;

extern __shared__ __align__(1024) unsigned char smem[];
#define TK_DECL
#define TK(i)
#define TK_CNT(i)
#define TK_OUT
#define TK_ARG
#define TK_PASS
#define TKX(i)
#define TKY(i)

constexpr int NR = (R2MAX + NTHR - 1) / NTHR;
__device__ __forceinline__ void gates(const Params& p, int e0, int e1, int e2, uint4* gh) {
    constexpr int NH = 3;
    const int e[NH] = {e0, e1, e2};
    uint32_t dd[NH];
    float g[NH][4], h[NH][4];
#pragma unroll
    for (int u = 0; u < NH; u++) {
        dd[u] = reinterpret_cast<const uint16_t*>(p.dist)[min(e[u], p.E - 1)] * 0x10001u;
#pragma unroll
        for (int k = 0; k < 4; k++) { g[u][k] = 0.f; h[u][k] = 0.f; }
    }
#pragma unroll 1
    for (int r2 = 0; r2 < 4; r2++) {
        const uint32_t cen = reinterpret_cast<const uint32_t*>(smem + OFF_WG + 256)[r2];
        uint32_t rb[NH];
#pragma unroll
        for (int u = 0; u < NH; u++) {
            const uint32_t df = hsub_bf2(dd[u], cen);
            const uint32_t ar = hmul_bf2(hmul_bf2(df, df), 0xc120c120u);
            rb[u] = pack_bf2(__expf(bf_lo(ar)), __expf(bf_hi(ar)));
        }
#pragma unroll
        for (int i = 0; i < 2; i++) {
            const float4 ws = reinterpret_cast<const float4*>(smem + OFF_WG)[r2 * 2 + i], wr = reinterpret_cast<const float4*>(smem + OFF_WG + 128)[r2 * 2 + i];
#pragma unroll
            for (int u = 0; u < NH; u++) {
                const float x = i ? bf_hi(rb[u]) : bf_lo(rb[u]);
                g[u][0] += x * ws.x; g[u][1] += x * ws.y; g[u][2] += x * ws.z; g[u][3] += x * ws.w;
                h[u][0] += x * wr.x; h[u][1] += x * wr.y; h[u][2] += x * wr.z; h[u][3] += x * wr.w;
            }
        }
    }
#pragma unroll
    for (int u = 0; u < NH; u++)
        gh[u] = make_uint4(pack_bf2(g[u][0], g[u][1]), pack_bf2(g[u][2], g[u][3]), pack_bf2(h[u][0], h[u][1]), pack_bf2(h[u][2], h[u][3]));
}
__device__ __forceinline__ void prefetch_l2(const void* a) { asm volatile("prefetch.global.L2 [%0];" ::"l"(a)); }
__device__ __forceinline__ uint4* gate_slot(int k) { return reinterpret_cast<uint4*>(smem + OFF_H1 + (k >= WIN / 16 ? 0x20000 - WIN : 0)) + k; }
__device__ __forceinline__ void wait_flags(const Params& p, uint32_t sb, int lane, uint32_t need) {
    const unsigned char* f = p.ring + M_FLAG + (lds32(sb + W_SIDE) << 12);
    int it = 0;
    while (true) {
        const float4 a = ld_rlx128f(reinterpret_cast<const float4*>(f) + lane);
        const uint32_t b = ld_rlx32(reinterpret_cast<const uint32_t*>(f) + 128 + (lane & 3));
        const uint32_t d = (__float_as_uint(a.x) ^ need) | (__float_as_uint(a.y) ^ need) | (__float_as_uint(a.z) ^ need) | (__float_as_uint(a.w) ^ need) | (b ^ need);
        if (__all_sync(0xffffffffu, d == 0)) break;
        __nanosleep(50);
        if (++it > SPIN_LIMIT) __trap();
    }
    __threadfence();
}
__device__ __forceinline__ void epilogue(const Params& p, uint32_t sb) {
    int tid;
    asm volatile("mov.u32 %0, %%tid.x;" : "=r"(tid));
    const int role = lds32(sb + W_ROLE), row0 = role * p.R2, nrows = min(p.R2, p.E - row0), hw = tid >> 5;
    const bool s3 = hw > W_M1 && hw < W_M2;
    constexpr int T3 = (W_M1 + 1) * 32, N3 = NC * 32;
    uint4 gh[NR];
    if (hw < NS1) {
        if (tid * 64 < nrows) prefetch_l2(p.dist + row0 + tid * 64);
        for (int i = tid * 16; i < nrows; i += NS1 * 32 * 16) prefetch_l2(p.m + row0 + i);
    }
    if (!s3) gates(p, row0 + tid + 3 * NTHR, row0 + tid + 4 * NTHR, row0 + tid + 5 * NTHR, gh + 3);
    if (hw < NS1) {
        bar_sync(BAR_H1, (NS1 + 1) * 32);
#pragma unroll 1
        for (int k0 = tid; k0 < NR * N3; k0 += 3 * NS1 * 32) {
            int k[3], e[3];
#pragma unroll
            for (int u = 0; u < 3; u++) { k[u] = k0 + u * NS1 * 32; e[u] = row0 + T3 + k[u] + k[u] / N3 * (NTHR - N3); }
            gates(p, e[0], e[1], e[2], gh);
#pragma unroll
            for (int u = 0; u < 3; u++) if (k[u] < NR * N3) *gate_slot(k[u]) = gh[u];
        }
#pragma unroll
        for (int i = tid; i < DROW / 8; i += NS1 * 32) {
            const uint2 f = ld_rlx64(g_dirty + role * DROW + i * 8);
            if (f.x | f.y) prefetch_l2(g_ovf + role * RPAD + i * 8);
        }
    }
    if (!s3) gates(p, row0 + tid, row0 + tid + NTHR, row0 + tid + 2 * NTHR, gh);
    if (hw == W_M1) wait_flags(p, sb, tid & 31, lds32(sb + W_END));
    TKX(5)
    bar_sync(0, NTHR);
    TKX(6)
    uint32_t dirty = 0;
#pragma unroll
    for (int it = 0; it < NR; it++) {
        uint32_t f;
        asm volatile("ld.relaxed.gpu.global.u8 %0, [%1];" : "=r"(f) : "l"(g_dirty + role * DROW + tid + it * NTHR) : "memory");
        dirty |= f << it;
    }
    if (s3) {
#pragma unroll
        for (int it = 0; it < NR; it++) gh[it] = *gate_slot(tid - T3 + it * N3);
    }
    if (hw == W_M1 && blockIdx.x == 0) {
        if (tid == W_M1 * 32) g_base = lds32(sb + W_END);
        if (tid < W_M1 * 32 + 3) *reinterpret_cast<uint32_t*>(p.ring + (tid & 2 ? M_PAR : M_CNT + (tid & 1) * 4096)) = 0;
    }
    const float unit = *reinterpret_cast<const float*>(smem + W_UNIT);
    const float4* w4 = reinterpret_cast<const float4*>(smem + OFF_WSM);
#pragma unroll
    for (int i0 = 0; i0 < NR; i0 += 3) {
        uint2 mv[3];
        float4 o[3];
#pragma unroll
        for (int u = 0; u < 3; u++) mv[u] = __ldg(p.m + min(row0 + tid + (i0 + u) * NTHR, p.E - 1));
        take3(&g_ovf[role * RPAD + tid + i0 * NTHR], dirty >> i0, o);
#pragma unroll
        for (int u = 0; u < 3; u++) {
            const int it = i0 + u, i = tid + it * NTHR;
            if (dirty >> it & 1) g_dirty[role * DROW + i] = 0;
            if (i < nrows) {
                const uint2 ac = reinterpret_cast<const uint2*>(smem + OFF_ACC)[i];
                const uint32_t u0 = ac.x + 0x40004000u, u1 = ac.y + 0x40004000u;
                const float a[4] = {(float)((int)(u0 & 0xffffu) - 0x8000) * unit + o[u].x, (float)((int)(u0 >> 16) - 0x8000) * unit + o[u].y,
                                    (float)((int)(u1 & 0xffffu) - 0x8000) * unit + o[u].z, (float)((int)(u1 >> 16) - 0x8000) * unit + o[u].w};
                float sd[4] = {0, 0, 0, 0}, uu[4] = {0, 0, 0, 0};
#pragma unroll
                for (int j = 0; j < 4; j++) {
                    float4 w = w4[j];
                    sd[0] += a[j] * w.x; sd[1] += a[j] * w.y; sd[2] += a[j] * w.z; sd[3] += a[j] * w.w;
                }
                const uint32_t a01 = pack_bf2(sd[0] * bf_lo(gh[it].x), sd[1] * bf_hi(gh[it].x)), a23 = pack_bf2(sd[2] * bf_lo(gh[it].y), sd[3] * bf_hi(gh[it].y));
                const float ag[4] = {bf_lo(a01), bf_hi(a01), bf_lo(a23), bf_hi(a23)};
#pragma unroll
                for (int j = 0; j < 4; j++) {
                    float4 w = w4[4 + j];
                    uu[0] += ag[j] * w.x; uu[1] += ag[j] * w.y; uu[2] += ag[j] * w.z; uu[3] += ag[j] * w.w;
                }
                const uint32_t t01 = hmul_bf2(pack_bf2(uu[0], uu[1]), gh[it].z);
                const uint32_t t23 = hmul_bf2(pack_bf2(uu[2], uu[3]), gh[it].w);
                uint2 q;
                asm("add.rn.bf16x2 %0, %1, %2;" : "=r"(q.x) : "r"(mv[u].x), "r"(t01));
                asm("add.rn.bf16x2 %0, %1, %2;" : "=r"(q.y) : "r"(mv[u].y), "r"(t23));
                p.out[row0 + i] = q;
            }
        }
        if (i0 == 0) { TKY(3) }
    }
}

template <int HOP> __device__ __forceinline__ uint2 null_rec(int lane, uint32_t R) {
    if (HOP == 1) return make_uint2(0x800000u | H<1>::tag(R), (OFF_CNT1 - OFF_M) / 8);
    return make_uint2(0x08000800u | lane << 28, 0x08000800u | H<2>::tag(R));
}
template <int OFF> __device__ __forceinline__ void sts128(uint32_t a, const uint4& v) {
    asm volatile("st.shared.v4.u32 [%0+%5], {%1,%2,%3,%4};" ::"r"(a), "r"(v.x), "r"(v.y), "r"(v.z), "r"(v.w), "n"(OFF) : "memory");
}
template <int HOP> __device__ __forceinline__ void fill(uint32_t win, int lane, uint32_t R) {
    const uint2 v = null_rec<HOP>(lane, R);
#pragma unroll 11
    for (int i = 0; i < WIN / 512; i++) sts128<0>(win + lane * 16 + i * 512, make_uint4(v.x, v.y, v.x, v.y));
}
template <int HOP> __device__ __forceinline__ void reset(uint32_t win, int lane, uint32_t R) {
    const uint2 v = null_rec<HOP>(lane, R);
    const uint32_t a = win + lane * 32 + H<HOP>::mark(R, lane >> 2) * 8;
#pragma unroll
    for (int i = 0; i < 16; i++) sts64(a + i * 1024, v.x, v.y);
    if (lane < 16) sts64(a + 16384, v.x, v.y);
}
__device__ __forceinline__ bool elect() {
    uint32_t q; asm volatile("{ .reg .pred q; elect.sync _|q, 0xffffffff; selp.u32 %0, 1, 0, q; }" : "=r"(q)); return q;
}
__device__ __forceinline__ const unsigned char* mk_ptr(uint32_t lo, uint32_t hi) { return reinterpret_cast<const unsigned char*>((uint64_t)hi << 32 | lo); }
__device__ __forceinline__ void bulk_store(uint32_t lo, uint32_t hi, uint32_t src, uint32_t n) {
    asm volatile("cp.async.bulk.global.shared::cta.bulk_group [%0], [%1], %2;" ::"l"(mk_ptr(lo, hi)), "r"(src), "r"(n) : "memory");
}
#define CRED_NS 100
#define CRED_SKIP 1
#define LAG 0
template <int HOP>
__device__ __forceinline__ void manager(const Params& p, uint32_t sb, int lane, int role, uint32_t base) {
    typedef H<HOP> h;
    constexpr int V = h::NBIN / 32, PB = h::S * 8;
    const int RT = p.rounds, lo = HOP == 1 && role >= NG ? NG : 0, hi = lo + h::NBIN;
    const int w = (role - lo) / (HOP * J), j = (role - lo - w * HOP * J) / HOP;
    const Ring rg(p.ring, __reduce_or_sync(0xffffffffu, lds32(sb + W_PAR)), 2 * w + HOP - 1);
    const uint32_t side = lds32(sb + W_SIDE), dhi = rg.main >> 32, mhi = rg.mid >> 32;
    const uint32_t c0 = HOP == 2 ? role & 1 : 0, up = (HOP == 1 && lo) ^ rg.par ^ c0;
    uint32_t dA = ((uint32_t)rg.main + src_off(j) + (c0 << 16) + (up ? 4096 : 12288)) ^ slot_off(base % 3);
    uint32_t dM = ((uint32_t)rg.mid + src_off(j) + c0 * 1024) ^ slot_off(base % 3);
    const int a0 = max(64, lo), b1 = min(68, hi);
    int n0 = (min(NHI, hi) - a0) * PB, a1 = (max(NLO, lo) - lo) * PB;
    const unsigned char* cr = reinterpret_cast<const unsigned char*>(rg.main) + MISC + ((side ^ rg.par) << 12);
    const unsigned char* cr0 = cr + cred_off(lo + lane * V), *cr1 = cr + cred_off(lo + 32 * V + min(lane, V - 1));
    const uint32_t ca0 = sb + h::CNT + lane * V * 4, ca1 = sb + h::CNT + (32 * V + min(lane, V + NDUM)) * 4;
    const uint32_t rot0 = (lane * V & 7) * 16, rot1 = lane * 16;
    uint32_t st = slot_steps(base);
    uint32_t init = h::init(base), prim = sb + h::STG + (HOP == 1 ? h::win(base) : 0u);
    uint32_t cs[5];
    auto sample = [&]() {
        if (V == 2) asm volatile("ld.relaxed.gpu.global.v2.u32 {%0,%1}, [%2];" : "=r"(cs[0]), "=r"(cs[1]) : "l"(cr0) : "memory");
        else asm volatile("ld.relaxed.gpu.global.v4.u32 {%0,%1,%2,%3}, [%4];" : "=r"(cs[0]), "=r"(cs[1]), "=r"(cs[2]), "=r"(cs[3]) : "l"(cr0) : "memory");
        cs[V] = ld_rlx32(reinterpret_cast<const uint32_t*>(cr1));
    };
    sample();
    uint32_t c[5];
    TK_DECL
#pragma unroll 1
    for (int r = 0;; r++) {
        const uint32_t R = base + r, ninit = h::init(R + 1), done = prim;
        TK(5)
        mbar_wait(sb + B_FULL + (HOP - 1) * 8, r & 1);
        TK(0)
        if (V == 2) asm volatile("ld.shared.v2.u32 {%0,%1}, [%2];" : "=r"(c[0]), "=r"(c[1]) : "r"(ca0) : "memory");
        else asm volatile("ld.shared.v4.u32 {%0,%1,%2,%3}, [%4];" : "=r"(c[0]), "=r"(c[1]), "=r"(c[2]), "=r"(c[3]) : "r"(ca0) : "memory");
        c[V] = lds32(ca1);
        uint32_t nc[5];
#pragma unroll
        for (int k = 0; k <= V; k++) {
            const uint32_t z = ninit + (k < V ? rot0 + k * 16 : rot1);
            nc[k] = min(max(c[k] + (ninit - init - h::S * h::INC), z), z + (h::CAP - h::S) * h::INC);
        }
        if (V == 2) sts64(ca0, nc[0], nc[1]); else sts128<0>(ca0, make_uint4(nc[0], nc[1], nc[2], nc[3]));
        sts32(ca1, lane < V ? nc[V] : lane < V + NDUM ? DUMMY : r);
        __syncwarp();
        if (lane == 0) mbar_arrive(sb + B_OPEN + (HOP - 1) * 8);
        TK(1)
        TK(2)
        asm volatile("fence.proxy.async.shared::cta;" ::: "memory");
        TK(6)
        if (r >= D) {
            int it = 0;
            while (true) {
                uint32_t bad = 0;
#pragma unroll
                for (int k = 0; k <= V; k++) bad |= cs[k] - (R - D + 1);
                if (!__any_sync(0xffffffffu, bad >> 20)) break;
                if (++it > SPIN_LIMIT) __trap();
                if (it > CRED_SKIP) __nanosleep(CRED_NS);
                sample();
            }
        }
        TK(3)
        if (elect()) {
            const uint32_t dB = (HOP == 1 ? dA ^ 0x10000u : dA) + (up ? 8192 : -8192), sm = prim + (lo ? 2 * PB : 0);
            bulk_store(dA, dhi, sm, 8192);
            bulk_store(dB, dhi, HOP == 1 ? sm + 8192 : prim + 68 * PB, 8192);
            if (n0 > 0) bulk_store(dM + (a0 - 64) * PB, mhi, prim + (a0 - lo) * PB, n0);
            if (a1 < (b1 - lo) * PB) bulk_store((dM ^ 4096u) + (uint32_t)((lo - NLO) * PB + a1), mhi, prim + a1, (b1 - lo) * PB - a1);
            asm volatile("cp.async.bulk.commit_group;" ::: "memory");
            asm volatile("cp.async.bulk.wait_group.read 0;" ::: "memory");
        }
        __syncwarp();
        TK(4)
        prim = HOP == 1 ? prim ^ 0x20000u : prim >= sb + 0x30000u ? sb : prim + (prim - sb) + 0x10000u;
        if (r == RT - 1) break;
        reset<HOP>(done, lane, R + HOP + 1);
        if (HOP == 1) {
            __syncwarp();
            if (lane == 0) mbar_arrive(sb + B_FREE);
        }
        if (r == D - 1 || r == RT - D - 1) {
            uint32_t n = NHI, m = NLO;
            if (r < RT - D - 1) {
                int it = 0;
                while (true) {
                    n = ld_rlx32(reinterpret_cast<const uint32_t*>(p.ring + M_CNT + (side << 12)));
                    if ((n & 0xffffu) + (n >> 16) == NB) break;
                    if (++it > SPIN_LIMIT) __trap();
                }
                m = n = min(max(__reduce_or_sync(0xffffffffu, n) & 0xffffu, (uint32_t)NLO), (uint32_t)NHI);
            }
            n0 = (min((int)n, hi) - a0) * PB;
            a1 = (max((int)m, lo) - lo) * PB;
        }
        sample();
        slot_next(dA, st); slot_next(dM, st);
        st = slot_rot(st);
        init = ninit;
    }
#pragma unroll 1
    for (int k = 0; k <= V; k++) {
        const uint32_t bin = k < V ? lane * V + k : 32 * V + lane, n = bin < h::NBIN ? min((pick(k, c) - init) >> h::SH, (uint32_t)h::CAP) : 0u;
#pragma unroll 1
        for (uint32_t x = h::S; x < n; x++) {
            const uint2 w = lds64(prim + bin * PB + ((x + (bin & 7) * 2) & (h::S - 1)) * 8);
            if (HOP == 1) slow_rec1(p, w.x, w.y, bin);
            else slow_rec2(p, w.x, w.y, bin, __uint_as_float(lds32(sb + W_UNIT)));
        }
    }
    asm volatile("cp.async.bulk.wait_group 0;" ::: "memory");
    TK_OUT
}

#define POLL_NS 200
#define POLL_NS3 1500
template <int HOP> struct Reader {
    uint32_t lo, hi, st, line;
    uint32_t* cred;
    __device__ __forceinline__ void init(const Params& p, uint32_t sb, int w, int lane, int role, uint32_t base) {
        constexpr int PB = H<HOP>::S * 8;
        const int first = HOP == 1 ? (role >= NG ? NG : 0) + w * J : w * 2 * J;
        const Ring rg(p.ring, lds32(sb + W_PAR), 2 * w + HOP - 1);
        const uint32_t side = lds32(sb + W_SIDE);
        const bool mid = side ? role < 68 : role >= 64;
        const uint32_t i = role - (side ? (mid ? NLO : 68) : (mid ? 64 : 0));
        const uint32_t c = HOP == 1 ? i >> 5 : lane >> 4, in = HOP == 1 ? (i & 31) * PB + lane * 8 : i * PB + (lane & 15) * 8;
        lo = (in + (mid ? ((uint32_t)rg.mid ^ side << 12) + c * 1024 : (uint32_t)rg.main + (c << 16) + (side ^ rg.par ^ c ? 4096 : 12288))) ^ slot_off(base % 3);
        hi = __reduce_or_sync(0xffffffffu, (uint32_t)((mid ? rg.mid : rg.main) >> 32));
        st = slot_steps(base);
        line = HOP == 1 ? 2 * (role % NG) : role;
        const bool both = first >= NLO && first < NHI;
        cred = lane < 1 + both ? reinterpret_cast<uint32_t*>(rg.main + MISC + (((both ? lane : first >= NG) ^ rg.par) << 12) + cred_off(role)) : nullptr;
    }
    template <int K> __device__ __forceinline__ void load1(uint2& v) const {
        asm volatile("ld.relaxed.gpu.global.v2.u32 {%0,%1}, [%2+%3];" : "=r"(v.x), "=r"(v.y) : "l"(mk_ptr(lo, hi)), "n"(src_off(K)) : "memory");
    }
    template <int K> __device__ __forceinline__ void again(uint2& v, uint32_t want, uint32_t mask) const {
        if (__ballot_sync(0xffffffffu, xor_and<H<HOP>::TAG>(HOP == 1 ? v.x : v.y, want)) & mask) load1<K>(v);
    }
    __device__ __forceinline__ void load(uint2 (&rec)[J]) const {
        load1<0>(rec[0]); load1<1>(rec[1]); load1<2>(rec[2]); load1<3>(rec[3]); load1<4>(rec[4]); load1<5>(rec[5]);
    }
    __device__ __forceinline__ void check(uint2 (&rec)[J], uint32_t R, uint32_t ns TK_ARG) {
        const uint32_t want = H<HOP>::tag(R);
        const uint32_t mask = 0x1111u << H<HOP>::mark(R, line) | 0x11110000u << H<HOP>::mark(R, line + 2 - HOP);
        int it = 0;
        while (true) {
            uint32_t bad = 0;
#pragma unroll
            for (int j = 0; j < J; j++) bad |= (HOP == 1 ? rec[j].x : rec[j].y) ^ want;
            if (!(__ballot_sync(0xffffffffu, bad & H<HOP>::TAG) & mask)) break;
            if (++it > SPIN_LIMIT) __trap();
            __nanosleep(ns);
            TK_CNT(7)
            again<0>(rec[0], want, mask); again<1>(rec[1], want, mask); again<2>(rec[2], want, mask);
            again<3>(rec[3], want, mask); again<4>(rec[4], want, mask); again<5>(rec[5], want, mask);
        }
        if (cred) st_rlx32(cred, R + 1);
        if (CSYNC >> HOP & 1) __syncwarp();
        slot_next(lo, st);
        st = slot_rot(st);
    }
    __device__ __forceinline__ void finish() const { if (cred) st_rlx32(cred, 0u); }
};

#define NPROBE 9
__device__ __forceinline__ uint32_t near_half(unsigned char* pair, uint32_t zero) {
#pragma unroll
    for (int i = 0; i < 4; i++) *reinterpret_cast<uint4*>(pair + (i >> 1) * 4096 + (i & 1) * 16) = make_uint4(0u, 0u, 0u, 0u);
    uint32_t best[2] = {~0u, ~0u}, v = 0, prev = 0;
    asm volatile("red.relaxed.gpu.global.add.u32 [%0], 1;" ::"l"(pair + 4096) : "memory");
#pragma unroll
    for (int t = 0; t <= NPROBE; t++) {
        uint32_t now;
        asm volatile("atom.relaxed.gpu.global.add.u32 %0, [%1], 1;" : "=r"(v) : "l"(pair + (t & 1) * 4096 + (v & zero)) : "memory");
        asm volatile("mov.u32 %0, %%clock;" : "=r"(now) :: "memory");
        if (t > 1) best[(t - 1) & 1] = min(best[(t - 1) & 1], now - prev);
        prev = now;
    }
    return (best[1] < best[0] ? 1u : 0u) | (v & zero);
}
template <bool B> struct BoolC { static constexpr bool value = B; };

template <int NP>
__device__ __forceinline__ void stage1(const Params& p, uint32_t sb, const int pos0, int lane, uint32_t base) {
    typedef H<1> h;
    const int RT = p.rounds;
    uint32_t ff = *reinterpret_cast<const uint16_t*>(p.ang_freq) * 0x10001u;
    auto pair_of = [&](int r, int pos) {
        const int q = r < RT - 1 ? (r * NB + blockIdx.x) * NPR + pos : (RT - 1) * NB * NPR + blockIdx.x * p.lastn + pos;
        return (r < RT - 1 || (r == RT - 1 && pos < p.lastn)) && q < p.T2 ? q : -1;
    };
    uint2 vi[NP], vo[NP]; uint32_t va[NP];
    auto load_edge = [&](int r) {
#pragma unroll
        for (int u = 0; u < NP; u++) {
            const int q = max(pair_of(r, pos0 + u * 32), 0);
            vi[u] = ld_in(p.idx_in + q); vo[u] = ld_in(p.idx_out + q); va[u] = ld_in(p.angle + q);
        }
    };
    load_edge(0);
    if (blockIdx.x == 0 && pos0 == 0 && (p.T & 1)) {
        const int t = p.T - 1;
        slow_triplet(p, reinterpret_cast<const uint32_t*>(p.idx_in)[t], reinterpret_cast<const uint32_t*>(p.idx_out)[t],
                     bf16r(cos_bf(hmul_bf2(reinterpret_cast<const uint16_t*>(p.angle)[t], ff) & 0xffffu)));
    }
    for (int i = threadIdx.x * 16; i < p.R2 && blockIdx.x * p.R2 + i < p.E; i += NS1 * 32 * 16) prefetch_l2(p.m + blockIdx.x * p.R2 + i);
    uint32_t R = __reduce_or_sync(0xffffffffu, base);
    ff = __reduce_or_sync(0xffffffffu, ff);
    bar_sync(BAR_S1, (NS1 + 1) * 32);
    TK_DECL
    auto step = [&](const int r, const int qn, auto edge) {
        constexpr bool EDGE = decltype(edge)::value;
        uint32_t cc[NP], big = 0;
#pragma unroll
        for (int u = 0; u < NP; u++) {
            va[u] = hmul_bf2(va[u], ff);
            cc[u] = pack_bf2(__cosf(bf_lo(va[u])), __cosf(bf_hi(va[u])));
            big = __vmaxu2(big, va[u] & 0x7fff7fffu);
        }
        if ((big + (0x7fffu - BIGX) * 0x10001u) & 0x80008000u) {
#pragma unroll 1
            for (int u = 0; u < NP; u++) {
                const uint32_t a = pick(u, va);
                float c0 = cos_bf(a & 0xffffu), c1 = cos_bf(a >> 16);
                if ((c0 != c0 || c1 != c1) && (!EDGE || pair_of(r, pos0 + u * 32) >= 0)) {
                    const uint2 i2 = pick(u, vi), o2 = pick(u, vo);
                    if (c0 != c0) slow_triplet(p, i2.x, o2.x, c0);
                    if (c1 != c1) slow_triplet(p, i2.y, o2.y, c1);
                }
                const uint32_t v = pack_bf2(c0 != c0 ? 0.f : c0, c1 != c1 ? 0.f : c1);
#pragma unroll
                for (int k = 0; k < NP; k++) if (k == u) cc[k] = v;
            }
        }
        uint32_t bin[2 * NP], x[2 * NP], y[2 * NP];
        uint32_t dep = 0;
        auto loads = [&](int at) {
            const int q = qn + (dep & p.zero);
#pragma unroll
            for (int u = 0; u < NP; u++) if (min((LDA >> u * 4) & 15, (2 * NP + G1 - 1) / G1) == at) va[u] = ld_in(p.angle + q + u * 32);
#pragma unroll
            for (int u = 0; u < NP; u++) if (min((LDO >> u * 4) & 15, (2 * NP + G1 - 1) / G1) == at) vo[u] = ld_in(p.idx_out + q + u * 32);
#pragma unroll
            for (int u = 0; u < NP; u++) if (min((LDI >> u * 4) & 15, (2 * NP + G1 - 1) / G1) == at) vi[u] = ld_in(p.idx_in + q + u * 32);
        };
#pragma unroll
        for (int j = 0; j < 2 * NP; j++) {
            const uint32_t ii = j & 1 ? vi[j >> 1].y : vi[j >> 1].x, oo = j & 1 ? vo[j >> 1].y : vo[j >> 1].x;
            bin[j] = __umulhi(ii, p.mg1);
            y[j] = __byte_perm(bin[j] * p.k1 + ii, cc[j >> 1], j & 1 ? 0x7610 : 0x5410);
            const uint32_t bo = __umulhi(oo, p.mg2);
            x[j] = __byte_perm(bo * p.k2 + oo * 8u, bo, 0x0514);
            dep |= x[j] | y[j];
            if (EDGE && pair_of(r, pos0 + (j >> 1) * 32) < 0) bin[j] = NG + (lane & (NDUM - 1));
        }
        if (EDGE) load_edge(r + 1);
        else loads(0);
        const uint32_t init = h::init(R), kb = sb + h::win(R + 1), lim = init + (h::CAP << h::SH);
        TK(0)
        mbar_wait(sb + B_OPEN, ~R & 1);
        TK(1)
        bool freed = false;
        uint32_t over = 0;
#pragma unroll
        for (int g = 0; g < 2 * NP; g += G1) {
            constexpr int G = G1;
            uint32_t ret[G];
            int mx = 0;
#pragma unroll
            for (int j = 0; j < G; j++) if (g + j < 2 * NP) ret[j] = atoms_add<h::CNT>(sb + bin[g + j] * 4, h::INC);
#pragma unroll
            for (int j = 0; j < G; j++) if (g + j < 2 * NP) mx = j ? max(mx, (int)ret[j]) : (int)ret[j];
            if (!DEFER && !freed && __any_sync(0xffffffffu, mx >= (int)(init + 0x10000u))) { TK(2) mbar_wait(sb + B_FREE, ~R & 1); freed = true; TK(3) }
            TK(2)
#pragma unroll
            for (int j = 0; j < G; j++) if (g + j < 2 * NP) {
                x[g + j] = and_or<h::TAG>(ret[j], x[g + j]);
                if (DEFER) {
                    bin[g + j] = and_xor(EDGE ? ret[j] | (ret[j] >> 14 & 0x20000u) : ret[j], 0x20000u | h::PM, bin[g + j] * 256 + kb);
                    put_rec<h::STG>(ret[j], init + 0x10000u, bin[g + j], x[g + j], y[g + j]);
                } else put_rec<h::STG>(ret[j], lim, and_xor(ret[j], 0x20000u | h::PM, bin[g + j] * 256 + kb), x[g + j], y[g + j]);
            }
            if (mx >= (int)lim) {
#pragma unroll
                for (int j = 0; j < G; j++) if (g + j < 2 * NP && (int)ret[j] >= (int)lim) { over |= 1u << (g + j); if (DEFER) bin[g + j] = mux(bin[g + j], ~kb, 0x20000u); }
            }
            if (!EDGE) { dep = mx; loads(g / G1 + 1); }
        }
        if (!DEFER || !EDGE) { __syncwarp(); if (elect()) mbar_arrive(sb + B_FULL); }
        if (DEFER) {
            TK(4)
            mbar_wait(sb + B_FREE, ~R & 1);
            TK(3)
#pragma unroll
            for (int j = 0; j < 2 * NP; j++) put_rec<h::STG>(xor_and<0x20000u>(bin[j], kb), 1u, bin[j], x[j], y[j]);
            if (EDGE) { __syncwarp(); if (elect()) mbar_arrive(sb + B_FULL); }
        }
        R++;
        TK(4)
#pragma unroll 1
        while (over) {
            TK_CNT(7)
            const int j = __ffs(over) - 1;
            over &= over - 1;
            slow_rec1(p, pick(j, x), pick(j, y), DEFER ? (pick(j, bin) - sb) >> 8 & 0xffu : pick(j, bin));
        }
        __syncwarp();
    };
#pragma unroll 1
    for (int q = (NB + blockIdx.x) * NPR; q < p.qfull; q += NB * NPR) step(q / (NB * NPR) - 1, q + pos0, BoolC<false>());
#pragma unroll 1
    for (int r = max(p.qfull / (NB * NPR) - 1, 0); r < RT; r++) step(r, 0, BoolC<true>());
    TK_OUT
}

__device__ __forceinline__ void stage2(const Params& p, uint32_t sb, int w, int lane, int role, uint32_t base) {
    typedef H<2> h;
    const int RT = p.rounds;
    Reader<1> rd;
    rd.init(p, sb, w, lane, role, base);
    uint2 rec[J];
    rd.load(rec);
    bar_sync(BAR_TABLE, 2 * NC * 32);
    uint32_t kb = sb + 0x10000u, am = 0x10000u | h::PM;
    const float unit = __uint_as_float(__reduce_or_sync(0xffffffffu, lds32(sb + W_UNIT)));
    TK_DECL
#pragma unroll 1
    for (int r = 0; r < RT; r++) {
        rd.check(rec, base + r, POLL_NS TK_PASS);
        const uint32_t want = H<1>::tag(base + r);
        TK(0)
        uint2 mv[J];
#pragma unroll
        for (int j = 0; j < J; j++) mv[j] = lds64<OFF_M>(sb + (rec[j].y & 0xffffu) * 8);
        uint32_t fl = 0;
#pragma unroll
        for (int j = 0; j < J; j++) fl |= mv[j].y;
        if (fl & 0x40000000u) {
#pragma unroll 1
            for (int j = 0; j < J; j++) {
                const uint2 v = pick(j, mv), w = pick(j, rec);
                if ((v.y & 0x40000000u) && !((w.x ^ want) & 0xf00000u)) {
                    if (v.x & 0x40000000u) slow_rec1(p, w.x, w.y, lds32(sb + W_ROLE) % NG);
                    else {
                        const float c = bf_hi(w.y), s = __uint_as_float(lds32(sb + W_UNIT)) * 1024.f;
                        side_add(w.x & 0xffu, __byte_perm(w.x, 0u, 0x4413) >> 3, c * (bf_lo(v.x) * s), c * (bf_hi(v.x) * s),
                                 c * (bf_lo(v.y) * s), c * (bf_hi(v.y & 0xbfffffffu) * s));
                    }
                }
            }
#pragma unroll
            for (int j = 0; j < J; j++) if (mv[j].y & 0x40000000u) rec[j].x = 0x800000u;
        }
        uint32_t w0[J], w1[J], bin[J], ret[J];
#pragma unroll
        for (int j = 0; j < J; j++) {
            const float c = bf_hi(rec[j].y), MG = 8194.0f;
            const uint32_t x = rec[j].x;
            w0[j] = and_or<0xf000f000u>(x, __byte_perm(__float_as_uint(fmaf(c, bf_lo(mv[j].x), MG)), __float_as_uint(fmaf(c, bf_hi(mv[j].x), MG)), 0x5410));
            w1[j] = and_or<0xf000f000u>(x << 4, __byte_perm(__float_as_uint(fmaf(c, bf_lo(mv[j].y), MG)), __float_as_uint(fmaf(c, bf_hi(mv[j].y), MG)), 0x5410));
            bin[j] = min(xor_and<0xf000ffu>(x, want), NB + (lane & (NDUM - 1)));
        }
        const uint32_t lim = h::init(base + r) + 0x20000u;
        rd.load(rec);
        TK(1)
        mbar_wait(sb + B_OPEN + 8, (r - 1) & 1);
        TK(2)
#pragma unroll
        for (int j = 0; j < J; j++) ret[j] = atoms_add<h::CNT>(sb + bin[j] * 4, h::INC);
        uint32_t mx = 0;
#pragma unroll
        for (int j = 0; j < J; j++) {
            w1[j] = and_or<h::TAG>(ret[j], w1[j]);
            put_rec<0>(ret[j], lim, and_xor(ret[j], am, bin[j] * 128 + kb), w0[j], w1[j]);
            mx = __viaddmax_u32(ret[j], 0u - DUMMY, mx);
        }
        __syncwarp();
        if (lane == 0) mbar_arrive(sb + B_FULL + 8);
        TK(3)
        if (mx >= lim - DUMMY) {
            uint32_t over = 0;
#pragma unroll
            for (int j = 0; j < J; j++) if (ret[j] - DUMMY >= lim - DUMMY) over |= 1u << j;
#pragma unroll 1
            do {
                const int j = __ffs(over) - 1;
                over &= over - 1;
                slow_rec2(p, pick(j, w0), pick(j, w1), pick(j, bin), unit);
            } while (over);
        }
        __syncwarp();
        am = am >= 0x30000u ? 0x10000u | h::PM : am + 0x10000u;
        kb ^= am & 0x30000u;
        TK(4)
    }
    rd.finish();
    TK_OUT
}

__device__ __forceinline__ float2 acc_fix(uint32_t old, uint32_t q) {
    const uint32_t u = old + 0x40004000u, n = u + q - 0x08000800u;
    return make_float2((float)((int)(u & 0xffffu) + (int)(q & 0xffffu) - 2048 - (int)(n & 0xffffu)), (float)((int)(u >> 16) + (int)(q >> 16) - 2048 - (int)(n >> 16)));
}
__device__ __forceinline__ void stage3(const Params& p, uint32_t sb, int w, int lane, int role, uint32_t base) {
    const int RT = p.rounds;
    Reader<2> rd;
    rd.init(p, sb, w, lane, role, base);
    uint2 rec[J];
    bar_sync(BAR_TABLE, 2 * NC * 32);
    TK_DECL
#pragma unroll 1
    for (int r = 0; r < RT; r++) {
        if (LAG) { const int need = min(r + 1, RT - 1); if ((int)lds32(sb + W_RND) < need) mbar_wait(sb + B_OPEN + 8, need & 1); }
        rd.load(rec);
        rd.check(rec, base + r, r < RT - 2 ? POLL_NS3 : 100 TK_PASS);
        TK(0)
        const uint32_t want = H<2>::tag(base + r), t = 0u - (lane & 1u), k = (t & 1u << 26) - (want >> 4);
        uint32_t o0[J], o1[J], g = 0;
#pragma unroll
        for (int j = 0; j < J; j++) {
            o0[j] = 0; o1[j] = 0;
            if (!xor_and<H<2>::TAG>(rec[j].y, want)) {
                const uint32_t a = aux_of(rec[j].x, rec[j].y, k) + (j >= G3 ? (o0[j - G3] | o1[j - G3]) & p.zero : 0u);
                const uint32_t v0 = (rec[j].x & 0x0fff0fffu) - 0x08000800u, v1 = (rec[j].y & 0x0fff0fffu) - 0x08000800u;
                o0[j] = atoms_add<OFF_ACC>(sb + a, mux(v0, v1, t));
                o1[j] = atoms_add<OFF_ACC>(sb + (a ^ 4u), mux(v1, v0, t));
            }
        }
#pragma unroll
        for (int j = 0; j < J; j++) g |= o0[j] | o1[j];
        if (__any_sync(0xffffffffu, g & 0x80008000u)) {
#pragma unroll 1
            for (int j = 0; j < J; j++) {
                const uint2 w = pick(j, rec);
                const uint32_t aux = aux_of(w.x, w.y), p0 = pick(j, o0), p1 = pick(j, o1);
                const float2 a = acc_fix(t ? p1 : p0, w.x & 0x0fff0fffu), b = acc_fix(t ? p0 : p1, w.y & 0x0fff0fffu);
                const float unit = __uint_as_float(lds32(sb + W_UNIT));
                if (!((w.y ^ want) & H<2>::TAG) && (a.x != 0.f || a.y != 0.f || b.x != 0.f || b.y != 0.f))
                    side_add(lds32(sb + W_ROLE), aux >> 3, a.x * unit, a.y * unit, b.x * unit, b.y * unit);
                __syncwarp();
            }
        }
        TK(1)
    }
    rd.finish();
    TK_OUT
}

__device__ __forceinline__ uint32_t row_max(uint32_t x, uint32_t y) {
    const uint32_t mx = __vmaxu2(x & 0x7fff7fffu, y & 0x7fff7fffu);
    return max(mx & 0xffffu, mx >> 16);
}
constexpr int EWIN = 5;

__global__ void __launch_bounds__(NTHR, 1) fused_kernel(const Params p) {
    const int tid = threadIdx.x, lane = tid & 31;
    const int hw = __reduce_max_sync(0xffffffffu, tid >> 5);
    const uint32_t sb = __reduce_or_sync(0xffffffffu, (uint32_t)__cvta_generic_to_shared(smem));
    TKX(0)
    const uint32_t epoch = ld_rlx32(&g_base);
    uint32_t base = epoch & 31u;

    if (hw < NS1) {
        if (hw < NS1 - 1 || NPR == 1024) stage1<4>(p, sb, hw * 128 + lane, lane, base);
        else stage1<NPR / 32 - (NS1 - 1) * 4>(p, sb, hw * 128 + lane, lane, base);
        __threadfence();
        bar_arrive(BAR_DONE, (NS1 + NC + 2) * 32);
    } else if (hw == W_M1) {
        if (lane == 0) {
            if (sb & 255u) __trap();
            mbar_init(sb + B_FULL, NS1); mbar_init(sb + B_OPEN, 1); mbar_init(sb + B_FREE, 1);
        }
        base = __reduce_or_sync(0xffffffffu, base);
        if (lane == 0 && (base & 1u)) { mbar_arrive(sb + B_OPEN); mbar_arrive(sb + B_FREE); }
        for (int i = lane; i < NG + NDUM; i += 32) sts32(sb + OFF_CNT1 + i * 4, i < NG ? H<1>::init(base) + (i & 7) * 16 : DUMMY);
#pragma unroll 1
        for (int i = 0; i < 2; i++) fill<1>(sb + OFF_H1 + H<1>::win(base + i), lane, base + i);
        bar_arrive(BAR_S1, (NS1 + 1) * 32);
        bar_sync(BAR_PROBE, (2 * NC + 1) * 32);
        {
            const uint32_t raw = __ballot_sync(0xffffffffu, lane < 2 * NC && smem[OFF_PROBE + lane]), side = raw & 1u;
            uint32_t v = 0;
            if (lane < 2) asm volatile("atom.relaxed.gpu.global.add.u32 %0, [%1], %2;" : "=r"(v) : "l"(p.ring + M_CNT + lane * 4096), "r"(side ? 0x10000u : 1u) : "memory");
            const uint32_t mine = (side ? ~raw : raw) | 0x80000000u;
            if (lane == 2) asm volatile("atom.relaxed.gpu.global.cas.b32 %0, [%1], 0, %2;" : "=r"(v) : "l"(p.ring + M_PAR), "r"(mine) : "memory");
            bar_sync(BAR_HIST, (2 * NC + 1) * 32);
            uint32_t best = 0;
#pragma unroll 1
            for (int e = 11 + lane; e <= 230; e += 32) {
                uint32_t c = 0;
#pragma unroll
                for (int i = 0; i < EWIN; i++) c += lds32(sb + OFF_HIST + (e - i) * 4);
                best = max(best, c << 8 | (255 - e));
            }
            const uint32_t e = 255 - (__reduce_max_sync(0xffffffffu, best) & 255u);
            if (lane == 0) {
                const uint32_t role = side ? NB - 1 - (v >> 16) : v & 0xffffu;
                sts32(sb + W_ROLE, role); sts32(sb + W_SIDE, role < NLO ? 0u : role >= NHI ? 1u : side);
                sts32(sb + W_EXP, e); sts32(sb + W_UNIT, (e - 10) << 23); sts32(sb + W_END, (epoch | 31u) + 1u + (base + p.rounds) % 24u);
            }
            if (lane == 2) sts32(sb + W_PAR, v ? v : mine);
        }
        bar_sync(BAR_ROLE, (2 * NC + 2) * 32);
        manager<1>(p, sb, lane, __reduce_max_sync(0xffffffffu, lds32(sb + W_ROLE)), base);
        bar_arrive(BAR_H1, (NS1 + 1) * 32);
        __threadfence();
        bar_arrive(BAR_DONE, (NS1 + NC + 2) * 32);
    } else if (hw == W_M2) {
        const float wd = __bfloat162float(lane & 16 ? p.w_up[lane & 15] : p.w_down[lane & 15]);
        const float ws = __bfloat162float(p.w_sbf[lane]), wr = __bfloat162float(p.w_rbf[lane]);
        const __nv_bfloat16 cen = p.centers[lane & 7];
        if (lane == 0) { mbar_init(sb + B_FULL + 8, NC); mbar_init(sb + B_OPEN + 8, 1); }
        base = __reduce_or_sync(0xffffffffu, base);
        for (int i = lane; i <= NB + NDUM; i += 32) sts32(sb + OFF_CNT2 + i * 4, i < NB ? H<2>::init(base) + (i & 7) * 16 : DUMMY);
#pragma unroll 1
        for (int i = 0; i < 3; i++) fill<2>(sb + H<2>::win(i), lane, base + i);
        reinterpret_cast<float*>(smem + OFF_WSM)[lane] = wd;
        reinterpret_cast<float*>(smem + OFF_WG)[lane] = ws;
        reinterpret_cast<float*>(smem + OFF_WG + 128)[lane] = wr;
        reinterpret_cast<__nv_bfloat16*>(smem + OFF_WG + 256)[lane & 7] = cen;
        bar_sync(BAR_ROLE, (2 * NC + 2) * 32);
        manager<2>(p, sb, lane, __reduce_max_sync(0xffffffffu, lds32(sb + W_ROLE)), base);
        __threadfence();
        bar_sync(BAR_DONE, (NS1 + NC + 2) * 32);
        if (lane < 2) { __threadfence(); st_rlx32(reinterpret_cast<uint32_t*>(p.ring + M_FLAG + lane * 4096) + blockIdx.x, lds32(sb + W_END)); }
    } else {
        const int pw = __reduce_max_sync(0xffffffffu, hw < W_M1 ? hw - NS1 : hw - NS1 - 1), ct = pw * 32 + lane;
        constexpr int CT = 2 * NC * 32;
        const uint4 sm = __ldg(reinterpret_cast<const uint4*>(p.m) + min((ct >> 3) * (p.E >> 1) / (CT / 8) + (lane & 7), (p.E >> 1) - 1));
        if (ct < 256) sts32(sb + OFF_HIST + ct * 4, 0u);
        if (lane == 0) smem[OFF_PROBE + pw] = pw < NPAGE ? near_half(p.ring + (size_t)pw * PAGE + PROBE + (blockIdx.x & 31) * 128 + (blockIdx.x >> 5 & 3) * 16384 + (blockIdx.x >> 7 << 20), p.zero) : 0;
        TKX(1)
        bar_sync(BAR_PROBE, (2 * NC + 1) * 32);
        {
            const uint32_t m0 = row_max(sm.x, sm.y), m1 = row_max(sm.z, sm.w);
            if (m0) atoms_add<OFF_HIST>(sb + (m0 >> 7) * 4, 1u);
            if (m1) atoms_add<OFF_HIST>(sb + (m1 >> 7) * 4, 1u);
        }
        bar_arrive(BAR_HIST, (2 * NC + 1) * 32);
        base = __reduce_or_sync(0xffffffffu, base);
        for (int i = ct; i < R2MAX / 2; i += CT) reinterpret_cast<uint4*>(smem + OFF_ACC)[i] = make_uint4(0x40004000u, 0x40004000u, 0x40004000u, 0x40004000u);
        bar_sync(BAR_ROLE, (2 * NC + 2) * 32);
        const int role = __reduce_max_sync(0xffffffffu, lds32(sb + W_ROLE));
        TKX(2)
        {
            const int e = lds32(sb + W_EXP), q0 = (role >= NG ? role - NG : role) * (p.R1 >> 1), nq = min(p.R1 >> 1, (p.E >> 1) - q0);
            const uint32_t sc = (uint32_t)(254 - e) * 0x800080u;
            constexpr int CH = (R1MAX / 2 + CT - 1) / CT;
            uint4 v[CH];
#pragma unroll
            for (int u = 0; u < CH; u++) v[u] = __ldg(reinterpret_cast<const uint4*>(p.m) + min(q0 + ct + u * CT, (p.E >> 1) - 1));
            auto conv = [&](uint32_t& x, uint32_t& y) {
                const uint32_t mx = row_max(x, y);
                const int d = e - (int)(mx >> 7);
                x = hmul_bf2(x, sc); y = hmul_bf2(y, sc);
                if (d >= EWIN) y |= 0x40000000u;
                if (d < 0 || (d >= EWIN && e > 127)) { x = 0x40000000u; y = x; }
                if (mx == 0) { x = 0; y = 0; }
            };
#pragma unroll
            for (int u = 0; u < CH; u++) {
                conv(v[u].x, v[u].y); conv(v[u].z, v[u].w);
                if (ct + u * CT < nq) sts128<OFF_M>(sb + (ct + u * CT) * 16, v[u]);
            }
        }
        TKX(3)
        if (hw < W_M1) {
            stage2(p, sb, pw, lane, role, base);
            __threadfence();
            bar_arrive(BAR_DONE, (NS1 + NC + 2) * 32);
        } else {
            stage3(p, sb, pw - NC, lane, role, base);
            __threadfence();
        }
    }
    TKX(4)
    epilogue(p, sb);
}

__global__ void fb_scatter(const uint2* __restrict__ m, const int* __restrict__ idx_in, const int* __restrict__ idx_out,
                           const uint16_t* __restrict__ angle, const __nv_bfloat16* __restrict__ ang_freq, int T, int e0, int e1) {
    const uint32_t fb = *reinterpret_cast<const uint16_t*>(ang_freq);
    for (long long t = blockIdx.x * (long long)blockDim.x + threadIdx.x; t < T; t += (long long)gridDim.x * blockDim.x) {
        int o = idx_out[t];
        if (o < e0 || o >= e1) continue;
        float c = bf16r(cos_bf(hmul_bf2(angle[t], fb) & 0xffffu));
        uint2 v = __ldg(m + idx_in[t]);
        red4(&g_ovf[o - e0], c * bf_lo(v.x), c * bf_hi(v.x), c * bf_lo(v.y), c * bf_hi(v.y));
    }
}
__global__ void fb_final(const Params p, int e0, int e1) {
    int e = e0 + blockIdx.x * blockDim.x + threadIdx.x;
    if (e >= e1) return;
    float4 a4 = g_ovf[e - e0];
    g_ovf[e - e0] = make_float4(0.f, 0.f, 0.f, 0.f);
    float a[4] = {a4.x, a4.y, a4.z, a4.w};
    float d = __bfloat162float(p.dist[e]);
    float g[4] = {0, 0, 0, 0}, h[4] = {0, 0, 0, 0};
    for (int r = 0; r < 8; r++) {
        float df = bf16r(d - __bfloat162float(p.centers[r]));
        float rb = bf16r(expf(bf16r(-10.0f * bf16r(df * df))));
        for (int k = 0; k < 4; k++) {
            g[k] += rb * __bfloat162float(p.w_sbf[r * 4 + k]);
            h[k] += rb * __bfloat162float(p.w_rbf[r * 4 + k]);
        }
    }
    float ag[4];
    for (int k = 0; k < 4; k++) {
        float s = 0.f;
        for (int j = 0; j < 4; j++) s += a[j] * __bfloat162float(p.w_down[j * 4 + k]);
        ag[k] = bf16r(s * g[k]);
    }
    uint2 mv = p.m[e];
    float mm[4] = {bf_lo(mv.x), bf_hi(mv.x), bf_lo(mv.y), bf_hi(mv.y)};
    __nv_bfloat16 o[4];
    for (int k = 0; k < 4; k++) {
        float u = 0.f;
        for (int j = 0; j < 4; j++) u += ag[j] * __bfloat162float(p.w_up[j * 4 + k]);
        o[k] = __float2bfloat16_rn(mm[k] + bf16r(bf16r(u) * bf16r(h[k])));
    }
    p.out[e] = *reinterpret_cast<uint2*>(o);
}

}

static bool exact_div(int E, int lo, int hi, int* R, uint32_t* magic) {
    for (int r = lo + (lo & 1); r <= hi; r += 2) {
        unsigned long long mg = ((1ull << 32) + r - 1) / r, err = mg * r - (1ull << 32);
        if (err * (unsigned long long)E < (1ull << 32)) { *R = r; *magic = (uint32_t)mg; return true; }
    }
    return false;
}

extern "C" void kernel_launch(void* const* d_in, const int* in_sizes, int n_in, void* d_out, int out_size) {
    typedef const __nv_bfloat16* B;
    Params p;
    p.m = (const uint2*)d_in[0]; p.idx_in = (const uint2*)d_in[1]; p.idx_out = (const uint2*)d_in[2]; p.dist = (B)d_in[3];
    p.angle = (const uint32_t*)d_in[4]; p.centers = (B)d_in[5]; p.ang_freq = (B)d_in[6]; p.w_rbf = (B)d_in[7]; p.w_sbf = (B)d_in[8];
    p.w_down = (B)d_in[9]; p.w_up = (B)d_in[10]; p.out = (uint2*)d_out;
    p.E = in_sizes[3]; p.T = in_sizes[1]; p.T2 = p.T >> 1; p.zero = 0;
    p.R1 = p.R2 = p.rounds = p.lastn = p.qfull = 0; p.mg1 = p.mg2 = p.k1 = p.k2 = 0;
    static int ok = -1;
    static unsigned char* ring = nullptr;
    if (ok < 0) {
        void* ra = nullptr;
        cudaGetSymbolAddress(&ra, g_ring);
        ring = reinterpret_cast<unsigned char*>(((uintptr_t)ra + PAGE - 1) & ~(uintptr_t)(PAGE - 1));
        int dev = 0, sms = 0, occ = 0;
        cudaGetDevice(&dev);
        cudaDeviceGetAttribute(&sms, cudaDevAttrMultiProcessorCount, dev);
        cudaError_t e = cudaFuncSetAttribute(fused_kernel, cudaFuncAttributeMaxDynamicSharedMemorySize, SMEM_BYTES);
        if (e == cudaSuccess) e = cudaOccupancyMaxActiveBlocksPerMultiprocessor(&occ, fused_kernel, NTHR, SMEM_BYTES);
        ok = (e == cudaSuccess && occ >= 1 && sms >= NB) ? 1 : 0;
        (void)cudaGetLastError();
    }
    p.ring = ring;
    const bool fused = ok == 1 && p.E <= EMAX && p.E >= 2 * NB && p.E % 2 == 0 && p.T >= 2 && exact_div(p.E, (p.E + NG - 1) / NG, R1MAX, &p.R1, &p.mg1) &&
                       exact_div(p.E, (p.E + NB - 1) / NB, R2MAX, &p.R2, &p.mg2);
    if (fused) {
        p.k1 = 0u - (uint32_t)p.R1; p.k2 = 0u - 8u * (uint32_t)p.R2;
        const int per = NB * NPR;
        int full = p.T2 / per, rest = p.T2 - full * per;
        p.qfull = full * per;
        p.lastn = (rest + NB - 1) / NB;
        if (p.lastn > NPR / 2) { full++; p.lastn = 0; }
        if (full < D) { full = D; p.lastn = 0; }
        p.rounds = full + 1;
        fused_kernel<<<NB, NTHR, SMEM_BYTES>>>(p);
    } else {
        for (int e0 = 0; e0 < p.E; e0 += EMAX) {
            int e1 = p.E - e0 < EMAX ? p.E : e0 + EMAX;
            fb_scatter<<<1056, 256>>>(p.m, (const int*)d_in[1], (const int*)d_in[2], (const uint16_t*)d_in[4], p.ang_freq, p.T, e0, e1);
            fb_final<<<(e1 - e0 + 255) / 256, 256>>>(p, e0, e1);
        }
    }
}
```

```cpp
#include <cuda_runtime.h>
#include <cuda_bf16.h>
#include <stdint.h>

namespace {

constexpr int NB = 132, NG = 66;
constexpr int R2MAX = 6062, R1MAX = 12124;
constexpr int EMAX = NB * R2MAX;
constexpr int NTHR = 1024;
constexpr int NS1 = 8, NC = 11, J = 6;
#define TILES 30
#define DEFER 0
#define CSYNC 6
#define G1 4
#define G3 6
#define CAP1 64
constexpr int NPR = TILES * 32;
constexpr int D = 3;
constexpr int WIN = 16896;
constexpr int NDUM = 16;
constexpr uint32_t DUMMY = 0xc0000000u;

constexpr int OFF_ACC = WIN, OFF_BAR = OFF_ACC + R2MAX * 8;
constexpr int OFF_H1 = 0x10000 + WIN, OFF_M = OFF_H1 + WIN, OFF_WSM = OFF_M + R1MAX * 8;
constexpr int OFF_CNT1 = OFF_H1 + 0x20000 + WIN, OFF_CNT2 = OFF_CNT1 + (NG + NDUM + 2) * 4, W_RND = OFF_CNT2 + (NB + NDUM) * 4, OFF_WG = W_RND + 16;
constexpr int OFF_HIST = OFF_M;
constexpr int OFF_PROBE = OFF_WSM + 128;
constexpr int SMEM_BYTES = OFF_WG + 272;
static_assert(SMEM_BYTES <= 232448 && OFF_BAR + 64 <= 0x10000 && OFF_PROBE + 32 <= 0x30000, "smem");
static_assert(OFF_BAR % 8 == 0 && OFF_WG % 16 == 0 && OFF_WSM % 16 == 0 && OFF_CNT2 % 16 == 0, "align");
static_assert(NC * J == NG && NC * 32 * 6 * 16 == 2 * WIN, "shape");

template <int HOP> struct H {
    static constexpr int S = HOP == 1 ? 32 : 16, NBIN = HOP == 1 ? NG : NB, CAP = HOP == 1 ? CAP1 : 32, SH = HOP == 1 ? 11 : 12;
    static constexpr int TB = HOP == 1 ? 20 : 28, CNT = HOP == 1 ? OFF_CNT1 : OFF_CNT2, STG = HOP == 1 ? OFF_H1 : 0;
    static constexpr uint32_t INC = (1u << SH) + 8u, PM = (S - 1) * 8, TAG = 7u << TB;
    static __device__ __forceinline__ uint32_t tag(uint32_t R) { return R << TB & TAG; }
    static __device__ __forceinline__ uint32_t init(uint32_t R) { return tag(R) | ((1u << TB) - 0x10000u); }
    static __device__ __forceinline__ uint32_t mark(uint32_t R, uint32_t line) { return ((HOP == 1 ? R >> 1 : R) + line) & 3u; }
    static __device__ __forceinline__ uint32_t win(int r) { return HOP == 1 ? (r & 1) << 17 : (0x310u >> (r % 3 * 4) & 3u) << 16; }
};

constexpr uint32_t PAGE = 1u << 21;
constexpr int NPAGE = NC + 2;
__device__ __align__(256) unsigned char g_ring[(size_t)(NPAGE + 1) * PAGE];
constexpr int MISC = 0xa0000;
constexpr int M_CNT = MISC + 1024, M_PAR = MISC + 1088;
constexpr int M_FLAG = MISC + 2048;
constexpr int PROBE = MISC + 0x40000;
#define CSTR 16384
__device__ __forceinline__ uint32_t cred_off(uint32_t role) { return role * 4 + min(role >> 5, 3u) * (CSTR - 128); }
struct Ring {
    uint64_t main, mid;
    uint32_t par;
    __device__ __forceinline__ Ring(const unsigned char* ring, uint32_t pars, int k) {
        main = reinterpret_cast<uint64_t>(ring) + ((uint64_t)k << 20);
        par = pars >> (k >> 1) & 1u;
        mid = reinterpret_cast<uint64_t>(ring) + (uint64_t)NC * PAGE + (((k >> 3 << 20) + (k >> 2 & 1) * 0x11000u + (k & 1) * 2048) ^ (k >> 1 & 1) * 0x3000u ^ (pars >> (NC + (k >> 4)) & 1u) << 12);
    }
};
constexpr int NLO = 60, NHI = 72;
__host__ __device__ constexpr uint32_t src_off(int j) { return (j % 3) << 14 | (j / 3) << 18; }
__device__ __forceinline__ uint32_t slot_off(uint32_t s) { return (0xa930u >> s * 4 & 15u) << 16; }
__device__ __forceinline__ uint32_t slot_steps(uint32_t R) { return (uint32_t)(0x30a09030aull >> (2 - R % 3) * 8) & 0xffffffu; }
__device__ __forceinline__ void slot_next(uint32_t& a, uint32_t st) { a ^= st & 0xf0000u; }
__device__ __forceinline__ uint32_t slot_rot(uint32_t st) { return __byte_perm(st, 0u, 0x4102); }
constexpr int RPAD = 6064, DROW = 6144;
__device__ __align__(128) uint8_t g_dirty[NB * DROW];
__device__ uint32_t g_base = 1;
__device__ __align__(128) float4 g_ovf[NB * RPAD];

struct Params {
    const uint2* m; const uint2* idx_in; const uint2* idx_out; const __nv_bfloat16* dist; const uint32_t* angle;
    const __nv_bfloat16* centers; const __nv_bfloat16* ang_freq; const __nv_bfloat16* w_rbf; const __nv_bfloat16* w_sbf;
    const __nv_bfloat16* w_down; const __nv_bfloat16* w_up; uint2* out; unsigned char* ring;
    cudaTextureObject_t ti, to, ta;
    int E, T, T2, R1, R2, rounds, lastn, qfull; uint32_t mg1, mg2, k1, k2, zero;
};

__device__ __forceinline__ float bf16r(float x) { return __bfloat162float(__float2bfloat16_rn(x)); }
__device__ __forceinline__ float bf_lo(uint32_t v) { return __uint_as_float(v << 16); }
__device__ __forceinline__ float bf_hi(uint32_t v) { return __uint_as_float(v & 0xffff0000u); }
__device__ __forceinline__ void red4(float4* a, float x, float y, float z, float w) {
    asm volatile("red.global.add.v4.f32 [%0], {%1,%2,%3,%4};" ::"l"(a), "f"(x), "f"(y), "f"(z), "f"(w) : "memory");
}
__device__ __forceinline__ void bar_sync(int id, int n) { __syncwarp(); asm volatile("bar.sync %0, %1;" ::"r"(id), "r"(n) : "memory"); }
__device__ __forceinline__ void bar_arrive(int id, int n) { __syncwarp(); asm volatile("bar.arrive %0, %1;" ::"r"(id), "r"(n) : "memory"); }
template <int OFF> __device__ __forceinline__ uint32_t atoms_add(uint32_t addr, uint32_t v) {
    uint32_t r; asm volatile("atom.shared.add.u32 %0, [%1+%3], %2;" : "=r"(r) : "r"(addr), "r"(v), "n"(OFF) : "memory"); return r;
}
__device__ __forceinline__ void sts64(uint32_t addr, uint32_t x, uint32_t y) {
    asm volatile("st.shared.v2.u32 [%0], {%1,%2};" ::"r"(addr), "r"(x), "r"(y) : "memory");
}
__device__ __forceinline__ void sts32(uint32_t addr, uint32_t x) { asm volatile("st.shared.u32 [%0], %1;" ::"r"(addr), "r"(x) : "memory"); }
template <int OFF = 0> __device__ __forceinline__ uint2 lds64(uint32_t addr) {
    uint2 v; asm volatile("ld.shared.v2.u32 {%0,%1}, [%2+%3];" : "=r"(v.x), "=r"(v.y) : "r"(addr), "n"(OFF) : "memory"); return v;
}
__device__ __forceinline__ uint32_t lds32(uint32_t addr) {
    uint32_t v; asm volatile("ld.shared.u32 %0, [%1];" : "=r"(v) : "r"(addr) : "memory"); return v;
}
__device__ __forceinline__ uint32_t ld_rlx32(const uint32_t* p) {
    uint32_t v; asm volatile("ld.relaxed.gpu.global.u32 %0, [%1];" : "=r"(v) : "l"(p) : "memory"); return v;
}
__device__ __forceinline__ uint2 ld_rlx64(const void* p) {
    uint2 v; asm volatile("ld.relaxed.gpu.global.v2.u32 {%0,%1}, [%2];" : "=r"(v.x), "=r"(v.y) : "l"(p) : "memory"); return v;
}
__device__ __forceinline__ float4 ld_rlx128f(const float4* p) {
    float4 v; asm volatile("ld.relaxed.gpu.global.v4.f32 {%0,%1,%2,%3}, [%4];" : "=f"(v.x), "=f"(v.y), "=f"(v.z), "=f"(v.w) : "l"(p) : "memory"); return v;
}
__device__ __forceinline__ void take3(float4* p, uint32_t mask, float4 (&v)[3]) {
    asm volatile("{ .reg .b128 a, b, c; .reg .b64 x, y; .reg .pred q0, q1, q2; .reg .b32 t;\n"
                 "mov.b64 x, 0; mov.b128 a, {x, x}; mov.b128 b, {x, x}; mov.b128 c, {x, x};\n"
                 "and.b32 t, %13, 1; setp.ne.u32 q0, t, 0; and.b32 t, %13, 2; setp.ne.u32 q1, t, 0; and.b32 t, %13, 4; setp.ne.u32 q2, t, 0;\n"
                 "@q0 atom.relaxed.gpu.global.exch.b128 a, [%12], a; @q1 atom.relaxed.gpu.global.exch.b128 b, [%12+16384], b;\n"
                 "@q2 atom.relaxed.gpu.global.exch.b128 c, [%12+32768], c;\n"
                 "mov.b128 {x, y}, a; mov.b64 {%0,%1}, x; mov.b64 {%2,%3}, y; mov.b128 {x, y}, b; mov.b64 {%4,%5}, x; mov.b64 {%6,%7}, y;\n"
                 "mov.b128 {x, y}, c; mov.b64 {%8,%9}, x; mov.b64 {%10,%11}, y; }"
                 : "=f"(v[0].x), "=f"(v[0].y), "=f"(v[0].z), "=f"(v[0].w), "=f"(v[1].x), "=f"(v[1].y), "=f"(v[1].z), "=f"(v[1].w),
                   "=f"(v[2].x), "=f"(v[2].y), "=f"(v[2].z), "=f"(v[2].w) : "l"(p), "r"(mask) : "memory");
}
__device__ __forceinline__ void st_rlx32(uint32_t* p, uint32_t v) { asm volatile("st.relaxed.gpu.global.u32 [%0], %1;" ::"l"(p), "r"(v) : "memory"); }
__device__ __forceinline__ uint32_t hmul_bf2(uint32_t a, uint32_t b) {
    uint32_t r; asm("mul.rn.bf16x2 %0, %1, %2;" : "=r"(r) : "r"(a), "r"(b)); return r;
}
__device__ __forceinline__ uint32_t hsub_bf2(uint32_t a, uint32_t b) {
    uint32_t r; asm("sub.rn.bf16x2 %0, %1, %2;" : "=r"(r) : "r"(a), "r"(b)); return r;
}
constexpr int SPIN_LIMIT = 1 << 22;

__constant__ uint32_t c_inv2pi[8] = {0u, 0x28be60dbu, 0x9391054au, 0x7f09d5f4u, 0x7d4d3770u, 0x36d8a566u, 0x4f10e410u, 0x7f9458eau};
constexpr uint32_t BIGX = 0x4280u;
__device__ __forceinline__ float cos_big(uint32_t xb) {
    uint32_t e = (xb >> 7) & 0xffu, M = (xb & 0x7fu) | 0x80u;
    uint32_t pp = e - 102u;
    uint32_t wi = pp >> 5;
    uint32_t t0 = c_inv2pi[wi], t1 = c_inv2pi[wi + 1], t2 = c_inv2pi[wi + 2];
    uint32_t f = M * __funnelshift_l(t1, t0, pp) + __umulhi(M, __funnelshift_l(t2, t1, pp));
    float c = __cosf((float)(int)f * 1.4629180792671596e-9f);
    return e == 255u ? __uint_as_float(0x7fc00000u) : c;
}
__device__ __forceinline__ float cos_bf(uint32_t xb) {
    return (xb & 0x7fffu) > BIGX ? cos_big(xb) : __cosf(__uint_as_float(xb << 16));
}
__device__ __forceinline__ uint32_t pack_bf2(float lo, float hi) {
    uint32_t r; asm("cvt.rn.bf16x2.f32 %0, %1, %2;" : "=r"(r) : "f"(hi), "f"(lo)); return r;
}
template <int N> __device__ __forceinline__ uint32_t pick(int k, const uint32_t (&a)[N]) {
    uint32_t v = a[0];
#pragma unroll
    for (int i = 1; i < N; i++) if (k == i) v = a[i];
    return v;
}
template <int N> __device__ __forceinline__ uint2 pick(int k, const uint2 (&a)[N]) {
    uint2 v = a[0];
#pragma unroll
    for (int i = 1; i < N; i++) if (k == i) v = a[i];
    return v;
}
__device__ __forceinline__ void side_add(uint32_t bin, uint32_t row, float a, float b, float c, float d) {
    red4(&g_ovf[bin * RPAD + row], a, b, c, d);
    g_dirty[bin * DROW + row] = 1;
}
__device__ __forceinline__ void slow_triplet(const Params& p, uint32_t ii, uint32_t oo, float c) {
    const uint2 v = __ldg(p.m + ii);
    const uint32_t bo = __umulhi(oo, p.mg2);
    side_add(bo, oo - bo * p.R2, c * bf_lo(v.x), c * bf_hi(v.x), c * bf_lo(v.y), c * bf_hi(v.y));
}
__device__ __forceinline__ void slow_rec1(const Params& p, uint32_t x, uint32_t y, uint32_t bin) {
    const uint2 v = __ldg(p.m + bin * p.R1 + (y & 0xffffu));
    const float c = bf_hi(y);
    side_add(x & 0xffu, __byte_perm(x, 0u, 0x4413) >> 3, c * bf_lo(v.x), c * bf_hi(v.x), c * bf_lo(v.y), c * bf_hi(v.y));
}
__device__ __forceinline__ uint32_t aux_of(uint32_t w0, uint32_t w1, uint32_t k = 0) {
    uint32_t u; asm("lop3.b32 %0, %1, %2, 0xf000f000, 0xe4;" : "=r"(u) : "r"(w0), "r"((w1 >> 4) + k));
    return __byte_perm(u, 0u, 0x4413);
}
__device__ __forceinline__ void slow_rec2(const Params& p, uint32_t w0, uint32_t w1, uint32_t bin, float unit) {
    side_add(bin, aux_of(w0, w1) >> 3, (float)((int)(w0 & 0xfffu) - 2048) * unit, (float)((int)(w0 >> 16 & 0xfffu) - 2048) * unit,
             (float)((int)(w1 & 0xfffu) - 2048) * unit, (float)((int)(w1 >> 16 & 0xfffu) - 2048) * unit);
}
template <uint32_t M> __device__ __forceinline__ uint32_t and_or(uint32_t a, uint32_t c) {
    uint32_t r; asm("lop3.b32 %0, %1, %2, %3, 0xea;" : "=r"(r) : "r"(a), "n"(M), "r"(c)); return r;
}
template <uint32_t M> __device__ __forceinline__ uint32_t xor_and(uint32_t a, uint32_t c) {
    uint32_t r; asm("lop3.b32 %0, %1, %2, %3, 0x48;" : "=r"(r) : "r"(a), "n"(M), "r"(c)); return r;
}
__device__ __forceinline__ uint32_t mux(uint32_t a, uint32_t b, uint32_t m) {
    uint32_t r; asm("lop3.b32 %0, %1, %2, %3, 0xd8;" : "=r"(r) : "r"(a), "r"(b), "r"(m)); return r;
}
__device__ __forceinline__ uint32_t and_xor(uint32_t a, uint32_t m, uint32_t c) {
    uint32_t r; asm("lop3.b32 %0, %1, %2, %3, 0x6a;" : "=r"(r) : "r"(a), "r"(m), "r"(c)); return r;
}
__device__ __forceinline__ uint2 ld_in(const uint2* a) {
    uint2 v; asm volatile("ld.global.nc.L1::no_allocate.v2.u32 {%0,%1}, [%2];" : "=r"(v.x), "=r"(v.y) : "l"(a)); return v;
}
__device__ __forceinline__ uint32_t ld_in(const uint32_t* a) {
    uint32_t v; asm volatile("ld.global.nc.L1::no_allocate.u32 %0, [%1];" : "=r"(v) : "l"(a)); return v;
}
__device__ __forceinline__ void tex4(cudaTextureObject_t t, int i, uint2& a, uint2& b) {
    asm volatile("tex.1d.v4.u32.s32 {%0,%1,%2,%3}, [%4, {%5}];" : "=r"(a.x), "=r"(a.y), "=r"(b.x), "=r"(b.y) : "l"(t), "r"(i));
}
__device__ __forceinline__ void tex2(cudaTextureObject_t t, int i, uint32_t& a, uint32_t& b) {
    asm volatile("{ .reg .b32 z, w; tex.1d.v4.u32.s32 {%0,%1,z,w}, [%2, {%3}]; }" : "=r"(a), "=r"(b) : "l"(t), "r"(i));
}
template <int OFF> __device__ __forceinline__ void put_rec(uint32_t ret, uint32_t lim, uint32_t addr, uint32_t x, uint32_t y) {
    asm volatile("{ .reg .pred q; setp.lt.u32 q, %0, %1; @q st.shared.v2.u32 [%2+%5], {%3,%4}; }" ::"r"(ret), "r"(lim), "r"(addr), "r"(x), "r"(y), "n"(OFF) : "memory");
}
__device__ __forceinline__ uint32_t mbar_try(uint32_t mb, uint32_t parity) {
    uint32_t ok;
    asm volatile("{ .reg .pred q; mbarrier.try_wait.parity.shared::cta.b64 q, [%1], %2; selp.u32 %0, 1, 0, q; }" : "=r"(ok) : "r"(mb), "r"(parity) : "memory");
    return ok;
}
__device__ __forceinline__ void mbar_wait(uint32_t mb, uint32_t parity) {
    if (!mbar_try(mb, parity)) {
        int it = 0;
        while (!mbar_try(mb, parity)) if (++it > SPIN_LIMIT) __trap();
    }
}
__device__ __forceinline__ void mbar_init(uint32_t mb, uint32_t n) { asm volatile("mbarrier.init.shared::cta.b64 [%0], %1;" ::"r"(mb), "r"(n) : "memory"); }
__device__ __forceinline__ void mbar_arrive(uint32_t mb) { asm volatile("mbarrier.arrive.shared::cta.b64 _, [%0];" ::"r"(mb) : "memory"); }
constexpr int B_FULL = OFF_BAR, B_OPEN = OFF_BAR + 16, B_FREE = OFF_BAR + 32;
constexpr int W_END = OFF_BAR + 40, W_SIDE = OFF_BAR + 44, W_PAR = OFF_BAR + 48, W_ROLE = OFF_BAR + 52, W_EXP = OFF_BAR + 56, W_UNIT = OFF_BAR + 60;
enum { BAR_S1 = 1, BAR_PROBE, BAR_HIST, BAR_ROLE, BAR_TABLE, BAR_H1, BAR_DONE };
constexpr int W_M1 = NS1 + NC, W_M2 = 31;

extern __shared__ __align__(1024) unsigned char smem[];
#define TK_DECL
#define TK(i)
#define TK_CNT(i)
#define TK_OUT
#define TK_ARG
#define TK_PASS
#define TKX(i)
#define TKY(i)

constexpr int NR = (R2MAX + NTHR - 1) / NTHR;
__device__ __forceinline__ void gates(const Params& p, int e0, int e1, int e2, uint4* gh) {
    constexpr int NH = 3;
    const int e[NH] = {e0, e1, e2};
    uint32_t dd[NH];
    float g[NH][4], h[NH][4];
#pragma unroll
    for (int u = 0; u < NH; u++) {
        dd[u] = reinterpret_cast<const uint16_t*>(p.dist)[min(e[u], p.E - 1)] * 0x10001u;
#pragma unroll
        for (int k = 0; k < 4; k++) { g[u][k] = 0.f; h[u][k] = 0.f; }
    }
#pragma unroll 1
    for (int r2 = 0; r2 < 4; r2++) {
        const uint32_t cen = reinterpret_cast<const uint32_t*>(smem + OFF_WG + 256)[r2];
        uint32_t rb[NH];
#pragma unroll
        for (int u = 0; u < NH; u++) {
            const uint32_t df = hsub_bf2(dd[u], cen);
            const uint32_t ar = hmul_bf2(hmul_bf2(df, df), 0xc120c120u);
            rb[u] = pack_bf2(__expf(bf_lo(ar)), __expf(bf_hi(ar)));
        }
#pragma unroll
        for (int i = 0; i < 2; i++) {
            const float4 ws = reinterpret_cast<const float4*>(smem + OFF_WG)[r2 * 2 + i], wr = reinterpret_cast<const float4*>(smem + OFF_WG + 128)[r2 * 2 + i];
#pragma unroll
            for (int u = 0; u < NH; u++) {
                const float x = i ? bf_hi(rb[u]) : bf_lo(rb[u]);
                g[u][0] += x * ws.x; g[u][1] += x * ws.y; g[u][2] += x * ws.z; g[u][3] += x * ws.w;
                h[u][0] += x * wr.x; h[u][1] += x * wr.y; h[u][2] += x * wr.z; h[u][3] += x * wr.w;
            }
        }
    }
#pragma unroll
    for (int u = 0; u < NH; u++)
        gh[u] = make_uint4(pack_bf2(g[u][0], g[u][1]), pack_bf2(g[u][2], g[u][3]), pack_bf2(h[u][0], h[u][1]), pack_bf2(h[u][2], h[u][3]));
}
__device__ __forceinline__ void prefetch_l2(const void* a) { asm volatile("prefetch.global.L2 [%0];" ::"l"(a)); }
__device__ __forceinline__ uint4* gate_slot(int k) { return reinterpret_cast<uint4*>(smem + OFF_H1 + (k >= WIN / 16 ? 0x20000 - WIN : 0)) + k; }
__device__ __forceinline__ void wait_flags(const Params& p, uint32_t sb, int lane, uint32_t need) {
    const unsigned char* f = p.ring + M_FLAG + (lds32(sb + W_SIDE) << 12);
    int it = 0;
    while (true) {
        const float4 a = ld_rlx128f(reinterpret_cast<const float4*>(f) + lane);
        const uint32_t b = ld_rlx32(reinterpret_cast<const uint32_t*>(f) + 128 + (lane & 3));
        const uint32_t d = (__float_as_uint(a.x) ^ need) | (__float_as_uint(a.y) ^ need) | (__float_as_uint(a.z) ^ need) | (__float_as_uint(a.w) ^ need) | (b ^ need);
        if (__all_sync(0xffffffffu, d == 0)) break;
        __nanosleep(50);
        if (++it > SPIN_LIMIT) __trap();
    }
    __threadfence();
}
__device__ __forceinline__ void epilogue(const Params& p, uint32_t sb) {
    int tid;
    asm volatile("mov.u32 %0, %%tid.x;" : "=r"(tid));
    const int role = lds32(sb + W_ROLE), row0 = role * p.R2, nrows = min(p.R2, p.E - row0), hw = tid >> 5;
    const bool s3 = hw > W_M1 && hw < W_M2;
    constexpr int T3 = (W_M1 + 1) * 32, N3 = NC * 32;
    uint4 gh[NR];
    if (hw < NS1) {
        if (tid * 64 < nrows) prefetch_l2(p.dist + row0 + tid * 64);
        for (int i = tid * 16; i < nrows; i += NS1 * 32 * 16) prefetch_l2(p.m + row0 + i);
    }
    if (!s3) gates(p, row0 + tid + 3 * NTHR, row0 + tid + 4 * NTHR, row0 + tid + 5 * NTHR, gh + 3);
    if (hw < NS1) {
        bar_sync(BAR_H1, (NS1 + 1) * 32);
#pragma unroll 1
        for (int k0 = tid; k0 < NR * N3; k0 += 3 * NS1 * 32) {
            int k[3], e[3];
#pragma unroll
            for (int u = 0; u < 3; u++) { k[u] = k0 + u * NS1 * 32; e[u] = row0 + T3 + k[u] + k[u] / N3 * (NTHR - N3); }
            gates(p, e[0], e[1], e[2], gh);
#pragma unroll
            for (int u = 0; u < 3; u++) if (k[u] < NR * N3) *gate_slot(k[u]) = gh[u];
        }
#pragma unroll
        for (int i = tid; i < DROW / 8; i += NS1 * 32) {
            const uint2 f = ld_rlx64(g_dirty + role * DROW + i * 8);
            if (f.x | f.y) prefetch_l2(g_ovf + role * RPAD + i * 8);
        }
    }
    if (!s3) gates(p, row0 + tid, row0 + tid + NTHR, row0 + tid + 2 * NTHR, gh);
    if (hw == W_M1) wait_flags(p, sb, tid & 31, lds32(sb + W_END));
    TKX(5)
    bar_sync(0, NTHR);
    TKX(6)
    uint32_t dirty = 0;
#pragma unroll
    for (int it = 0; it < NR; it++) {
        uint32_t f;
        asm volatile("ld.relaxed.gpu.global.u8 %0, [%1];" : "=r"(f) : "l"(g_dirty + role * DROW + tid + it * NTHR) : "memory");
        dirty |= f << it;
    }
    if (s3) {
#pragma unroll
        for (int it = 0; it < NR; it++) gh[it] = *gate_slot(tid - T3 + it * N3);
    }
    if (hw == W_M1 && blockIdx.x == 0) {
        if (tid == W_M1 * 32) g_base = lds32(sb + W_END);
        if (tid < W_M1 * 32 + 3) *reinterpret_cast<uint32_t*>(p.ring + (tid & 2 ? M_PAR : M_CNT + (tid & 1) * 4096)) = 0;
    }
    const float unit = *reinterpret_cast<const float*>(smem + W_UNIT);
    const float4* w4 = reinterpret_cast<const float4*>(smem + OFF_WSM);
#pragma unroll
    for (int i0 = 0; i0 < NR; i0 += 3) {
        uint2 mv[3];
        float4 o[3];
#pragma unroll
        for (int u = 0; u < 3; u++) mv[u] = __ldg(p.m + min(row0 + tid + (i0 + u) * NTHR, p.E - 1));
        take3(&g_ovf[role * RPAD + tid + i0 * NTHR], dirty >> i0, o);
#pragma unroll
        for (int u = 0; u < 3; u++) {
            const int it = i0 + u, i = tid + it * NTHR;
            if (dirty >> it & 1) g_dirty[role * DROW + i] = 0;
            if (i < nrows) {
                const uint2 ac = reinterpret_cast<const uint2*>(smem + OFF_ACC)[i];
                const uint32_t u0 = ac.x + 0x40004000u, u1 = ac.y + 0x40004000u;
                const float a[4] = {(float)((int)(u0 & 0xffffu) - 0x8000) * unit + o[u].x, (float)((int)(u0 >> 16) - 0x8000) * unit + o[u].y,
                                    (float)((int)(u1 & 0xffffu) - 0x8000) * unit + o[u].z, (float)((int)(u1 >> 16) - 0x8000) * unit + o[u].w};
                float sd[4] = {0, 0, 0, 0}, uu[4] = {0, 0, 0, 0};
#pragma unroll
                for (int j = 0; j < 4; j++) {
                    float4 w = w4[j];
                    sd[0] += a[j] * w.x; sd[1] += a[j] * w.y; sd[2] += a[j] * w.z; sd[3] += a[j] * w.w;
                }
                const uint32_t a01 = pack_bf2(sd[0] * bf_lo(gh[it].x), sd[1] * bf_hi(gh[it].x)), a23 = pack_bf2(sd[2] * bf_lo(gh[it].y), sd[3] * bf_hi(gh[it].y));
                const float ag[4] = {bf_lo(a01), bf_hi(a01), bf_lo(a23), bf_hi(a23)};
#pragma unroll
                for (int j = 0; j < 4; j++) {
                    float4 w = w4[4 + j];
                    uu[0] += ag[j] * w.x; uu[1] += ag[j] * w.y; uu[2] += ag[j] * w.z; uu[3] += ag[j] * w.w;
                }
                const uint32_t t01 = hmul_bf2(pack_bf2(uu[0], uu[1]), gh[it].z);
                const uint32_t t23 = hmul_bf2(pack_bf2(uu[2], uu[3]), gh[it].w);
                uint2 q;
                asm("add.rn.bf16x2 %0, %1, %2;" : "=r"(q.x) : "r"(mv[u].x), "r"(t01));
                asm("add.rn.bf16x2 %0, %1, %2;" : "=r"(q.y) : "r"(mv[u].y), "r"(t23));
                p.out[row0 + i] = q;
            }
        }
        if (i0 == 0) { TKY(3) }
    }
}

template <int HOP> __device__ __forceinline__ uint2 null_rec(int lane, uint32_t R) {
    if (HOP == 1) return make_uint2(0x800000u | H<1>::tag(R), (OFF_CNT1 - OFF_M) / 8);
    return make_uint2(0x08000800u | lane << 28, 0x08000800u | H<2>::tag(R));
}
template <int OFF> __device__ __forceinline__ void sts128(uint32_t a, const uint4& v) {
    asm volatile("st.shared.v4.u32 [%0+%5], {%1,%2,%3,%4};" ::"r"(a), "r"(v.x), "r"(v.y), "r"(v.z), "r"(v.w), "n"(OFF) : "memory");
}
template <int HOP> __device__ __forceinline__ void fill(uint32_t win, int lane, uint32_t R) {
    const uint2 v = null_rec<HOP>(lane, R);
#pragma unroll 11
    for (int i = 0; i < WIN / 512; i++) sts128<0>(win + lane * 16 + i * 512, make_uint4(v.x, v.y, v.x, v.y));
}
template <int HOP> __device__ __forceinline__ void reset(uint32_t win, int lane, uint32_t R) {
    const uint2 v = null_rec<HOP>(lane, R);
    const uint32_t a = win + lane * 32 + H<HOP>::mark(R, lane >> 2) * 8;
#pragma unroll
    for (int i = 0; i < 16; i++) sts64(a + i * 1024, v.x, v.y);
    if (lane < 16) sts64(a + 16384, v.x, v.y);
}
__device__ __forceinline__ bool elect() {
    uint32_t q; asm volatile("{ .reg .pred q; elect.sync _|q, 0xffffffff; selp.u32 %0, 1, 0, q; }" : "=r"(q)); return q;
}
__device__ __forceinline__ const unsigned char* mk_ptr(uint32_t lo, uint32_t hi) { return reinterpret_cast<const unsigned char*>((uint64_t)hi << 32 | lo); }
__device__ __forceinline__ void bulk_store(uint32_t lo, uint32_t hi, uint32_t src, uint32_t n) {
    asm volatile("cp.async.bulk.global.shared::cta.bulk_group [%0], [%1], %2;" ::"l"(mk_ptr(lo, hi)), "r"(src), "r"(n) : "memory");
}
#define CRED_NS 100
#define CRED_SKIP 1
#define LAG 0
template <int HOP>
__device__ __forceinline__ void manager(const Params& p, uint32_t sb, int lane, int role, uint32_t base) {
    typedef H<HOP> h;
    constexpr int V = h::NBIN / 32, PB = h::S * 8;
    const int RT = p.rounds, lo = HOP == 1 && role >= NG ? NG : 0, hi = lo + h::NBIN;
    const int w = (role - lo) / (HOP * J), j = (role - lo - w * HOP * J) / HOP;
    const Ring rg(p.ring, __reduce_or_sync(0xffffffffu, lds32(sb + W_PAR)), 2 * w + HOP - 1);
    const uint32_t side = lds32(sb + W_SIDE), dhi = rg.main >> 32, mhi = rg.mid >> 32;
    const uint32_t c0 = HOP == 2 ? role & 1 : 0, up = (HOP == 1 && lo) ^ rg.par ^ c0;
    uint32_t dA = ((uint32_t)rg.main + src_off(j) + (c0 << 16) + (up ? 4096 : 12288)) ^ slot_off(base % 3);
    uint32_t dM = ((uint32_t)rg.mid + src_off(j) + c0 * 1024) ^ slot_off(base % 3);
    const int a0 = max(64, lo), b1 = min(68, hi);
    int n0 = (min(NHI, hi) - a0) * PB, a1 = (max(NLO, lo) - lo) * PB;
    const unsigned char* cr = reinterpret_cast<const unsigned char*>(rg.main) + MISC + ((side ^ rg.par) << 12);
    const unsigned char* cr0 = cr + cred_off(lo + lane * V), *cr1 = cr + cred_off(lo + 32 * V + min(lane, V - 1));
    const uint32_t ca0 = sb + h::CNT + lane * V * 4, ca1 = sb + h::CNT + (32 * V + min(lane, V + NDUM)) * 4;
    const uint32_t rot0 = (lane * V & 7) * 16, rot1 = lane * 16;
    uint32_t st = slot_steps(base);
    uint32_t init = h::init(base), prim = sb + h::STG + (HOP == 1 ? h::win(base) : 0u);
    uint32_t cs[5];
    auto sample = [&]() {
        if (V == 2) asm volatile("ld.relaxed.gpu.global.v2.u32 {%0,%1}, [%2];" : "=r"(cs[0]), "=r"(cs[1]) : "l"(cr0) : "memory");
        else asm volatile("ld.relaxed.gpu.global.v4.u32 {%0,%1,%2,%3}, [%4];" : "=r"(cs[0]), "=r"(cs[1]), "=r"(cs[2]), "=r"(cs[3]) : "l"(cr0) : "memory");
        cs[V] = ld_rlx32(reinterpret_cast<const uint32_t*>(cr1));
    };
    sample();
    uint32_t c[5];
    TK_DECL
#pragma unroll 1
    for (int r = 0;; r++) {
        const uint32_t R = base + r, ninit = h::init(R + 1), done = prim;
        TK(5)
        mbar_wait(sb + B_FULL + (HOP - 1) * 8, r & 1);
        TK(0)
        if (V == 2) asm volatile("ld.shared.v2.u32 {%0,%1}, [%2];" : "=r"(c[0]), "=r"(c[1]) : "r"(ca0) : "memory");
        else asm volatile("ld.shared.v4.u32 {%0,%1,%2,%3}, [%4];" : "=r"(c[0]), "=r"(c[1]), "=r"(c[2]), "=r"(c[3]) : "r"(ca0) : "memory");
        c[V] = lds32(ca1);
        uint32_t nc[5];
#pragma unroll
        for (int k = 0; k <= V; k++) {
            const uint32_t z = ninit + (k < V ? rot0 + k * 16 : rot1);
            nc[k] = min(max(c[k] + (ninit - init - h::S * h::INC), z), z + (h::CAP - h::S) * h::INC);
        }
        if (V == 2) sts64(ca0, nc[0], nc[1]); else sts128<0>(ca0, make_uint4(nc[0], nc[1], nc[2], nc[3]));
        sts32(ca1, lane < V ? nc[V] : lane < V + NDUM ? DUMMY : r);
        __syncwarp();
        if (lane == 0) mbar_arrive(sb + B_OPEN + (HOP - 1) * 8);
        TK(1)
        TK(2)
        asm volatile("fence.proxy.async.shared::cta;" ::: "memory");
        TK(6)
        if (r >= D) {
            int it = 0;
            while (true) {
                uint32_t bad = 0;
#pragma unroll
                for (int k = 0; k <= V; k++) bad |= cs[k] - (R - D + 1);
                if (!__any_sync(0xffffffffu, bad >> 20)) break;
                if (++it > SPIN_LIMIT) __trap();
                if (it > CRED_SKIP) __nanosleep(CRED_NS);
                sample();
            }
        }
        TK(3)
        if (elect()) {
            const uint32_t dB = (HOP == 1 ? dA ^ 0x10000u : dA) + (up ? 8192 : -8192), sm = prim + (lo ? 2 * PB : 0);
            bulk_store(dA, dhi, sm, 8192);
            bulk_store(dB, dhi, HOP == 1 ? sm + 8192 : prim + 68 * PB, 8192);
            if (n0 > 0) bulk_store(dM + (a0 - 64) * PB, mhi, prim + (a0 - lo) * PB, n0);
            if (a1 < (b1 - lo) * PB) bulk_store((dM ^ 4096u) + (uint32_t)((lo - NLO) * PB + a1), mhi, prim + a1, (b1 - lo) * PB - a1);
            asm volatile("cp.async.bulk.commit_group;" ::: "memory");
            asm volatile("cp.async.bulk.wait_group.read 0;" ::: "memory");
        }
        __syncwarp();
        TK(4)
        prim = HOP == 1 ? prim ^ 0x20000u : prim >= sb + 0x30000u ? sb : prim + (prim - sb) + 0x10000u;
        if (r == RT - 1) break;
        reset<HOP>(done, lane, R + HOP + 1);
        if (HOP == 1) {
            __syncwarp();
            if (lane == 0) mbar_arrive(sb + B_FREE);
        }
        if (r == D - 1 || r == RT - D - 1) {
            uint32_t n = NHI, m = NLO;
            if (r < RT - D - 1) {
                int it = 0;
                while (true) {
                    n = ld_rlx32(reinterpret_cast<const uint32_t*>(p.ring + M_CNT + (side << 12)));
                    if ((n & 0xffffu) + (n >> 16) == NB) break;
                    if (++it > SPIN_LIMIT) __trap();
                }
                m = n = min(max(__reduce_or_sync(0xffffffffu, n) & 0xffffu, (uint32_t)NLO), (uint32_t)NHI);
            }
            n0 = (min((int)n, hi) - a0) * PB;
            a1 = (max((int)m, lo) - lo) * PB;
        }
        sample();
        slot_next(dA, st); slot_next(dM, st);
        st = slot_rot(st);
        init = ninit;
    }
#pragma unroll 1
    for (int k = 0; k <= V; k++) {
        const uint32_t bin = k < V ? lane * V + k : 32 * V + lane, n = bin < h::NBIN ? min((pick(k, c) - init) >> h::SH, (uint32_t)h::CAP) : 0u;
#pragma unroll 1
        for (uint32_t x = h::S; x < n; x++) {
            const uint2 w = lds64(prim + bin * PB + ((x + (bin & 7) * 2) & (h::S - 1)) * 8);
            if (HOP == 1) slow_rec1(p, w.x, w.y, bin);
            else slow_rec2(p, w.x, w.y, bin, __uint_as_float(lds32(sb + W_UNIT)));
        }
    }
    asm volatile("cp.async.bulk.wait_group 0;" ::: "memory");
    TK_OUT
}

#define POLL_NS 200
#define POLL_NS3 1500
template <int HOP> struct Reader {
    uint32_t lo, hi, st, line;
    uint32_t* cred;
    __device__ __forceinline__ void init(const Params& p, uint32_t sb, int w, int lane, int role, uint32_t base) {
        constexpr int PB = H<HOP>::S * 8;
        const int first = HOP == 1 ? (role >= NG ? NG : 0) + w * J : w * 2 * J;
        const Ring rg(p.ring, lds32(sb + W_PAR), 2 * w + HOP - 1);
        const uint32_t side = lds32(sb + W_SIDE);
        const bool mid = side ? role < 68 : role >= 64;
        const uint32_t i = role - (side ? (mid ? NLO : 68) : (mid ? 64 : 0));
        const uint32_t c = HOP == 1 ? i >> 5 : lane >> 4, in = HOP == 1 ? (i & 31) * PB + lane * 8 : i * PB + (lane & 15) * 8;
        lo = (in + (mid ? ((uint32_t)rg.mid ^ side << 12) + c * 1024 : (uint32_t)rg.main + (c << 16) + (side ^ rg.par ^ c ? 4096 : 12288))) ^ slot_off(base % 3);
        hi = __reduce_or_sync(0xffffffffu, (uint32_t)((mid ? rg.mid : rg.main) >> 32));
        st = slot_steps(base);
        line = HOP == 1 ? 2 * (role % NG) : role;
        const bool both = first >= NLO && first < NHI;
        cred = lane < 1 + both ? reinterpret_cast<uint32_t*>(rg.main + MISC + (((both ? lane : first >= NG) ^ rg.par) << 12) + cred_off(role)) : nullptr;
    }
    template <int K> __device__ __forceinline__ void load1(uint2& v) const {
        asm volatile("ld.relaxed.gpu.global.v2.u32 {%0,%1}, [%2+%3];" : "=r"(v.x), "=r"(v.y) : "l"(mk_ptr(lo, hi)), "n"(src_off(K)) : "memory");
    }
    template <int K> __device__ __forceinline__ void again(uint2& v, uint32_t want, uint32_t mask) const {
        if (__ballot_sync(0xffffffffu, xor_and<H<HOP>::TAG>(HOP == 1 ? v.x : v.y, want)) & mask) load1<K>(v);
    }
    __device__ __forceinline__ void load(uint2 (&rec)[J]) const {
        load1<0>(rec[0]); load1<1>(rec[1]); load1<2>(rec[2]); load1<3>(rec[3]); load1<4>(rec[4]); load1<5>(rec[5]);
    }
    __device__ __forceinline__ void check(uint2 (&rec)[J], uint32_t R, uint32_t ns TK_ARG) {
        const uint32_t want = H<HOP>::tag(R);
        const uint32_t mask = 0x1111u << H<HOP>::mark(R, line) | 0x11110000u << H<HOP>::mark(R, line + 2 - HOP);
        int it = 0;
        while (true) {
            uint32_t bad = 0;
#pragma unroll
            for (int j = 0; j < J; j++) bad |= (HOP == 1 ? rec[j].x : rec[j].y) ^ want;
            if (!(__ballot_sync(0xffffffffu, bad & H<HOP>::TAG) & mask)) break;
            if (++it > SPIN_LIMIT) __trap();
            __nanosleep(ns);
            TK_CNT(7)
            again<0>(rec[0], want, mask); again<1>(rec[1], want, mask); again<2>(rec[2], want, mask);
            again<3>(rec[3], want, mask); again<4>(rec[4], want, mask); again<5>(rec[5], want, mask);
        }
        if (cred) st_rlx32(cred, R + 1);
        if (CSYNC >> HOP & 1) __syncwarp();
        slot_next(lo, st);
        st = slot_rot(st);
    }
    __device__ __forceinline__ void finish() const { if (cred) st_rlx32(cred, 0u); }
};

#define NPROBE 9
__device__ __forceinline__ uint32_t near_half(unsigned char* pair, uint32_t zero) {
#pragma unroll
    for (int i = 0; i < 4; i++) *reinterpret_cast<uint4*>(pair + (i >> 1) * 4096 + (i & 1) * 16) = make_uint4(0u, 0u, 0u, 0u);
    uint32_t best[2] = {~0u, ~0u}, v = 0, prev = 0;
    asm volatile("red.relaxed.gpu.global.add.u32 [%0], 1;" ::"l"(pair + 4096) : "memory");
#pragma unroll
    for (int t = 0; t <= NPROBE; t++) {
        uint32_t now;
        asm volatile("atom.relaxed.gpu.global.add.u32 %0, [%1], 1;" : "=r"(v) : "l"(pair + (t & 1) * 4096 + (v & zero)) : "memory");
        asm volatile("mov.u32 %0, %%clock;" : "=r"(now) :: "memory");
        if (t > 1) best[(t - 1) & 1] = min(best[(t - 1) & 1], now - prev);
        prev = now;
    }
    return (best[1] < best[0] ? 1u : 0u) | (v & zero);
}
template <bool B> struct BoolC { static constexpr bool value = B; };

template <int NP>
__device__ __forceinline__ void stage1(const Params& p, uint32_t sb, const int pos0, int lane, uint32_t base) {
    typedef H<1> h;
    const int RT = p.rounds;
    uint32_t ff = *reinterpret_cast<const uint16_t*>(p.ang_freq) * 0x10001u;
    auto pair_of = [&](int r, int pos) {
        const int q = r < RT - 1 ? (r * NB + blockIdx.x) * NPR + pos : (RT - 1) * NB * NPR + blockIdx.x * p.lastn + pos;
        return (r < RT - 1 || (r == RT - 1 && pos < p.lastn)) && q < p.T2 ? q : -1;
    };
    uint2 vi[NP], vo[NP]; uint32_t va[NP];
    auto load_edge = [&](int r) {
#pragma unroll
        for (int u = 0; u < NP; u++) {
            const int q = max(pair_of(r, pos0 + u * 32), 0);
            vi[u] = ld_in(p.idx_in + q); vo[u] = ld_in(p.idx_out + q); va[u] = ld_in(p.angle + q);
        }
    };
    load_edge(0);
    if (blockIdx.x == 0 && pos0 == 0 && (p.T & 1)) {
        const int t = p.T - 1;
        slow_triplet(p, reinterpret_cast<const uint32_t*>(p.idx_in)[t], reinterpret_cast<const uint32_t*>(p.idx_out)[t],
                     bf16r(cos_bf(hmul_bf2(reinterpret_cast<const uint16_t*>(p.angle)[t], ff) & 0xffffu)));
    }
    for (int i = threadIdx.x * 16; i < p.R2 && blockIdx.x * p.R2 + i < p.E; i += NS1 * 32 * 16) prefetch_l2(p.m + blockIdx.x * p.R2 + i);
    uint32_t R = __reduce_or_sync(0xffffffffu, base);
    ff = __reduce_or_sync(0xffffffffu, ff);
    bar_sync(BAR_S1, (NS1 + 1) * 32);
    TK_DECL
    auto step = [&](const int r, const int qn, auto edge) {
        constexpr bool EDGE = decltype(edge)::value;
        uint32_t cc[NP], big = 0;
#pragma unroll
        for (int u = 0; u < NP; u++) {
            va[u] = hmul_bf2(va[u], ff);
            cc[u] = pack_bf2(__cosf(bf_lo(va[u])), __cosf(bf_hi(va[u])));
            big = __vmaxu2(big, va[u] & 0x7fff7fffu);
        }
        if ((big + (0x7fffu - BIGX) * 0x10001u) & 0x80008000u) {
#pragma unroll 1
            for (int u = 0; u < NP; u++) {
                const uint32_t a = pick(u, va);
                float c0 = cos_bf(a & 0xffffu), c1 = cos_bf(a >> 16);
                if ((c0 != c0 || c1 != c1) && (!EDGE || pair_of(r, pos0 + u * 32) >= 0)) {
                    const uint2 i2 = pick(u, vi), o2 = pick(u, vo);
                    if (c0 != c0) slow_triplet(p, i2.x, o2.x, c0);
                    if (c1 != c1) slow_triplet(p, i2.y, o2.y, c1);
                }
                const uint32_t v = pack_bf2(c0 != c0 ? 0.f : c0, c1 != c1 ? 0.f : c1);
#pragma unroll
                for (int k = 0; k < NP; k++) if (k == u) cc[k] = v;
            }
        }
        uint32_t bin[2 * NP], x[2 * NP], y[2 * NP];
        uint32_t dep = 0;
        auto loads = [&]() {
            const int q = qn + (dep & p.zero);
#pragma unroll
            for (int u = 0; u + 1 < NP; u += 2) { tex2(p.ta, q + u * 16, va[u], va[u + 1]); tex4(p.to, q + u * 16, vo[u], vo[u + 1]); tex4(p.ti, q + u * 16, vi[u], vi[u + 1]); }
            if (NP & 1) {
                const int k = 2 * q - lane + (NP - 1) * 32;
                va[NP - 1] = ld_in(p.angle + k); vo[NP - 1] = ld_in(p.idx_out + k); vi[NP - 1] = ld_in(p.idx_in + k);
            }
        };
#pragma unroll
        for (int j = 0; j < 2 * NP; j++) {
            const uint32_t ii = j & 1 ? vi[j >> 1].y : vi[j >> 1].x, oo = j & 1 ? vo[j >> 1].y : vo[j >> 1].x;
            bin[j] = __umulhi(ii, p.mg1);
            y[j] = __byte_perm(bin[j] * p.k1 + ii, cc[j >> 1], j & 1 ? 0x7610 : 0x5410);
            const uint32_t bo = __umulhi(oo, p.mg2);
            x[j] = __byte_perm(bo * p.k2 + oo * 8u, bo, 0x0514);
            dep |= x[j] | y[j];
            if (EDGE && pair_of(r, pos0 + (j >> 1) * 32) < 0) bin[j] = NG + (lane & (NDUM - 1));
        }
        if (EDGE) load_edge(r + 1);
        else loads();
        const uint32_t init = h::init(R), kb = sb + h::win(R + 1), lim = init + (h::CAP << h::SH);
        TK(0)
        mbar_wait(sb + B_OPEN, ~R & 1);
        TK(1)
        bool freed = false;
        uint32_t over = 0;
#pragma unroll
        for (int g = 0; g < 2 * NP; g += G1) {
            constexpr int G = G1;
            uint32_t ret[G];
            int mx = 0;
#pragma unroll
            for (int j = 0; j < G; j++) if (g + j < 2 * NP) ret[j] = atoms_add<h::CNT>(sb + bin[g + j] * 4, h::INC);
#pragma unroll
            for (int j = 0; j < G; j++) if (g + j < 2 * NP) mx = j ? max(mx, (int)ret[j]) : (int)ret[j];
            if (!DEFER && !freed && __any_sync(0xffffffffu, mx >= (int)(init + 0x10000u))) { TK(2) mbar_wait(sb + B_FREE, ~R & 1); freed = true; TK(3) }
            TK(2)
#pragma unroll
            for (int j = 0; j < G; j++) if (g + j < 2 * NP) {
                x[g + j] = and_or<h::TAG>(ret[j], x[g + j]);
                if (DEFER) {
                    bin[g + j] = and_xor(EDGE ? ret[j] | (ret[j] >> 14 & 0x20000u) : ret[j], 0x20000u | h::PM, bin[g + j] * 256 + kb);
                    put_rec<h::STG>(ret[j], init + 0x10000u, bin[g + j], x[g + j], y[g + j]);
                } else put_rec<h::STG>(ret[j], lim, and_xor(ret[j], 0x20000u | h::PM, bin[g + j] * 256 + kb), x[g + j], y[g + j]);
            }
            if (mx >= (int)lim) {
#pragma unroll
                for (int j = 0; j < G; j++) if (g + j < 2 * NP && (int)ret[j] >= (int)lim) { over |= 1u << (g + j); if (DEFER) bin[g + j] = mux(bin[g + j], ~kb, 0x20000u); }
            }
        }
        if (!DEFER || !EDGE) { __syncwarp(); if (elect()) mbar_arrive(sb + B_FULL); }
        if (DEFER) {
            TK(4)
            mbar_wait(sb + B_FREE, ~R & 1);
            TK(3)
#pragma unroll
            for (int j = 0; j < 2 * NP; j++) put_rec<h::STG>(xor_and<0x20000u>(bin[j], kb), 1u, bin[j], x[j], y[j]);
            if (EDGE) { __syncwarp(); if (elect()) mbar_arrive(sb + B_FULL); }
        }
        R++;
        TK(4)
#pragma unroll 1
        while (over) {
            TK_CNT(7)
            const int j = __ffs(over) - 1;
            over &= over - 1;
            slow_rec1(p, pick(j, x), pick(j, y), DEFER ? (pick(j, bin) - sb) >> 8 & 0xffu : pick(j, bin));
        }
        __syncwarp();
    };
#pragma unroll 1
    for (int q = (NB + blockIdx.x) * NPR; q < p.qfull; q += NB * NPR) step(q / (NB * NPR) - 1, (q + pos0 + lane) >> 1, BoolC<false>());
#pragma unroll 1
    for (int r = max(p.qfull / (NB * NPR) - 1, 0); r < RT; r++) step(r, 0, BoolC<true>());
    TK_OUT
}

__device__ __forceinline__ void stage2(const Params& p, uint32_t sb, int w, int lane, int role, uint32_t base) {
    typedef H<2> h;
    const int RT = p.rounds;
    Reader<1> rd;
    rd.init(p, sb, w, lane, role, base);
    uint2 rec[J];
    rd.load(rec);
    bar_sync(BAR_TABLE, 2 * NC * 32);
    uint32_t kb = sb + 0x10000u, am = 0x10000u | h::PM;
    const float unit = __uint_as_float(__reduce_or_sync(0xffffffffu, lds32(sb + W_UNIT)));
    TK_DECL
#pragma unroll 1
    for (int r = 0; r < RT; r++) {
        rd.check(rec, base + r, POLL_NS TK_PASS);
        const uint32_t want = H<1>::tag(base + r);
        TK(0)
        uint2 mv[J];
#pragma unroll
        for (int j = 0; j < J; j++) mv[j] = lds64<OFF_M>(sb + (rec[j].y & 0xffffu) * 8);
        uint32_t fl = 0;
#pragma unroll
        for (int j = 0; j < J; j++) fl |= mv[j].y;
        if (fl & 0x40000000u) {
#pragma unroll 1
            for (int j = 0; j < J; j++) {
                const uint2 v = pick(j, mv), w = pick(j, rec);
                if ((v.y & 0x40000000u) && !((w.x ^ want) & 0xf00000u)) {
                    if (v.x & 0x40000000u) slow_rec1(p, w.x, w.y, lds32(sb + W_ROLE) % NG);
                    else {
                        const float c = bf_hi(w.y), s = __uint_as_float(lds32(sb + W_UNIT)) * 1024.f;
                        side_add(w.x & 0xffu, __byte_perm(w.x, 0u, 0x4413) >> 3, c * (bf_lo(v.x) * s), c * (bf_hi(v.x) * s),
                                 c * (bf_lo(v.y) * s), c * (bf_hi(v.y & 0xbfffffffu) * s));
                    }
                }
            }
#pragma unroll
            for (int j = 0; j < J; j++) if (mv[j].y & 0x40000000u) rec[j].x = 0x800000u;
        }
        uint32_t w0[J], w1[J], bin[J], ret[J];
#pragma unroll
        for (int j = 0; j < J; j++) {
            const float c = bf_hi(rec[j].y), MG = 8194.0f;
            const uint32_t x = rec[j].x;
            w0[j] = and_or<0xf000f000u>(x, __byte_perm(__float_as_uint(fmaf(c, bf_lo(mv[j].x), MG)), __float_as_uint(fmaf(c, bf_hi(mv[j].x), MG)), 0x5410));
            w1[j] = and_or<0xf000f000u>(x << 4, __byte_perm(__float_as_uint(fmaf(c, bf_lo(mv[j].y), MG)), __float_as_uint(fmaf(c, bf_hi(mv[j].y), MG)), 0x5410));
            bin[j] = min(xor_and<0xf000ffu>(x, want), NB + (lane & (NDUM - 1)));
        }
        const uint32_t lim = h::init(base + r) + 0x20000u;
        rd.load(rec);
        TK(1)
        mbar_wait(sb + B_OPEN + 8, (r - 1) & 1);
        TK(2)
#pragma unroll
        for (int j = 0; j < J; j++) ret[j] = atoms_add<h::CNT>(sb + bin[j] * 4, h::INC);
        uint32_t mx = 0;
#pragma unroll
        for (int j = 0; j < J; j++) {
            w1[j] = and_or<h::TAG>(ret[j], w1[j]);
            put_rec<0>(ret[j], lim, and_xor(ret[j], am, bin[j] * 128 + kb), w0[j], w1[j]);
            mx = __viaddmax_u32(ret[j], 0u - DUMMY, mx);
        }
        __syncwarp();
        if (lane == 0) mbar_arrive(sb + B_FULL + 8);
        TK(3)
        if (mx >= lim - DUMMY) {
            uint32_t over = 0;
#pragma unroll
            for (int j = 0; j < J; j++) if (ret[j] - DUMMY >= lim - DUMMY) over |= 1u << j;
#pragma unroll 1
            do {
                const int j = __ffs(over) - 1;
                over &= over - 1;
                slow_rec2(p, pick(j, w0), pick(j, w1), pick(j, bin), unit);
            } while (over);
        }
        __syncwarp();
        am = am >= 0x30000u ? 0x10000u | h::PM : am + 0x10000u;
        kb ^= am & 0x30000u;
        TK(4)
    }
    rd.finish();
    TK_OUT
}

__device__ __forceinline__ float2 acc_fix(uint32_t old, uint32_t q) {
    const uint32_t u = old + 0x40004000u, n = u + q - 0x08000800u;
    return make_float2((float)((int)(u & 0xffffu) + (int)(q & 0xffffu) - 2048 - (int)(n & 0xffffu)), (float)((int)(u >> 16) + (int)(q >> 16) - 2048 - (int)(n >> 16)));
}
__device__ __forceinline__ void stage3(const Params& p, uint32_t sb, int w, int lane, int role, uint32_t base) {
    const int RT = p.rounds;
    Reader<2> rd;
    rd.init(p, sb, w, lane, role, base);
    uint2 rec[J];
    bar_sync(BAR_TABLE, 2 * NC * 32);
    TK_DECL
#pragma unroll 1
    for (int r = 0; r < RT; r++) {
        if (LAG) { const int need = min(r + 1, RT - 1); if ((int)lds32(sb + W_RND) < need) mbar_wait(sb + B_OPEN + 8, need & 1); }
        rd.load(rec);
        rd.check(rec, base + r, r < RT - 2 ? POLL_NS3 : 100 TK_PASS);
        TK(0)
        const uint32_t want = H<2>::tag(base + r), t = 0u - (lane & 1u), k = (t & 1u << 26) - (want >> 4);
        uint32_t o0[J], o1[J], g = 0;
#pragma unroll
        for (int j = 0; j < J; j++) {
            o0[j] = 0; o1[j] = 0;
            if (!xor_and<H<2>::TAG>(rec[j].y, want)) {
                const uint32_t a = aux_of(rec[j].x, rec[j].y, k) + (j >= G3 ? (o0[j - G3] | o1[j - G3]) & p.zero : 0u);
                const uint32_t v0 = (rec[j].x & 0x0fff0fffu) - 0x08000800u, v1 = (rec[j].y & 0x0fff0fffu) - 0x08000800u;
                o0[j] = atoms_add<OFF_ACC>(sb + a, mux(v0, v1, t));
                o1[j] = atoms_add<OFF_ACC>(sb + (a ^ 4u), mux(v1, v0, t));
            }
        }
#pragma unroll
        for (int j = 0; j < J; j++) g |= o0[j] | o1[j];
        if (__any_sync(0xffffffffu, g & 0x80008000u)) {
#pragma unroll 1
            for (int j = 0; j < J; j++) {
                const uint2 w = pick(j, rec);
                const uint32_t aux = aux_of(w.x, w.y), p0 = pick(j, o0), p1 = pick(j, o1);
                const float2 a = acc_fix(t ? p1 : p0, w.x & 0x0fff0fffu), b = acc_fix(t ? p0 : p1, w.y & 0x0fff0fffu);
                const float unit = __uint_as_float(lds32(sb + W_UNIT));
                if (!((w.y ^ want) & H<2>::TAG) && (a.x != 0.f || a.y != 0.f || b.x != 0.f || b.y != 0.f))
                    side_add(lds32(sb + W_ROLE), aux >> 3, a.x * unit, a.y * unit, b.x * unit, b.y * unit);
                __syncwarp();
            }
        }
        TK(1)
    }
    rd.finish();
    TK_OUT
}

__device__ __forceinline__ uint32_t row_max(uint32_t x, uint32_t y) {
    const uint32_t mx = __vmaxu2(x & 0x7fff7fffu, y & 0x7fff7fffu);
    return max(mx & 0xffffu, mx >> 16);
}
constexpr int EWIN = 5;

__global__ void __launch_bounds__(NTHR, 1) fused_kernel(const Params p) {
    const int tid = threadIdx.x, lane = tid & 31;
    const int hw = __reduce_max_sync(0xffffffffu, tid >> 5);
    const uint32_t sb = __reduce_or_sync(0xffffffffu, (uint32_t)__cvta_generic_to_shared(smem));
    TKX(0)
    const uint32_t epoch = ld_rlx32(&g_base);
    uint32_t base = epoch & 31u;

    if (hw < NS1) {
        if (hw < NS1 - 1 || NPR == 1024) stage1<4>(p, sb, hw * 128 + lane, lane, base);
        else stage1<NPR / 32 - (NS1 - 1) * 4>(p, sb, hw * 128 + lane, lane, base);
        __threadfence();
        bar_arrive(BAR_DONE, (NS1 + NC + 2) * 32);
    } else if (hw == W_M1) {
        if (lane == 0) {
            if (sb & 255u) __trap();
            mbar_init(sb + B_FULL, NS1); mbar_init(sb + B_OPEN, 1); mbar_init(sb + B_FREE, 1);
        }
        base = __reduce_or_sync(0xffffffffu, base);
        if (lane == 0 && (base & 1u)) { mbar_arrive(sb + B_OPEN); mbar_arrive(sb + B_FREE); }
        for (int i = lane; i < NG + NDUM; i += 32) sts32(sb + OFF_CNT1 + i * 4, i < NG ? H<1>::init(base) + (i & 7) * 16 : DUMMY);
#pragma unroll 1
        for (int i = 0; i < 2; i++) fill<1>(sb + OFF_H1 + H<1>::win(base + i), lane, base + i);
        bar_arrive(BAR_S1, (NS1 + 1) * 32);
        bar_sync(BAR_PROBE, (2 * NC + 1) * 32);
        {
            const uint32_t raw = __ballot_sync(0xffffffffu, lane < 2 * NC && smem[OFF_PROBE + lane]), side = raw & 1u;
            uint32_t v = 0;
            if (lane < 2) asm volatile("atom.relaxed.gpu.global.add.u32 %0, [%1], %2;" : "=r"(v) : "l"(p.ring + M_CNT + lane * 4096), "r"(side ? 0x10000u : 1u) : "memory");
            const uint32_t mine = (side ? ~raw : raw) | 0x80000000u;
            if (lane == 2) asm volatile("atom.relaxed.gpu.global.cas.b32 %0, [%1], 0, %2;" : "=r"(v) : "l"(p.ring + M_PAR), "r"(mine) : "memory");
            bar_sync(BAR_HIST, (2 * NC + 1) * 32);
            uint32_t best = 0;
#pragma unroll 1
            for (int e = 11 + lane; e <= 230; e += 32) {
                uint32_t c = 0;
#pragma unroll
                for (int i = 0; i < EWIN; i++) c += lds32(sb + OFF_HIST + (e - i) * 4);
                best = max(best, c << 8 | (255 - e));
            }
            const uint32_t e = 255 - (__reduce_max_sync(0xffffffffu, best) & 255u);
            if (lane == 0) {
                const uint32_t role = side ? NB - 1 - (v >> 16) : v & 0xffffu;
                sts32(sb + W_ROLE, role); sts32(sb + W_SIDE, role < NLO ? 0u : role >= NHI ? 1u : side);
                sts32(sb + W_EXP, e); sts32(sb + W_UNIT, (e - 10) << 23); sts32(sb + W_END, (epoch | 31u) + 1u + (base + p.rounds) % 24u);
            }
            if (lane == 2) sts32(sb + W_PAR, v ? v : mine);
        }
        bar_sync(BAR_ROLE, (2 * NC + 2) * 32);
        manager<1>(p, sb, lane, __reduce_max_sync(0xffffffffu, lds32(sb + W_ROLE)), base);
        bar_arrive(BAR_H1, (NS1 + 1) * 32);
        __threadfence();
        bar_arrive(BAR_DONE, (NS1 + NC + 2) * 32);
    } else if (hw == W_M2) {
        const float wd = __bfloat162float(lane & 16 ? p.w_up[lane & 15] : p.w_down[lane & 15]);
        const float ws = __bfloat162float(p.w_sbf[lane]), wr = __bfloat162float(p.w_rbf[lane]);
        const __nv_bfloat16 cen = p.centers[lane & 7];
        if (lane == 0) { mbar_init(sb + B_FULL + 8, NC); mbar_init(sb + B_OPEN + 8, 1); }
        base = __reduce_or_sync(0xffffffffu, base);
        for (int i = lane; i <= NB + NDUM; i += 32) sts32(sb + OFF_CNT2 + i * 4, i < NB ? H<2>::init(base) + (i & 7) * 16 : DUMMY);
#pragma unroll 1
        for (int i = 0; i < 3; i++) fill<2>(sb + H<2>::win(i), lane, base + i);
        reinterpret_cast<float*>(smem + OFF_WSM)[lane] = wd;
        reinterpret_cast<float*>(smem + OFF_WG)[lane] = ws;
        reinterpret_cast<float*>(smem + OFF_WG + 128)[lane] = wr;
        reinterpret_cast<__nv_bfloat16*>(smem + OFF_WG + 256)[lane & 7] = cen;
        bar_sync(BAR_ROLE, (2 * NC + 2) * 32);
        manager<2>(p, sb, lane, __reduce_max_sync(0xffffffffu, lds32(sb + W_ROLE)), base);
        __threadfence();
        bar_sync(BAR_DONE, (NS1 + NC + 2) * 32);
        if (lane < 2) { __threadfence(); st_rlx32(reinterpret_cast<uint32_t*>(p.ring + M_FLAG + lane * 4096) + blockIdx.x, lds32(sb + W_END)); }
    } else {
        const int pw = __reduce_max_sync(0xffffffffu, hw < W_M1 ? hw - NS1 : hw - NS1 - 1), ct = pw * 32 + lane;
        constexpr int CT = 2 * NC * 32;
        const uint4 sm = __ldg(reinterpret_cast<const uint4*>(p.m) + min((ct >> 3) * (p.E >> 1) / (CT / 8) + (lane & 7), (p.E >> 1) - 1));
        if (ct < 256) sts32(sb + OFF_HIST + ct * 4, 0u);
        if (lane == 0) smem[OFF_PROBE + pw] = pw < NPAGE ? near_half(p.ring + (size_t)pw * PAGE + PROBE + (blockIdx.x & 31) * 128 + (blockIdx.x >> 5 & 3) * 16384 + (blockIdx.x >> 7 << 20), p.zero) : 0;
        TKX(1)
        bar_sync(BAR_PROBE, (2 * NC + 1) * 32);
        {
            const uint32_t m0 = row_max(sm.x, sm.y), m1 = row_max(sm.z, sm.w);
            if (m0) atoms_add<OFF_HIST>(sb + (m0 >> 7) * 4, 1u);
            if (m1) atoms_add<OFF_HIST>(sb + (m1 >> 7) * 4, 1u);
        }
        bar_arrive(BAR_HIST, (2 * NC + 1) * 32);
        base = __reduce_or_sync(0xffffffffu, base);
        for (int i = ct; i < R2MAX / 2; i += CT) reinterpret_cast<uint4*>(smem + OFF_ACC)[i] = make_uint4(0x40004000u, 0x40004000u, 0x40004000u, 0x40004000u);
        bar_sync(BAR_ROLE, (2 * NC + 2) * 32);
        const int role = __reduce_max_sync(0xffffffffu, lds32(sb + W_ROLE));
        TKX(2)
        {
            const int e = lds32(sb + W_EXP), q0 = (role >= NG ? role - NG : role) * (p.R1 >> 1), nq = min(p.R1 >> 1, (p.E >> 1) - q0);
            const uint32_t sc = (uint32_t)(254 - e) * 0x800080u;
            constexpr int CH = (R1MAX / 2 + CT - 1) / CT;
            uint4 v[CH];
#pragma unroll
            for (int u = 0; u < CH; u++) v[u] = __ldg(reinterpret_cast<const uint4*>(p.m) + min(q0 + ct + u * CT, (p.E >> 1) - 1));
            auto conv = [&](uint32_t& x, uint32_t& y) {
                const uint32_t mx = row_max(x, y);
                const int d = e - (int)(mx >> 7);
                x = hmul_bf2(x, sc); y = hmul_bf2(y, sc);
                if (d >= EWIN) y |= 0x40000000u;
                if (d < 0 || (d >= EWIN && e > 127)) { x = 0x40000000u; y = x; }
                if (mx == 0) { x = 0; y = 0; }
            };
#pragma unroll
            for (int u = 0; u < CH; u++) {
                conv(v[u].x, v[u].y); conv(v[u].z, v[u].w);
                if (ct + u * CT < nq) sts128<OFF_M>(sb + (ct + u * CT) * 16, v[u]);
            }
        }
        TKX(3)
        if (hw < W_M1) {
            stage2(p, sb, pw, lane, role, base);
            __threadfence();
            bar_arrive(BAR_DONE, (NS1 + NC + 2) * 32);
        } else {
            stage3(p, sb, pw - NC, lane, role, base);
            __threadfence();
        }
    }
    TKX(4)
    epilogue(p, sb);
}

__global__ void fb_scatter(const uint2* __restrict__ m, const int* __restrict__ idx_in, const int* __restrict__ idx_out,
                           const uint16_t* __restrict__ angle, const __nv_bfloat16* __restrict__ ang_freq, int T, int e0, int e1) {
    const uint32_t fb = *reinterpret_cast<const uint16_t*>(ang_freq);
    for (long long t = blockIdx.x * (long long)blockDim.x + threadIdx.x; t < T; t += (long long)gridDim.x * blockDim.x) {
        int o = idx_out[t];
        if (o < e0 || o >= e1) continue;
        float c = bf16r(cos_bf(hmul_bf2(angle[t], fb) & 0xffffu));
        uint2 v = __ldg(m + idx_in[t]);
        red4(&g_ovf[o - e0], c * bf_lo(v.x), c * bf_hi(v.x), c * bf_lo(v.y), c * bf_hi(v.y));
    }
}
__global__ void fb_final(const Params p, int e0, int e1) {
    int e = e0 + blockIdx.x * blockDim.x + threadIdx.x;
    if (e >= e1) return;
    float4 a4 = g_ovf[e - e0];
    g_ovf[e - e0] = make_float4(0.f, 0.f, 0.f, 0.f);
    float a[4] = {a4.x, a4.y, a4.z, a4.w};
    float d = __bfloat162float(p.dist[e]);
    float g[4] = {0, 0, 0, 0}, h[4] = {0, 0, 0, 0};
    for (int r = 0; r < 8; r++) {
        float df = bf16r(d - __bfloat162float(p.centers[r]));
        float rb = bf16r(expf(bf16r(-10.0f * bf16r(df * df))));
        for (int k = 0; k < 4; k++) {
            g[k] += rb * __bfloat162float(p.w_sbf[r * 4 + k]);
            h[k] += rb * __bfloat162float(p.w_rbf[r * 4 + k]);
        }
    }
    float ag[4];
    for (int k = 0; k < 4; k++) {
        float s = 0.f;
        for (int j = 0; j < 4; j++) s += a[j] * __bfloat162float(p.w_down[j * 4 + k]);
        ag[k] = bf16r(s * g[k]);
    }
    uint2 mv = p.m[e];
    float mm[4] = {bf_lo(mv.x), bf_hi(mv.x), bf_lo(mv.y), bf_hi(mv.y)};
    __nv_bfloat16 o[4];
    for (int k = 0; k < 4; k++) {
        float u = 0.f;
        for (int j = 0; j < 4; j++) u += ag[j] * __bfloat162float(p.w_up[j * 4 + k]);
        o[k] = __float2bfloat16_rn(mm[k] + bf16r(bf16r(u) * bf16r(h[k])));
    }
    p.out[e] = *reinterpret_cast<uint2*>(o);
}

}

static bool exact_div(int E, int lo, int hi, int* R, uint32_t* magic) {
    for (int r = lo + (lo & 1); r <= hi; r += 2) {
        unsigned long long mg = ((1ull << 32) + r - 1) / r, err = mg * r - (1ull << 32);
        if (err * (unsigned long long)E < (1ull << 32)) { *R = r; *magic = (uint32_t)mg; return true; }
    }
    return false;
}

static cudaTextureObject_t make_tex(const void* ptr, size_t bytes, int words) {
    cudaResourceDesc rd = {}; cudaTextureDesc td = {};
    rd.resType = cudaResourceTypeLinear; rd.res.linear.devPtr = const_cast<void*>(ptr); rd.res.linear.sizeInBytes = bytes;
    rd.res.linear.desc = cudaCreateChannelDesc(32, words > 1 ? 32 : 0, words > 2 ? 32 : 0, words > 2 ? 32 : 0, cudaChannelFormatKindUnsigned);
    td.readMode = cudaReadModeElementType;
    cudaTextureObject_t t = 0;
    if (cudaCreateTextureObject(&t, &rd, &td, nullptr) != cudaSuccess) { t = 0; (void)cudaGetLastError(); }
    return t;
}

extern "C" void kernel_launch(void* const* d_in, const int* in_sizes, int n_in, void* d_out, int out_size) {
    typedef const __nv_bfloat16* B;
    Params p;
    p.m = (const uint2*)d_in[0]; p.idx_in = (const uint2*)d_in[1]; p.idx_out = (const uint2*)d_in[2]; p.dist = (B)d_in[3];
    p.angle = (const uint32_t*)d_in[4]; p.centers = (B)d_in[5]; p.ang_freq = (B)d_in[6]; p.w_rbf = (B)d_in[7]; p.w_sbf = (B)d_in[8];
    p.w_down = (B)d_in[9]; p.w_up = (B)d_in[10]; p.out = (uint2*)d_out;
    p.E = in_sizes[3]; p.T = in_sizes[1]; p.T2 = p.T >> 1; p.zero = 0;
    p.R1 = p.R2 = p.rounds = p.lastn = p.qfull = 0; p.mg1 = p.mg2 = p.k1 = p.k2 = 0;
    static int ok = -1;
    static unsigned char* ring = nullptr;
    if (ok < 0) {
        void* ra = nullptr;
        cudaGetSymbolAddress(&ra, g_ring);
        ring = reinterpret_cast<unsigned char*>(((uintptr_t)ra + PAGE - 1) & ~(uintptr_t)(PAGE - 1));
        int dev = 0, sms = 0, occ = 0;
        cudaGetDevice(&dev);
        cudaDeviceGetAttribute(&sms, cudaDevAttrMultiProcessorCount, dev);
        cudaError_t e = cudaFuncSetAttribute(fused_kernel, cudaFuncAttributeMaxDynamicSharedMemorySize, SMEM_BYTES);
        if (e == cudaSuccess) e = cudaOccupancyMaxActiveBlocksPerMultiprocessor(&occ, fused_kernel, NTHR, SMEM_BYTES);
        ok = (e == cudaSuccess && occ >= 1 && sms >= NB) ? 1 : 0;
        (void)cudaGetLastError();
    }
    p.ring = ring;
    static cudaTextureObject_t tx[3];
    if (!tx[0]) { tx[0] = make_tex(p.idx_in, (size_t)(p.T >> 2) * 16, 4); tx[1] = make_tex(p.idx_out, (size_t)(p.T >> 2) * 16, 4); tx[2] = make_tex(p.angle, (size_t)(p.T >> 2) * 8, 2); }
    p.ti = tx[0]; p.to = tx[1]; p.ta = tx[2];
    const bool fused = ok == 1 && p.E <= EMAX && p.E >= 2 * NB && p.E % 2 == 0 && p.T >= 2 && exact_div(p.E, (p.E + NG - 1) / NG, R1MAX, &p.R1, &p.mg1) &&
                       exact_div(p.E, (p.E + NB - 1) / NB, R2MAX, &p.R2, &p.mg2);
    if (fused) {
        p.k1 = 0u - (uint32_t)p.R1; p.k2 = 0u - 8u * (uint32_t)p.R2;
        const int per = NB * NPR;
        int full = p.T2 / per, rest = p.T2 - full * per;
        p.qfull = full * per;
        p.lastn = (rest + NB - 1) / NB;
        if (p.lastn > NPR / 2) { full++; p.lastn = 0; }
        if (full < D) { full = D; p.lastn = 0; }
        p.rounds = full + 1;
        fused_kernel<<<NB, NTHR, SMEM_BYTES>>>(p);
    } else {
        for (int e0 = 0; e0 < p.E; e0 += EMAX) {
            int e1 = p.E - e0 < EMAX ? p.E : e0 + EMAX;
            fb_scatter<<<1056, 256>>>(p.m, (const int*)d_in[1], (const int*)d_in[2], (const uint16_t*)d_in[4], p.ang_freq, p.T, e0, e1);
            fb_final<<<(e1 - e0 + 255) / 256, 256>>>(p, e0, e1);
        }
    }
}
```

```cpp
#include <cuda_runtime.h>
#include <cuda_bf16.h>
#include <stdint.h>

namespace {

constexpr int NB = 132, NG = 66;
constexpr int R2MAX = 6062, R1MAX = 12124;
constexpr int EMAX = NB * R2MAX;
constexpr int NTHR = 1024;
constexpr int NS1 = 8, NC = 11, J = 6;
#define TILES 30
#define TEXIN 1
#define DEFER 0
#define G1 4
#define G3 6
#define CAP1 64
constexpr int NPR = TILES * 32;
constexpr int D = 3;
constexpr int WIN = 16896;
constexpr int NDUM = 16;
constexpr uint32_t DUMMY = 0xc0000000u;

constexpr int OFF_ACC = WIN, OFF_BAR = OFF_ACC + R2MAX * 8;
constexpr int OFF_H1 = 0x10000 + WIN, OFF_M = OFF_H1 + WIN, OFF_WSM = OFF_M + R1MAX * 8;
constexpr int OFF_CNT1 = OFF_H1 + 0x20000 + WIN, OFF_CNT2 = OFF_CNT1 + (NG + NDUM + 2) * 4, W_RND = OFF_CNT2 + (NB + NDUM) * 4, OFF_WG = W_RND + 16;
constexpr int OFF_HIST = OFF_M;
constexpr int OFF_PROBE = OFF_WSM + 128;
constexpr int SMEM_BYTES = OFF_WG + 272;
static_assert(SMEM_BYTES <= 232448 && OFF_BAR + 64 <= 0x10000 && OFF_PROBE + 32 <= 0x30000, "smem");
static_assert(OFF_BAR % 8 == 0 && OFF_WG % 16 == 0 && OFF_WSM % 16 == 0 && OFF_CNT2 % 16 == 0, "align");
static_assert(NC * J == NG && NC * 32 * 6 * 16 == 2 * WIN, "shape");

template <int HOP> struct H {
    static constexpr int S = HOP == 1 ? 32 : 16, NBIN = HOP == 1 ? NG : NB, CAP = HOP == 1 ? CAP1 : 32, SH = HOP == 1 ? 11 : 12;
    static constexpr int TB = HOP == 1 ? 20 : 28, CNT = HOP == 1 ? OFF_CNT1 : OFF_CNT2, STG = HOP == 1 ? OFF_H1 : 0;
    static constexpr uint32_t INC = (1u << SH) + 8u, PM = (S - 1) * 8, TAG = 7u << TB;
    static __device__ __forceinline__ uint32_t tag(uint32_t R) { return R << TB & TAG; }
    static __device__ __forceinline__ uint32_t init(uint32_t R) { return tag(R) | ((1u << TB) - 0x10000u); }
    static __device__ __forceinline__ uint32_t mark(uint32_t R, uint32_t line) { return ((HOP == 1 ? R >> 1 : R) + line) & 3u; }
    static __device__ __forceinline__ uint32_t win(int r) { return HOP == 1 ? (r & 1) << 17 : (0x310u >> (r % 3 * 4) & 3u) << 16; }
};

constexpr uint32_t PAGE = 1u << 21;
constexpr int NPAGE = NC + 2;
__device__ __align__(256) unsigned char g_ring[(size_t)(NPAGE + 1) * PAGE];
constexpr int MISC = 0xa0000;
constexpr int M_CNT = MISC + 1024, M_PAR = MISC + 1088;
constexpr int M_FLAG = MISC + 2048;
constexpr int PROBE = MISC + 0x40000;
#define CSTR 16384
__device__ __forceinline__ uint32_t cred_off(uint32_t role) { return role * 4 + min(role >> 5, 3u) * (CSTR - 128); }
struct Ring {
    uint64_t main, mid;
    uint32_t par;
    __device__ __forceinline__ Ring(const unsigned char* ring, uint32_t pars, int k) {
        main = reinterpret_cast<uint64_t>(ring) + ((uint64_t)k << 20);
        par = pars >> (k >> 1) & 1u;
        mid = reinterpret_cast<uint64_t>(ring) + (uint64_t)NC * PAGE + (((k >> 3 << 20) + (k >> 2 & 1) * 0x11000u + (k & 1) * 2048) ^ (k >> 1 & 1) * 0x3000u ^ (pars >> (NC + (k >> 4)) & 1u) << 12);
    }
};
constexpr int NLO = 60, NHI = 72;
__host__ __device__ constexpr uint32_t src_off(int j) { return (j % 3) << 14 | (j / 3) << 18; }
__device__ __forceinline__ uint32_t slot_off(uint32_t s) { return (0xa930u >> s * 4 & 15u) << 16; }
__device__ __forceinline__ uint32_t slot_steps(uint32_t R) { return (uint32_t)(0x30a09030aull >> (2 - R % 3) * 8) & 0xffffffu; }
__device__ __forceinline__ void slot_next(uint32_t& a, uint32_t st) { a ^= st & 0xf0000u; }
__device__ __forceinline__ uint32_t slot_rot(uint32_t st) { return __byte_perm(st, 0u, 0x4102); }
constexpr int RPAD = 6064, DROW = 6144;
__device__ __align__(128) uint8_t g_dirty[NB * DROW];
__device__ uint32_t g_base = 1;
__device__ __align__(128) float4 g_ovf[NB * RPAD];

struct Params {
    const uint2* m; const uint2* idx_in; const uint2* idx_out; const __nv_bfloat16* dist; const uint32_t* angle;
    const __nv_bfloat16* centers; const __nv_bfloat16* ang_freq; const __nv_bfloat16* w_rbf; const __nv_bfloat16* w_sbf;
    const __nv_bfloat16* w_down; const __nv_bfloat16* w_up; uint2* out; unsigned char* ring;
    cudaTextureObject_t ti, to, ta;
    int E, T, T2, R1, R2, rounds, lastn, qfull; uint32_t mg1, mg2, k1, k2, zero;
};

__device__ __forceinline__ float bf16r(float x) { return __bfloat162float(__float2bfloat16_rn(x)); }
__device__ __forceinline__ float bf_lo(uint32_t v) { return __uint_as_float(v << 16); }
__device__ __forceinline__ float bf_hi(uint32_t v) { return __uint_as_float(v & 0xffff0000u); }
__device__ __forceinline__ void red4(float4* a, float x, float y, float z, float w) {
    asm volatile("red.global.add.v4.f32 [%0], {%1,%2,%3,%4};" ::"l"(a), "f"(x), "f"(y), "f"(z), "f"(w) : "memory");
}
__device__ __forceinline__ void bar_sync(int id, int n) { __syncwarp(); asm volatile("bar.sync %0, %1;" ::"r"(id), "r"(n) : "memory"); }
__device__ __forceinline__ void bar_arrive(int id, int n) { __syncwarp(); asm volatile("bar.arrive %0, %1;" ::"r"(id), "r"(n) : "memory"); }
template <int OFF> __device__ __forceinline__ uint32_t atoms_add(uint32_t addr, uint32_t v) {
    uint32_t r; asm volatile("atom.shared.add.u32 %0, [%1+%3], %2;" : "=r"(r) : "r"(addr), "r"(v), "n"(OFF) : "memory"); return r;
}
__device__ __forceinline__ void sts64(uint32_t addr, uint32_t x, uint32_t y) {
    asm volatile("st.shared.v2.u32 [%0], {%1,%2};" ::"r"(addr), "r"(x), "r"(y) : "memory");
}
__device__ __forceinline__ void sts32(uint32_t addr, uint32_t x) { asm volatile("st.shared.u32 [%0], %1;" ::"r"(addr), "r"(x) : "memory"); }
template <int OFF = 0> __device__ __forceinline__ uint2 lds64(uint32_t addr) {
    uint2 v; asm volatile("ld.shared.v2.u32 {%0,%1}, [%2+%3];" : "=r"(v.x), "=r"(v.y) : "r"(addr), "n"(OFF) : "memory"); return v;
}
__device__ __forceinline__ uint32_t lds32(uint32_t addr) {
    uint32_t v; asm volatile("ld.shared.u32 %0, [%1];" : "=r"(v) : "r"(addr) : "memory"); return v;
}
__device__ __forceinline__ uint32_t ld_rlx32(const uint32_t* p) {
    uint32_t v; asm volatile("ld.relaxed.gpu.global.u32 %0, [%1];" : "=r"(v) : "l"(p) : "memory"); return v;
}
__device__ __forceinline__ uint2 ld_rlx64(const void* p) {
    uint2 v; asm volatile("ld.relaxed.gpu.global.v2.u32 {%0,%1}, [%2];" : "=r"(v.x), "=r"(v.y) : "l"(p) : "memory"); return v;
}
__device__ __forceinline__ float4 ld_rlx128f(const float4* p) {
    float4 v; asm volatile("ld.relaxed.gpu.global.v4.f32 {%0,%1,%2,%3}, [%4];" : "=f"(v.x), "=f"(v.y), "=f"(v.z), "=f"(v.w) : "l"(p) : "memory"); return v;
}
__device__ __forceinline__ void take3(float4* p, uint32_t mask, float4 (&v)[3]) {
    asm volatile("{ .reg .b128 a, b, c; .reg .b64 x, y; .reg .pred q0, q1, q2; .reg .b32 t;\n"
                 "mov.b64 x, 0; mov.b128 a, {x, x}; mov.b128 b, {x, x}; mov.b128 c, {x, x};\n"
                 "and.b32 t, %13, 1; setp.ne.u32 q0, t, 0; and.b32 t, %13, 2; setp.ne.u32 q1, t, 0; and.b32 t, %13, 4; setp.ne.u32 q2, t, 0;\n"
                 "@q0 atom.relaxed.gpu.global.exch.b128 a, [%12], a; @q1 atom.relaxed.gpu.global.exch.b128 b, [%12+16384], b;\n"
                 "@q2 atom.relaxed.gpu.global.exch.b128 c, [%12+32768], c;\n"
                 "mov.b128 {x, y}, a; mov.b64 {%0,%1}, x; mov.b64 {%2,%3}, y; mov.b128 {x, y}, b; mov.b64 {%4,%5}, x; mov.b64 {%6,%7}, y;\n"
                 "mov.b128 {x, y}, c; mov.b64 {%8,%9}, x; mov.b64 {%10,%11}, y; }"
                 : "=f"(v[0].x), "=f"(v[0].y), "=f"(v[0].z), "=f"(v[0].w), "=f"(v[1].x), "=f"(v[1].y), "=f"(v[1].z), "=f"(v[1].w),
                   "=f"(v[2].x), "=f"(v[2].y), "=f"(v[2].z), "=f"(v[2].w) : "l"(p), "r"(mask) : "memory");
}
__device__ __forceinline__ void st_rlx32(uint32_t* p, uint32_t v) { asm volatile("st.relaxed.gpu.global.u32 [%0], %1;" ::"l"(p), "r"(v) : "memory"); }
__device__ __forceinline__ uint32_t hmul_bf2(uint32_t a, uint32_t b) {
    uint32_t r; asm("mul.rn.bf16x2 %0, %1, %2;" : "=r"(r) : "r"(a), "r"(b)); return r;
}
__device__ __forceinline__ uint32_t hsub_bf2(uint32_t a, uint32_t b) {
    uint32_t r; asm("sub.rn.bf16x2 %0, %1, %2;" : "=r"(r) : "r"(a), "r"(b)); return r;
}
constexpr int SPIN_LIMIT = 1 << 22;

__constant__ uint32_t c_inv2pi[8] = {0u, 0x28be60dbu, 0x9391054au, 0x7f09d5f4u, 0x7d4d3770u, 0x36d8a566u, 0x4f10e410u, 0x7f9458eau};
constexpr uint32_t BIGX = 0x4280u;
__device__ __forceinline__ float cos_big(uint32_t xb) {
    uint32_t e = (xb >> 7) & 0xffu, M = (xb & 0x7fu) | 0x80u;
    uint32_t pp = e - 102u;
    uint32_t wi = pp >> 5;
    uint32_t t0 = c_inv2pi[wi], t1 = c_inv2pi[wi + 1], t2 = c_inv2pi[wi + 2];
    uint32_t f = M * __funnelshift_l(t1, t0, pp) + __umulhi(M, __funnelshift_l(t2, t1, pp));
    float c = __cosf((float)(int)f * 1.4629180792671596e-9f);
    return e == 255u ? __uint_as_float(0x7fc00000u) : c;
}
__device__ __forceinline__ float cos_bf(uint32_t xb) {
    return (xb & 0x7fffu) > BIGX ? cos_big(xb) : __cosf(__uint_as_float(xb << 16));
}
__device__ __forceinline__ uint32_t pack_bf2(float lo, float hi) {
    uint32_t r; asm("cvt.rn.bf16x2.f32 %0, %1, %2;" : "=r"(r) : "f"(hi), "f"(lo)); return r;
}
template <int N> __device__ __forceinline__ uint32_t pick(int k, const uint32_t (&a)[N]) {
    uint32_t v = a[0];
#pragma unroll
    for (int i = 1; i < N; i++) if (k == i) v = a[i];
    return v;
}
template <int N> __device__ __forceinline__ uint2 pick(int k, const uint2 (&a)[N]) {
    uint2 v = a[0];
#pragma unroll
    for (int i = 1; i < N; i++) if (k == i) v = a[i];
    return v;
}
__device__ __forceinline__ void side_add(uint32_t bin, uint32_t row, float a, float b, float c, float d) {
    red4(&g_ovf[bin * RPAD + row], a, b, c, d);
    g_dirty[bin * DROW + row] = 1;
}
__device__ __forceinline__ void slow_triplet(const Params& p, uint32_t ii, uint32_t oo, float c) {
    const uint2 v = __ldg(p.m + ii);
    const uint32_t bo = __umulhi(oo, p.mg2);
    side_add(bo, oo - bo * p.R2, c * bf_lo(v.x), c * bf_hi(v.x), c * bf_lo(v.y), c * bf_hi(v.y));
}
__device__ __forceinline__ void slow_rec1(const Params& p, uint32_t x, uint32_t y, uint32_t bin) {
    const uint2 v = __ldg(p.m + bin * p.R1 + (y & 0xffffu));
    const float c = bf_hi(y);
    side_add(x & 0xffu, __byte_perm(x, 0u, 0x4413) >> 3, c * bf_lo(v.x), c * bf_hi(v.x), c * bf_lo(v.y), c * bf_hi(v.y));
}
__device__ __forceinline__ uint32_t aux_of(uint32_t w0, uint32_t w1, uint32_t k = 0) {
    uint32_t u; asm("lop3.b32 %0, %1, %2, 0xf000f000, 0xe4;" : "=r"(u) : "r"(w0), "r"((w1 >> 4) + k));
    return __byte_perm(u, 0u, 0x4413);
}
__device__ __forceinline__ void slow_rec2(const Params& p, uint32_t w0, uint32_t w1, uint32_t bin, float unit) {
    side_add(bin, aux_of(w0, w1) >> 3, (float)((int)(w0 & 0xfffu) - 2048) * unit, (float)((int)(w0 >> 16 & 0xfffu) - 2048) * unit,
             (float)((int)(w1 & 0xfffu) - 2048) * unit, (float)((int)(w1 >> 16 & 0xfffu) - 2048) * unit);
}
template <uint32_t M> __device__ __forceinline__ uint32_t and_or(uint32_t a, uint32_t c) {
    uint32_t r; asm("lop3.b32 %0, %1, %2, %3, 0xea;" : "=r"(r) : "r"(a), "n"(M), "r"(c)); return r;
}
template <uint32_t M> __device__ __forceinline__ uint32_t xor_and(uint32_t a, uint32_t c) {
    uint32_t r; asm("lop3.b32 %0, %1, %2, %3, 0x48;" : "=r"(r) : "r"(a), "n"(M), "r"(c)); return r;
}
__device__ __forceinline__ uint32_t mux(uint32_t a, uint32_t b, uint32_t m) {
    uint32_t r; asm("lop3.b32 %0, %1, %2, %3, 0xd8;" : "=r"(r) : "r"(a), "r"(b), "r"(m)); return r;
}
__device__ __forceinline__ uint32_t and_xor(uint32_t a, uint32_t m, uint32_t c) {
    uint32_t r; asm("lop3.b32 %0, %1, %2, %3, 0x6a;" : "=r"(r) : "r"(a), "r"(m), "r"(c)); return r;
}
__device__ __forceinline__ uint2 ld_in(const uint2* a) {
    uint2 v; asm volatile("ld.global.nc.L1::no_allocate.v2.u32 {%0,%1}, [%2];" : "=r"(v.x), "=r"(v.y) : "l"(a)); return v;
}
__device__ __forceinline__ uint32_t ld_in(const uint32_t* a) {
    uint32_t v; asm volatile("ld.global.nc.L1::no_allocate.u32 %0, [%1];" : "=r"(v) : "l"(a)); return v;
}
__device__ __forceinline__ void ld_in4(const uint2* p, uint2& a, uint2& b) {
    asm volatile("ld.global.nc.L1::no_allocate.v4.u32 {%0,%1,%2,%3}, [%4];" : "=r"(a.x), "=r"(a.y), "=r"(b.x), "=r"(b.y) : "l"(p));
}
__device__ __forceinline__ void tex4(cudaTextureObject_t t, int i, uint2& a, uint2& b) {
    asm volatile("tex.1d.v4.u32.s32 {%0,%1,%2,%3}, [%4, {%5}];" : "=r"(a.x), "=r"(a.y), "=r"(b.x), "=r"(b.y) : "l"(t), "r"(i));
}
__device__ __forceinline__ void tex2(cudaTextureObject_t t, int i, uint32_t& a, uint32_t& b) {
    asm volatile("{ .reg .b32 z, w; tex.1d.v4.u32.s32 {%0,%1,z,w}, [%2, {%3}]; }" : "=r"(a), "=r"(b) : "l"(t), "r"(i) : "memory");
}
template <int OFF> __device__ __forceinline__ void put_rec(uint32_t ret, uint32_t lim, uint32_t addr, uint32_t x, uint32_t y) {
    asm volatile("{ .reg .pred q; setp.lt.u32 q, %0, %1; @q st.shared.v2.u32 [%2+%5], {%3,%4}; }" ::"r"(ret), "r"(lim), "r"(addr), "r"(x), "r"(y), "n"(OFF) : "memory");
}
__device__ __forceinline__ uint32_t mbar_try(uint32_t mb, uint32_t parity) {
    uint32_t ok;
    asm volatile("{ .reg .pred q; mbarrier.try_wait.parity.shared::cta.b64 q, [%1], %2; selp.u32 %0, 1, 0, q; }" : "=r"(ok) : "r"(mb), "r"(parity) : "memory");
    return ok;
}
__device__ __forceinline__ void mbar_wait(uint32_t mb, uint32_t parity) {
    if (!mbar_try(mb, parity)) {
        int it = 0;
        while (!mbar_try(mb, parity)) if (++it > SPIN_LIMIT) __trap();
    }
}
__device__ __forceinline__ void mbar_init(uint32_t mb, uint32_t n) { asm volatile("mbarrier.init.shared::cta.b64 [%0], %1;" ::"r"(mb), "r"(n) : "memory"); }
__device__ __forceinline__ void mbar_arrive(uint32_t mb) { asm volatile("mbarrier.arrive.shared::cta.b64 _, [%0];" ::"r"(mb) : "memory"); }
constexpr int B_FULL = OFF_BAR, B_OPEN = OFF_BAR + 16, B_FREE = OFF_BAR + 32;
constexpr int W_END = OFF_BAR + 40, W_SIDE = OFF_BAR + 44, W_PAR = OFF_BAR + 48, W_ROLE = OFF_BAR + 52, W_EXP = OFF_BAR + 56, W_UNIT = OFF_BAR + 60;
enum { BAR_S1 = 1, BAR_PROBE, BAR_HIST, BAR_ROLE, BAR_TABLE, BAR_H1, BAR_DONE };
constexpr int W_M1 = NS1 + NC, W_M2 = 31;

extern __shared__ __align__(1024) unsigned char smem[];
#define TK_DECL
#define TK(i)
#define TK_CNT(i)
#define TK_OUT
#define TK_ARG
#define TK_PASS
#define TKX(i)
#define TKY(i)

constexpr int NR = (R2MAX + NTHR - 1) / NTHR;
__device__ __forceinline__ void gates(const Params& p, int e0, int e1, int e2, uint4* gh) {
    constexpr int NH = 3;
    const int e[NH] = {e0, e1, e2};
    uint32_t dd[NH];
    float g[NH][4], h[NH][4];
#pragma unroll
    for (int u = 0; u < NH; u++) {
        dd[u] = reinterpret_cast<const uint16_t*>(p.dist)[min(e[u], p.E - 1)] * 0x10001u;
#pragma unroll
        for (int k = 0; k < 4; k++) { g[u][k] = 0.f; h[u][k] = 0.f; }
    }
#pragma unroll 1
    for (int r2 = 0; r2 < 4; r2++) {
        const uint32_t cen = reinterpret_cast<const uint32_t*>(smem + OFF_WG + 256)[r2];
        uint32_t rb[NH];
#pragma unroll
        for (int u = 0; u < NH; u++) {
            const uint32_t df = hsub_bf2(dd[u], cen);
            const uint32_t ar = hmul_bf2(hmul_bf2(df, df), 0xc120c120u);
            rb[u] = pack_bf2(__expf(bf_lo(ar)), __expf(bf_hi(ar)));
        }
#pragma unroll
        for (int i = 0; i < 2; i++) {
            const float4 ws = reinterpret_cast<const float4*>(smem + OFF_WG)[r2 * 2 + i], wr = reinterpret_cast<const float4*>(smem + OFF_WG + 128)[r2 * 2 + i];
#pragma unroll
            for (int u = 0; u < NH; u++) {
                const float x = i ? bf_hi(rb[u]) : bf_lo(rb[u]);
                g[u][0] += x * ws.x; g[u][1] += x * ws.y; g[u][2] += x * ws.z; g[u][3] += x * ws.w;
                h[u][0] += x * wr.x; h[u][1] += x * wr.y; h[u][2] += x * wr.z; h[u][3] += x * wr.w;
            }
        }
    }
#pragma unroll
    for (int u = 0; u < NH; u++)
        gh[u] = make_uint4(pack_bf2(g[u][0], g[u][1]), pack_bf2(g[u][2], g[u][3]), pack_bf2(h[u][0], h[u][1]), pack_bf2(h[u][2], h[u][3]));
}
__device__ __forceinline__ void prefetch_l2(const void* a) { asm volatile("prefetch.global.L2 [%0];" ::"l"(a)); }
__device__ __forceinline__ uint4* gate_slot(int k) { return reinterpret_cast<uint4*>(smem + OFF_H1 + (k >= WIN / 16 ? 0x20000 - WIN : 0)) + k; }
__device__ __forceinline__ void wait_flags(const Params& p, uint32_t sb, int lane, uint32_t need) {
    const unsigned char* f = p.ring + M_FLAG + (lds32(sb + W_SIDE) << 12);
    int it = 0;
    while (true) {
        const float4 a = ld_rlx128f(reinterpret_cast<const float4*>(f) + lane);
        const uint32_t b = ld_rlx32(reinterpret_cast<const uint32_t*>(f) + 128 + (lane & 3));
        const uint32_t d = (__float_as_uint(a.x) ^ need) | (__float_as_uint(a.y) ^ need) | (__float_as_uint(a.z) ^ need) | (__float_as_uint(a.w) ^ need) | (b ^ need);
        if (__all_sync(0xffffffffu, d == 0)) break;
        __nanosleep(50);
        if (++it > SPIN_LIMIT) __trap();
    }
    __threadfence();
}
__device__ __forceinline__ void epilogue(const Params& p, uint32_t sb) {
    int tid;
    asm volatile("mov.u32 %0, %%tid.x;" : "=r"(tid));
    const int role = lds32(sb + W_ROLE), row0 = role * p.R2, nrows = min(p.R2, p.E - row0), hw = tid >> 5;
    const bool s3 = hw > W_M1 && hw < W_M2;
    constexpr int T3 = (W_M1 + 1) * 32, N3 = NC * 32;
    uint4 gh[NR];
    if (hw < NS1) {
        if (tid * 64 < nrows) prefetch_l2(p.dist + row0 + tid * 64);
        for (int i = tid * 16; i < nrows; i += NS1 * 32 * 16) prefetch_l2(p.m + row0 + i);
    }
    if (!s3) gates(p, row0 + tid + 3 * NTHR, row0 + tid + 4 * NTHR, row0 + tid + 5 * NTHR, gh + 3);
    if (hw < NS1) {
        bar_sync(BAR_H1, (NS1 + 1) * 32);
#pragma unroll 1
        for (int k0 = tid; k0 < NR * N3; k0 += 3 * NS1 * 32) {
            int k[3], e[3];
#pragma unroll
            for (int u = 0; u < 3; u++) { k[u] = k0 + u * NS1 * 32; e[u] = row0 + T3 + k[u] + k[u] / N3 * (NTHR - N3); }
            gates(p, e[0], e[1], e[2], gh);
#pragma unroll
            for (int u = 0; u < 3; u++) if (k[u] < NR * N3) *gate_slot(k[u]) = gh[u];
        }
#pragma unroll
        for (int i = tid; i < DROW / 8; i += NS1 * 32) {
            const uint2 f = ld_rlx64(g_dirty + role * DROW + i * 8);
            if (f.x | f.y) prefetch_l2(g_ovf + role * RPAD + i * 8);
        }
    }
    if (!s3) gates(p, row0 + tid, row0 + tid + NTHR, row0 + tid + 2 * NTHR, gh);
    if (hw == W_M1) wait_flags(p, sb, tid & 31, lds32(sb + W_END));
    TKX(5)
    bar_sync(0, NTHR);
    TKX(6)
    uint32_t dirty = 0;
#pragma unroll
    for (int it = 0; it < NR; it++) {
        uint32_t f;
        asm volatile("ld.relaxed.gpu.global.u8 %0, [%1];" : "=r"(f) : "l"(g_dirty + role * DROW + tid + it * NTHR) : "memory");
        dirty |= f << it;
    }
    if (s3) {
#pragma unroll
        for (int it = 0; it < NR; it++) gh[it] = *gate_slot(tid - T3 + it * N3);
    }
    if (hw == W_M1 && blockIdx.x == 0) {
        if (tid == W_M1 * 32) g_base = lds32(sb + W_END);
        if (tid < W_M1 * 32 + 3) *reinterpret_cast<uint32_t*>(p.ring + (tid & 2 ? M_PAR : M_CNT + (tid & 1) * 4096)) = 0;
    }
    const float unit = *reinterpret_cast<const float*>(smem + W_UNIT);
    const float4* w4 = reinterpret_cast<const float4*>(smem + OFF_WSM);
#pragma unroll
    for (int i0 = 0; i0 < NR; i0 += 3) {
        uint2 mv[3];
        float4 o[3];
#pragma unroll
        for (int u = 0; u < 3; u++) mv[u] = __ldg(p.m + min(row0 + tid + (i0 + u) * NTHR, p.E - 1));
        take3(&g_ovf[role * RPAD + tid + i0 * NTHR], dirty >> i0, o);
#pragma unroll
        for (int u = 0; u < 3; u++) {
            const int it = i0 + u, i = tid + it * NTHR;
            if (dirty >> it & 1) g_dirty[role * DROW + i] = 0;
            if (i < nrows) {
                const uint2 ac = reinterpret_cast<const uint2*>(smem + OFF_ACC)[i];
                const uint32_t u0 = ac.x + 0x40004000u, u1 = ac.y + 0x40004000u;
                const float a[4] = {(float)((int)(u0 & 0xffffu) - 0x8000) * unit + o[u].x, (float)((int)(u0 >> 16) - 0x8000) * unit + o[u].y,
                                    (float)((int)(u1 & 0xffffu) - 0x8000) * unit + o[u].z, (float)((int)(u1 >> 16) - 0x8000) * unit + o[u].w};
                float sd[4] = {0, 0, 0, 0}, uu[4] = {0, 0, 0, 0};
#pragma unroll
                for (int j = 0; j < 4; j++) {
                    float4 w = w4[j];
                    sd[0] += a[j] * w.x; sd[1] += a[j] * w.y; sd[2] += a[j] * w.z; sd[3] += a[j] * w.w;
                }
                const uint32_t a01 = pack_bf2(sd[0] * bf_lo(gh[it].x), sd[1] * bf_hi(gh[it].x)), a23 = pack_bf2(sd[2] * bf_lo(gh[it].y), sd[3] * bf_hi(gh[it].y));
                const float ag[4] = {bf_lo(a01), bf_hi(a01), bf_lo(a23), bf_hi(a23)};
#pragma unroll
                for (int j = 0; j < 4; j++) {
                    float4 w = w4[4 + j];
                    uu[0] += ag[j] * w.x; uu[1] += ag[j] * w.y; uu[2] += ag[j] * w.z; uu[3] += ag[j] * w.w;
                }
                const uint32_t t01 = hmul_bf2(pack_bf2(uu[0], uu[1]), gh[it].z);
                const uint32_t t23 = hmul_bf2(pack_bf2(uu[2], uu[3]), gh[it].w);
                uint2 q;
                asm("add.rn.bf16x2 %0, %1, %2;" : "=r"(q.x) : "r"(mv[u].x), "r"(t01));
                asm("add.rn.bf16x2 %0, %1, %2;" : "=r"(q.y) : "r"(mv[u].y), "r"(t23));
                p.out[row0 + i] = q;
            }
        }
        if (i0 == 0) { TKY(3) }
    }
}

template <int HOP> __device__ __forceinline__ uint2 null_rec(int lane, uint32_t R) {
    if (HOP == 1) return make_uint2(0x800000u | H<1>::tag(R), (OFF_CNT1 - OFF_M) / 8);
    return make_uint2(0x08000800u | lane << 28, 0x08000800u | H<2>::tag(R));
}
template <int OFF> __device__ __forceinline__ void sts128(uint32_t a, const uint4& v) {
    asm volatile("st.shared.v4.u32 [%0+%5], {%1,%2,%3,%4};" ::"r"(a), "r"(v.x), "r"(v.y), "r"(v.z), "r"(v.w), "n"(OFF) : "memory");
}
template <int HOP> __device__ __forceinline__ void fill(uint32_t win, int lane, uint32_t R) {
    const uint2 v = null_rec<HOP>(lane, R);
#pragma unroll 11
    for (int i = 0; i < WIN / 512; i++) sts128<0>(win + lane * 16 + i * 512, make_uint4(v.x, v.y, v.x, v.y));
}
template <int HOP> __device__ __forceinline__ void reset(uint32_t win, int lane, uint32_t R) {
    const uint2 v = null_rec<HOP>(lane, R);
    const uint32_t a = win + lane * 32 + H<HOP>::mark(R, lane >> 2) * 8;
#pragma unroll
    for (int i = 0; i < 16; i++) sts64(a + i * 1024, v.x, v.y);
    if (lane < 16) sts64(a + 16384, v.x, v.y);
}
__device__ __forceinline__ bool elect() {
    uint32_t q; asm volatile("{ .reg .pred q; elect.sync _|q, 0xffffffff; selp.u32 %0, 1, 0, q; }" : "=r"(q)); return q;
}
__device__ __forceinline__ const unsigned char* mk_ptr(uint32_t lo, uint32_t hi) { return reinterpret_cast<const unsigned char*>((uint64_t)hi << 32 | lo); }
__device__ __forceinline__ void bulk_store(uint32_t lo, uint32_t hi, uint32_t src, uint32_t n) {
    asm volatile("cp.async.bulk.global.shared::cta.bulk_group [%0], [%1], %2;" ::"l"(mk_ptr(lo, hi)), "r"(src), "r"(n) : "memory");
}
#define CRED_NS 100
#define CRED_SKIP 1
#define LAG 0
template <int HOP>
__device__ __forceinline__ void manager(const Params& p, uint32_t sb, int lane, int role, uint32_t base) {
    typedef H<HOP> h;
    constexpr int V = h::NBIN / 32, PB = h::S * 8;
    const int RT = p.rounds, lo = HOP == 1 && role >= NG ? NG : 0, hi = lo + h::NBIN;
    const int w = (role - lo) / (HOP * J), j = (role - lo - w * HOP * J) / HOP;
    const Ring rg(p.ring, __reduce_or_sync(0xffffffffu, lds32(sb + W_PAR)), 2 * w + HOP - 1);
    const uint32_t side = lds32(sb + W_SIDE), dhi = rg.main >> 32, mhi = rg.mid >> 32;
    const uint32_t c0 = HOP == 2 ? role & 1 : 0, up = (HOP == 1 && lo) ^ rg.par ^ c0;
    uint32_t dA = ((uint32_t)rg.main + src_off(j) + (c0 << 16) + (up ? 4096 : 12288)) ^ slot_off(base % 3);
    uint32_t dM = ((uint32_t)rg.mid + src_off(j) + c0 * 1024) ^ slot_off(base % 3);
    const int a0 = max(64, lo), b1 = min(68, hi);
    int n0 = (min(NHI, hi) - a0) * PB, a1 = (max(NLO, lo) - lo) * PB;
    const unsigned char* cr = reinterpret_cast<const unsigned char*>(rg.main) + MISC + ((side ^ rg.par) << 12);
    const unsigned char* cr0 = cr + cred_off(lo + lane * V), *cr1 = cr + cred_off(lo + 32 * V + min(lane, V - 1));
    const uint32_t ca0 = sb + h::CNT + lane * V * 4, ca1 = sb + h::CNT + (32 * V + min(lane, V + NDUM)) * 4;
    const uint32_t rot0 = (lane * V & 7) * 16, rot1 = lane * 16;
    uint32_t st = slot_steps(base);
    uint32_t init = h::init(base), prim = sb + h::STG + (HOP == 1 ? h::win(base) : 0u);
    uint32_t cs[5];
    auto sample = [&]() {
        if (V == 2) asm volatile("ld.relaxed.gpu.global.v2.u32 {%0,%1}, [%2];" : "=r"(cs[0]), "=r"(cs[1]) : "l"(cr0) : "memory");
        else asm volatile("ld.relaxed.gpu.global.v4.u32 {%0,%1,%2,%3}, [%4];" : "=r"(cs[0]), "=r"(cs[1]), "=r"(cs[2]), "=r"(cs[3]) : "l"(cr0) : "memory");
        cs[V] = ld_rlx32(reinterpret_cast<const uint32_t*>(cr1));
    };
    sample();
    uint32_t c[5];
    TK_DECL
#pragma unroll 1
    for (int r = 0;; r++) {
        const uint32_t R = base + r, ninit = h::init(R + 1), done = prim;
        TK(5)
        mbar_wait(sb + B_FULL + (HOP - 1) * 8, r & 1);
        TK(0)
        if (V == 2) asm volatile("ld.shared.v2.u32 {%0,%1}, [%2];" : "=r"(c[0]), "=r"(c[1]) : "r"(ca0) : "memory");
        else asm volatile("ld.shared.v4.u32 {%0,%1,%2,%3}, [%4];" : "=r"(c[0]), "=r"(c[1]), "=r"(c[2]), "=r"(c[3]) : "r"(ca0) : "memory");
        c[V] = lds32(ca1);
        uint32_t nc[5];
#pragma unroll
        for (int k = 0; k <= V; k++) {
            const uint32_t z = ninit + (k < V ? rot0 + k * 16 : rot1);
            nc[k] = min(max(c[k] + (ninit - init - h::S * h::INC), z), z + (h::CAP - h::S) * h::INC);
        }
        if (V == 2) sts64(ca0, nc[0], nc[1]); else sts128<0>(ca0, make_uint4(nc[0], nc[1], nc[2], nc[3]));
        sts32(ca1, lane < V ? nc[V] : lane < V + NDUM ? DUMMY : r);
        __syncwarp();
        if (lane == 0) mbar_arrive(sb + B_OPEN + (HOP - 1) * 8);
        TK(1)
        TK(2)
        asm volatile("fence.proxy.async.shared::cta;" ::: "memory");
        TK(6)
        if (r >= D) {
            int it = 0;
            while (true) {
                uint32_t bad = 0;
#pragma unroll
                for (int k = 0; k <= V; k++) bad |= cs[k] - (R - D + 1);
                if (!__any_sync(0xffffffffu, bad >> 20)) break;
                if (++it > SPIN_LIMIT) __trap();
                if (it > CRED_SKIP) __nanosleep(CRED_NS);
                sample();
            }
        }
        TK(3)
        if (elect()) {
            const uint32_t dB = (HOP == 1 ? dA ^ 0x10000u : dA) + (up ? 8192 : -8192), sm = prim + (lo ? 2 * PB : 0);
            bulk_store(dA, dhi, sm, 8192);
            bulk_store(dB, dhi, HOP == 1 ? sm + 8192 : prim + 68 * PB, 8192);
            if (n0 > 0) bulk_store(dM + (a0 - 64) * PB, mhi, prim + (a0 - lo) * PB, n0);
            if (a1 < (b1 - lo) * PB) bulk_store((dM ^ 4096u) + (uint32_t)((lo - NLO) * PB + a1), mhi, prim + a1, (b1 - lo) * PB - a1);
            asm volatile("cp.async.bulk.commit_group;" ::: "memory");
            asm volatile("cp.async.bulk.wait_group.read 0;" ::: "memory");
        }
        __syncwarp();
        TK(4)
        prim = HOP == 1 ? prim ^ 0x20000u : prim >= sb + 0x30000u ? sb : prim + (prim - sb) + 0x10000u;
        if (r == RT - 1) break;
        reset<HOP>(done, lane, R + HOP + 1);
        if (HOP == 1) {
            __syncwarp();
            if (lane == 0) mbar_arrive(sb + B_FREE);
        }
        if (r == D - 1 || r == RT - D - 1) {
            uint32_t n = NHI, m = NLO;
            if (r < RT - D - 1) {
                int it = 0;
                while (true) {
                    n = ld_rlx32(reinterpret_cast<const uint32_t*>(p.ring + M_CNT + (side << 12)));
                    if ((n & 0xffffu) + (n >> 16) == NB) break;
                    if (++it > SPIN_LIMIT) __trap();
                }
                m = n = min(max(__reduce_or_sync(0xffffffffu, n) & 0xffffu, (uint32_t)NLO), (uint32_t)NHI);
            }
            n0 = (min((int)n, hi) - a0) * PB;
            a1 = (max((int)m, lo) - lo) * PB;
        }
        sample();
        slot_next(dA, st); slot_next(dM, st);
        st = slot_rot(st);
        init = ninit;
    }
#pragma unroll 1
    for (int k = 0; k <= V; k++) {
        const uint32_t bin = k < V ? lane * V + k : 32 * V + lane, n = bin < h::NBIN ? min((pick(k, c) - init) >> h::SH, (uint32_t)h::CAP) : 0u;
#pragma unroll 1
        for (uint32_t x = h::S; x < n; x++) {
            const uint2 w = lds64(prim + bin * PB + ((x + (bin & 7) * 2) & (h::S - 1)) * 8);
            if (HOP == 1) slow_rec1(p, w.x, w.y, bin);
            else slow_rec2(p, w.x, w.y, bin, __uint_as_float(lds32(sb + W_UNIT)));
        }
    }
    asm volatile("cp.async.bulk.wait_group 0;" ::: "memory");
    TK_OUT
}

#define POLL_NS 200
#define POLL_NS3 1500
template <int HOP> struct Reader {
    uint32_t lo, hi, st, line;
    uint32_t* cred;
    __device__ __forceinline__ void init(const Params& p, uint32_t sb, int w, int lane, int role, uint32_t base) {
        constexpr int PB = H<HOP>::S * 8;
        const int first = HOP == 1 ? (role >= NG ? NG : 0) + w * J : w * 2 * J;
        const Ring rg(p.ring, lds32(sb + W_PAR), 2 * w + HOP - 1);
        const uint32_t side = lds32(sb + W_SIDE);
        const bool mid = side ? role < 68 : role >= 64;
        const uint32_t i = role - (side ? (mid ? NLO : 68) : (mid ? 64 : 0));
        const uint32_t c = HOP == 1 ? i >> 5 : lane >> 3 & 1, in = (HOP == 1 ? (i & 31) * PB + (lane & 15) * 16 : i * PB + (lane & 7) * 16) + (lane >> 4) * src_off(3);
        lo = (in + (mid ? ((uint32_t)rg.mid ^ side << 12) + c * 1024 : (uint32_t)rg.main + (c << 16) + (side ^ rg.par ^ c ? 4096 : 12288))) ^ slot_off(base % 3);
        hi = __reduce_or_sync(0xffffffffu, (uint32_t)((mid ? rg.mid : rg.main) >> 32));
        st = slot_steps(base);
        line = (HOP == 1 ? 2 * (role % NG) + (lane >> 3 & 1) : role) + (lane & 1) * 2;
        const bool both = first >= NLO && first < NHI;
        cred = lane < 1 + both ? reinterpret_cast<uint32_t*>(rg.main + MISC + (((both ? lane : first >= NG) ^ rg.par) << 12) + cred_off(role)) : nullptr;
    }
    template <int K> __device__ __forceinline__ void load1(uint2 (&v)[J]) const {
        asm volatile("ld.relaxed.gpu.global.v4.u32 {%0,%1,%2,%3}, [%4+%5];" : "=r"(v[2 * K].x), "=r"(v[2 * K].y), "=r"(v[2 * K + 1].x), "=r"(v[2 * K + 1].y)
                     : "l"(mk_ptr(lo, hi)), "n"(src_off(K)) : "memory");
    }
    static __device__ __forceinline__ uint32_t word(const uint2& v) { return HOP == 1 ? v.x : v.y; }
    template <int K> __device__ __forceinline__ void again(uint2 (&v)[J], uint32_t want, uint32_t m0, uint32_t m1, uint32_t grp) const {
        if (__ballot_sync(0xffffffffu, ((word(v[2 * K]) ^ want) & m0) | ((word(v[2 * K + 1]) ^ want) & m1)) & grp) load1<K>(v);
    }
    __device__ __forceinline__ void load(uint2 (&rec)[J]) const { load1<0>(rec); load1<1>(rec); load1<2>(rec); }
    __device__ __forceinline__ void check(uint2 (&rec)[J], uint32_t R, uint32_t ns TK_ARG) {
        const uint32_t want = H<HOP>::tag(R), mk = H<HOP>::mark(R, line);
        const uint32_t m0 = mk == 0 ? H<HOP>::TAG : 0u, m1 = mk == 1 ? H<HOP>::TAG : 0u;
        int it = 0;
        while (true) {
            uint32_t b0 = 0, b1 = 0;
#pragma unroll
            for (int j = 0; j < J; j += 2) { b0 |= word(rec[j]) ^ want; b1 |= word(rec[j + 1]) ^ want; }
            if (!__any_sync(0xffffffffu, (b0 & m0) | (b1 & m1))) break;
            if (++it > SPIN_LIMIT) __trap();
            __nanosleep(ns);
            TK_CNT(7)
            const uint32_t grp = 0xffu << (threadIdx.x & 24u);
            again<0>(rec, want, m0, m1, grp); again<1>(rec, want, m0, m1, grp); again<2>(rec, want, m0, m1, grp);
        }
        if (cred) st_rlx32(cred, R + 1);
        __syncwarp();
        slot_next(lo, st);
        st = slot_rot(st);
    }
    __device__ __forceinline__ void finish() const { if (cred) st_rlx32(cred, 0u); }
};

#define NPROBE 9
__device__ __forceinline__ uint32_t near_half(unsigned char* pair, uint32_t zero) {
#pragma unroll
    for (int i = 0; i < 4; i++) *reinterpret_cast<uint4*>(pair + (i >> 1) * 4096 + (i & 1) * 16) = make_uint4(0u, 0u, 0u, 0u);
    uint32_t best[2] = {~0u, ~0u}, v = 0, prev = 0;
    asm volatile("red.relaxed.gpu.global.add.u32 [%0], 1;" ::"l"(pair + 4096) : "memory");
#pragma unroll
    for (int t = 0; t <= NPROBE; t++) {
        uint32_t now;
        asm volatile("atom.relaxed.gpu.global.add.u32 %0, [%1], 1;" : "=r"(v) : "l"(pair + (t & 1) * 4096 + (v & zero)) : "memory");
        asm volatile("mov.u32 %0, %%clock;" : "=r"(now) :: "memory");
        if (t > 1) best[(t - 1) & 1] = min(best[(t - 1) & 1], now - prev);
        prev = now;
    }
    return (best[1] < best[0] ? 1u : 0u) | (v & zero);
}
template <bool B> struct BoolC { static constexpr bool value = B; };

template <int NP>
__device__ __forceinline__ void stage1(const Params& p, uint32_t sb, const int pos0, int lane, uint32_t base) {
    typedef H<1> h;
    const int RT = p.rounds;
    uint32_t ff = *reinterpret_cast<const uint16_t*>(p.ang_freq) * 0x10001u;
    auto pair_of = [&](int r, int pos) {
        const int q = r < RT - 1 ? (r * NB + blockIdx.x) * NPR + pos : (RT - 1) * NB * NPR + blockIdx.x * p.lastn + pos;
        return (r < RT - 1 || (r == RT - 1 && pos < p.lastn)) && q < p.T2 ? q : -1;
    };
    uint2 vi[NP], vo[NP]; uint32_t va[NP];
    auto load_edge = [&](int r) {
#pragma unroll
        for (int u = 0; u < NP; u++) {
            const int q = max(pair_of(r, pos0 + u * 32), 0);
            vi[u] = ld_in(p.idx_in + q); vo[u] = ld_in(p.idx_out + q); va[u] = ld_in(p.angle + q);
        }
    };
    load_edge(0);
    if (blockIdx.x == 0 && pos0 == 0 && (p.T & 1)) {
        const int t = p.T - 1;
        slow_triplet(p, reinterpret_cast<const uint32_t*>(p.idx_in)[t], reinterpret_cast<const uint32_t*>(p.idx_out)[t],
                     bf16r(cos_bf(hmul_bf2(reinterpret_cast<const uint16_t*>(p.angle)[t], ff) & 0xffffu)));
    }
    for (int i = threadIdx.x * 16; i < p.R2 && blockIdx.x * p.R2 + i < p.E; i += NS1 * 32 * 16) prefetch_l2(p.m + blockIdx.x * p.R2 + i);
    uint32_t R = __reduce_or_sync(0xffffffffu, base);
    ff = __reduce_or_sync(0xffffffffu, ff);
    bar_sync(BAR_S1, (NS1 + 1) * 32);
    TK_DECL
    auto step = [&](const int r, const int qn, auto edge) {
        constexpr bool EDGE = decltype(edge)::value;
        uint32_t cc[NP], big = 0;
#pragma unroll
        for (int u = 0; u < NP; u++) {
            va[u] = hmul_bf2(va[u], ff);
            cc[u] = pack_bf2(__cosf(bf_lo(va[u])), __cosf(bf_hi(va[u])));
            big = __vmaxu2(big, va[u] & 0x7fff7fffu);
        }
        if ((big + (0x7fffu - BIGX) * 0x10001u) & 0x80008000u) {
#pragma unroll 1
            for (int u = 0; u < NP; u++) {
                const uint32_t a = pick(u, va);
                float c0 = cos_bf(a & 0xffffu), c1 = cos_bf(a >> 16);
                if ((c0 != c0 || c1 != c1) && (!EDGE || pair_of(r, pos0 + u * 32) >= 0)) {
                    const uint2 i2 = pick(u, vi), o2 = pick(u, vo);
                    if (c0 != c0) slow_triplet(p, i2.x, o2.x, c0);
                    if (c1 != c1) slow_triplet(p, i2.y, o2.y, c1);
                }
                const uint32_t v = pack_bf2(c0 != c0 ? 0.f : c0, c1 != c1 ? 0.f : c1);
#pragma unroll
                for (int k = 0; k < NP; k++) if (k == u) cc[k] = v;
            }
        }
        uint32_t bin[2 * NP], x[2 * NP], y[2 * NP];
        uint32_t dep = 0;
        auto loads = [&]() {
            const int q = qn + (dep & p.zero);
#pragma unroll
            for (int u = 0; u + 1 < NP; u += 2) {
                if (TEXIN) { tex2(p.ta, q + u * 16, va[u], va[u + 1]); tex4(p.to, q + u * 16, vo[u], vo[u + 1]); tex4(p.ti, q + u * 16, vi[u], vi[u + 1]); }
                else {
                    const uint2 v = ld_in(reinterpret_cast<const uint2*>(p.angle) + q + u * 16); va[u] = v.x; va[u + 1] = v.y;
                    ld_in4(p.idx_out + 2 * (q + u * 16), vo[u], vo[u + 1]); ld_in4(p.idx_in + 2 * (q + u * 16), vi[u], vi[u + 1]);
                }
            }
            if (NP & 1) {
                const int k = 2 * q - lane + (NP - 1) * 32;
                va[NP - 1] = ld_in(p.angle + k); vo[NP - 1] = ld_in(p.idx_out + k); vi[NP - 1] = ld_in(p.idx_in + k);
            }
        };
#pragma unroll
        for (int j = 0; j < 2 * NP; j++) {
            const uint32_t ii = j & 1 ? vi[j >> 1].y : vi[j >> 1].x, oo = j & 1 ? vo[j >> 1].y : vo[j >> 1].x;
            bin[j] = __umulhi(ii, p.mg1);
            y[j] = __byte_perm(bin[j] * p.k1 + ii, cc[j >> 1], j & 1 ? 0x7610 : 0x5410);
            const uint32_t bo = __umulhi(oo, p.mg2);
            x[j] = __byte_perm(bo * p.k2 + oo * 8u, bo, 0x0514);
            dep |= x[j] | y[j];
            if (EDGE && pair_of(r, pos0 + (j >> 1) * 32) < 0) bin[j] = NG + (lane & (NDUM - 1));
        }
        if (EDGE) load_edge(r + 1);
        else loads();
        const uint32_t init = h::init(R), kb = sb + h::win(R + 1), lim = init + (h::CAP << h::SH);
        TK(0)
        mbar_wait(sb + B_OPEN, ~R & 1);
        TK(1)
        bool freed = false;
        uint32_t over = 0;
#pragma unroll
        for (int g = 0; g < 2 * NP; g += G1) {
            constexpr int G = G1;
            uint32_t ret[G];
            int mx = 0;
#pragma unroll
            for (int j = 0; j < G; j++) if (g + j < 2 * NP) ret[j] = atoms_add<h::CNT>(sb + bin[g + j] * 4, h::INC);
#pragma unroll
            for (int j = 0; j < G; j++) if (g + j < 2 * NP) mx = j ? max(mx, (int)ret[j]) : (int)ret[j];
            if (!DEFER && !freed && __any_sync(0xffffffffu, mx >= (int)(init + 0x10000u))) { TK(2) mbar_wait(sb + B_FREE, ~R & 1); freed = true; TK(3) }
            TK(2)
#pragma unroll
            for (int j = 0; j < G; j++) if (g + j < 2 * NP) {
                x[g + j] = and_or<h::TAG>(ret[j], x[g + j]);
                if (DEFER) {
                    bin[g + j] = and_xor(EDGE ? ret[j] | (ret[j] >> 14 & 0x20000u) : ret[j], 0x20000u | h::PM, bin[g + j] * 256 + kb);
                    put_rec<h::STG>(ret[j], init + 0x10000u, bin[g + j], x[g + j], y[g + j]);
                } else put_rec<h::STG>(ret[j], lim, and_xor(ret[j], 0x20000u | h::PM, bin[g + j] * 256 + kb), x[g + j], y[g + j]);
            }
            if (mx >= (int)lim) {
#pragma unroll
                for (int j = 0; j < G; j++) if (g + j < 2 * NP && (int)ret[j] >= (int)lim) { over |= 1u << (g + j); if (DEFER) bin[g + j] = mux(bin[g + j], ~kb, 0x20000u); }
            }
        }
        if (!DEFER || !EDGE) { __syncwarp(); if (elect()) mbar_arrive(sb + B_FULL); }
        if (DEFER) {
            TK(4)
            mbar_wait(sb + B_FREE, ~R & 1);
            TK(3)
#pragma unroll
            for (int j = 0; j < 2 * NP; j++) put_rec<h::STG>(xor_and<0x20000u>(bin[j], kb), 1u, bin[j], x[j], y[j]);
            if (EDGE) { __syncwarp(); if (elect()) mbar_arrive(sb + B_FULL); }
        }
        R++;
        TK(4)
#pragma unroll 1
        while (over) {
            TK_CNT(7)
            const int j = __ffs(over) - 1;
            over &= over - 1;
            slow_rec1(p, pick(j, x), pick(j, y), DEFER ? (pick(j, bin) - sb) >> 8 & 0xffu : pick(j, bin));
        }
        __syncwarp();
    };
#pragma unroll 1
    for (int q = (NB + blockIdx.x) * NPR; q < p.qfull; q += NB * NPR) step(q / (NB * NPR) - 1, (q + pos0 + lane) >> 1, BoolC<false>());
#pragma unroll 1
    for (int r = max(p.qfull / (NB * NPR) - 1, 0); r < RT; r++) step(r, 0, BoolC<true>());
    TK_OUT
}

__device__ __forceinline__ void stage2(const Params& p, uint32_t sb, int w, int lane, int role, uint32_t base) {
    typedef H<2> h;
    const int RT = p.rounds;
    Reader<1> rd;
    rd.init(p, sb, w, lane, role, base);
    uint2 rec[J];
    rd.load(rec);
    bar_sync(BAR_TABLE, 2 * NC * 32);
    uint32_t kb = sb + 0x10000u, am = 0x10000u | h::PM;
    const float unit = __uint_as_float(__reduce_or_sync(0xffffffffu, lds32(sb + W_UNIT)));
    TK_DECL
#pragma unroll 1
    for (int r = 0; r < RT; r++) {
        rd.check(rec, base + r, POLL_NS TK_PASS);
        const uint32_t want = H<1>::tag(base + r);
        TK(0)
        uint2 mv[J];
#pragma unroll
        for (int j = 0; j < J; j++) mv[j] = lds64<OFF_M>(sb + (rec[j].y & 0xffffu) * 8);
        uint32_t fl = 0;
#pragma unroll
        for (int j = 0; j < J; j++) fl |= mv[j].y;
        if (fl & 0x40000000u) {
#pragma unroll 1
            for (int j = 0; j < J; j++) {
                const uint2 v = pick(j, mv), w = pick(j, rec);
                if ((v.y & 0x40000000u) && !((w.x ^ want) & 0xf00000u)) {
                    if (v.x & 0x40000000u) slow_rec1(p, w.x, w.y, lds32(sb + W_ROLE) % NG);
                    else {
                        const float c = bf_hi(w.y), s = __uint_as_float(lds32(sb + W_UNIT)) * 1024.f;
                        side_add(w.x & 0xffu, __byte_perm(w.x, 0u, 0x4413) >> 3, c * (bf_lo(v.x) * s), c * (bf_hi(v.x) * s),
                                 c * (bf_lo(v.y) * s), c * (bf_hi(v.y & 0xbfffffffu) * s));
                    }
                }
            }
#pragma unroll
            for (int j = 0; j < J; j++) if (mv[j].y & 0x40000000u) rec[j].x = 0x800000u;
        }
        uint32_t w0[J], w1[J], bin[J], ret[J];
#pragma unroll
        for (int j = 0; j < J; j++) {
            const float c = bf_hi(rec[j].y), MG = 8194.0f;
            const uint32_t x = rec[j].x;
            w0[j] = and_or<0xf000f000u>(x, __byte_perm(__float_as_uint(fmaf(c, bf_lo(mv[j].x), MG)), __float_as_uint(fmaf(c, bf_hi(mv[j].x), MG)), 0x5410));
            w1[j] = and_or<0xf000f000u>(x << 4, __byte_perm(__float_as_uint(fmaf(c, bf_lo(mv[j].y), MG)), __float_as_uint(fmaf(c, bf_hi(mv[j].y), MG)), 0x5410));
            bin[j] = min(xor_and<0xf000ffu>(x, want), NB + (lane & (NDUM - 1)));
        }
        const uint32_t lim = h::init(base + r) + 0x20000u;
        rd.load(rec);
        TK(1)
        mbar_wait(sb + B_OPEN + 8, (r - 1) & 1);
        TK(2)
#pragma unroll
        for (int j = 0; j < J; j++) ret[j] = atoms_add<h::CNT>(sb + bin[j] * 4, h::INC);
        uint32_t mx = 0;
#pragma unroll
        for (int j = 0; j < J; j++) {
            w1[j] = and_or<h::TAG>(ret[j], w1[j]);
            put_rec<0>(ret[j], lim, and_xor(ret[j], am, bin[j] * 128 + kb), w0[j], w1[j]);
            mx = __viaddmax_u32(ret[j], 0u - DUMMY, mx);
        }
        __syncwarp();
        if (lane == 0) mbar_arrive(sb + B_FULL + 8);
        TK(3)
        if (mx >= lim - DUMMY) {
            uint32_t over = 0;
#pragma unroll
            for (int j = 0; j < J; j++) if (ret[j] - DUMMY >= lim - DUMMY) over |= 1u << j;
#pragma unroll 1
            do {
                const int j = __ffs(over) - 1;
                over &= over - 1;
                slow_rec2(p, pick(j, w0), pick(j, w1), pick(j, bin), unit);
            } while (over);
        }
        __syncwarp();
        am = am >= 0x30000u ? 0x10000u | h::PM : am + 0x10000u;
        kb ^= am & 0x30000u;
        TK(4)
    }
    rd.finish();
    TK_OUT
}

__device__ __forceinline__ float2 acc_fix(uint32_t old, uint32_t q) {
    const uint32_t u = old + 0x40004000u, n = u + q - 0x08000800u;
    return make_float2((float)((int)(u & 0xffffu) + (int)(q & 0xffffu) - 2048 - (int)(n & 0xffffu)), (float)((int)(u >> 16) + (int)(q >> 16) - 2048 - (int)(n >> 16)));
}
__device__ __forceinline__ void stage3(const Params& p, uint32_t sb, int w, int lane, int role, uint32_t base) {
    const int RT = p.rounds;
    Reader<2> rd;
    rd.init(p, sb, w, lane, role, base);
    uint2 rec[J];
    bar_sync(BAR_TABLE, 2 * NC * 32);
    TK_DECL
#pragma unroll 1
    for (int r = 0; r < RT; r++) {
        if (LAG) { const int need = min(r + 1, RT - 1); if ((int)lds32(sb + W_RND) < need) mbar_wait(sb + B_OPEN + 8, need & 1); }
        rd.load(rec);
        rd.check(rec, base + r, r < RT - 2 ? POLL_NS3 : 100 TK_PASS);
        TK(0)
        const uint32_t want = H<2>::tag(base + r), t = 0u - (lane & 1u), k = (t & 1u << 26) - (want >> 4);
        uint32_t o0[J], o1[J], g = 0;
#pragma unroll
        for (int j = 0; j < J; j++) {
            o0[j] = 0; o1[j] = 0;
            if (!xor_and<H<2>::TAG>(rec[j].y, want)) {
                const uint32_t a = aux_of(rec[j].x, rec[j].y, k) + (j >= G3 ? (o0[j - G3] | o1[j - G3]) & p.zero : 0u);
                const uint32_t v0 = (rec[j].x & 0x0fff0fffu) - 0x08000800u, v1 = (rec[j].y & 0x0fff0fffu) - 0x08000800u;
                o0[j] = atoms_add<OFF_ACC>(sb + a, mux(v0, v1, t));
                o1[j] = atoms_add<OFF_ACC>(sb + (a ^ 4u), mux(v1, v0, t));
            }
        }
#pragma unroll
        for (int j = 0; j < J; j++) g |= o0[j] | o1[j];
        if (__any_sync(0xffffffffu, g & 0x80008000u)) {
#pragma unroll 1
            for (int j = 0; j < J; j++) {
                const uint2 w = pick(j, rec);
                const uint32_t aux = aux_of(w.x, w.y), p0 = pick(j, o0), p1 = pick(j, o1);
                const float2 a = acc_fix(t ? p1 : p0, w.x & 0x0fff0fffu), b = acc_fix(t ? p0 : p1, w.y & 0x0fff0fffu);
                const float unit = __uint_as_float(lds32(sb + W_UNIT));
                if (!((w.y ^ want) & H<2>::TAG) && (a.x != 0.f || a.y != 0.f || b.x != 0.f || b.y != 0.f))
                    side_add(lds32(sb + W_ROLE), aux >> 3, a.x * unit, a.y * unit, b.x * unit, b.y * unit);
                __syncwarp();
            }
        }
        TK(1)
    }
    rd.finish();
    TK_OUT
}

__device__ __forceinline__ uint32_t row_max(uint32_t x, uint32_t y) {
    const uint32_t mx = __vmaxu2(x & 0x7fff7fffu, y & 0x7fff7fffu);
    return max(mx & 0xffffu, mx >> 16);
}
constexpr int EWIN = 5;

__global__ void __launch_bounds__(NTHR, 1) fused_kernel(const Params p) {
    const int tid = threadIdx.x, lane = tid & 31;
    const int hw = __reduce_max_sync(0xffffffffu, tid >> 5);
    const uint32_t sb = __reduce_or_sync(0xffffffffu, (uint32_t)__cvta_generic_to_shared(smem));
    TKX(0)
    const uint32_t epoch = ld_rlx32(&g_base);
    uint32_t base = epoch & 31u;

    if (hw < NS1) {
        if (hw < NS1 - 1 || NPR == 1024) stage1<4>(p, sb, hw * 128 + lane, lane, base);
        else stage1<NPR / 32 - (NS1 - 1) * 4>(p, sb, hw * 128 + lane, lane, base);
        __threadfence();
        bar_arrive(BAR_DONE, (NS1 + NC + 2) * 32);
    } else if (hw == W_M1) {
        if (lane == 0) {
            if (sb & 255u) __trap();
            mbar_init(sb + B_FULL, NS1); mbar_init(sb + B_OPEN, 1); mbar_init(sb + B_FREE, 1);
        }
        base = __reduce_or_sync(0xffffffffu, base);
        if (lane == 0 && (base & 1u)) { mbar_arrive(sb + B_OPEN); mbar_arrive(sb + B_FREE); }
        for (int i = lane; i < NG + NDUM; i += 32) sts32(sb + OFF_CNT1 + i * 4, i < NG ? H<1>::init(base) + (i & 7) * 16 : DUMMY);
#pragma unroll 1
        for (int i = 0; i < 2; i++) fill<1>(sb + OFF_H1 + H<1>::win(base + i), lane, base + i);
        bar_arrive(BAR_S1, (NS1 + 1) * 32);
        bar_sync(BAR_PROBE, (2 * NC + 1) * 32);
        {
            const uint32_t raw = __ballot_sync(0xffffffffu, lane < 2 * NC && smem[OFF_PROBE + lane]), side = raw & 1u;
            uint32_t v = 0;
            if (lane < 2) asm volatile("atom.relaxed.gpu.global.add.u32 %0, [%1], %2;" : "=r"(v) : "l"(p.ring + M_CNT + lane * 4096), "r"(side ? 0x10000u : 1u) : "memory");
            const uint32_t mine = (side ? ~raw : raw) | 0x80000000u;
            if (lane == 2) asm volatile("atom.relaxed.gpu.global.cas.b32 %0, [%1], 0, %2;" : "=r"(v) : "l"(p.ring + M_PAR), "r"(mine) : "memory");
            bar_sync(BAR_HIST, (2 * NC + 1) * 32);
            uint32_t best = 0;
#pragma unroll 1
            for (int e = 11 + lane; e <= 230; e += 32) {
                uint32_t c = 0;
#pragma unroll
                for (int i = 0; i < EWIN; i++) c += lds32(sb + OFF_HIST + (e - i) * 4);
                best = max(best, c << 8 | (255 - e));
            }
            const uint32_t e = 255 - (__reduce_max_sync(0xffffffffu, best) & 255u);
            if (lane == 0) {
                const uint32_t role = side ? NB - 1 - (v >> 16) : v & 0xffffu;
                sts32(sb + W_ROLE, role); sts32(sb + W_SIDE, role < NLO ? 0u : role >= NHI ? 1u : side);
                sts32(sb + W_EXP, e); sts32(sb + W_UNIT, (e - 10) << 23); sts32(sb + W_END, (epoch | 31u) + 1u + (base + p.rounds) % 24u);
            }
            if (lane == 2) sts32(sb + W_PAR, v ? v : mine);
        }
        bar_sync(BAR_ROLE, (2 * NC + 2) * 32);
        manager<1>(p, sb, lane, __reduce_max_sync(0xffffffffu, lds32(sb + W_ROLE)), base);
        bar_arrive(BAR_H1, (NS1 + 1) * 32);
        __threadfence();
        bar_arrive(BAR_DONE, (NS1 + NC + 2) * 32);
    } else if (hw == W_M2) {
        const float wd = __bfloat162float(lane & 16 ? p.w_up[lane & 15] : p.w_down[lane & 15]);
        const float ws = __bfloat162float(p.w_sbf[lane]), wr = __bfloat162float(p.w_rbf[lane]);
        const __nv_bfloat16 cen = p.centers[lane & 7];
        if (lane == 0) { mbar_init(sb + B_FULL + 8, NC); mbar_init(sb + B_OPEN + 8, 1); }
        base = __reduce_or_sync(0xffffffffu, base);
        for (int i = lane; i <= NB + NDUM; i += 32) sts32(sb + OFF_CNT2 + i * 4, i < NB ? H<2>::init(base) + (i & 7) * 16 : DUMMY);
#pragma unroll 1
        for (int i = 0; i < 3; i++) fill<2>(sb + H<2>::win(i), lane, base + i);
        reinterpret_cast<float*>(smem + OFF_WSM)[lane] = wd;
        reinterpret_cast<float*>(smem + OFF_WG)[lane] = ws;
        reinterpret_cast<float*>(smem + OFF_WG + 128)[lane] = wr;
        reinterpret_cast<__nv_bfloat16*>(smem + OFF_WG + 256)[lane & 7] = cen;
        bar_sync(BAR_ROLE, (2 * NC + 2) * 32);
        manager<2>(p, sb, lane, __reduce_max_sync(0xffffffffu, lds32(sb + W_ROLE)), base);
        __threadfence();
        bar_sync(BAR_DONE, (NS1 + NC + 2) * 32);
        if (lane < 2) { __threadfence(); st_rlx32(reinterpret_cast<uint32_t*>(p.ring + M_FLAG + lane * 4096) + blockIdx.x, lds32(sb + W_END)); }
    } else {
        const int pw = __reduce_max_sync(0xffffffffu, hw < W_M1 ? hw - NS1 : hw - NS1 - 1), ct = pw * 32 + lane;
        constexpr int CT = 2 * NC * 32;
        const uint4 sm = __ldg(reinterpret_cast<const uint4*>(p.m) + min((ct >> 3) * (p.E >> 1) / (CT / 8) + (lane & 7), (p.E >> 1) - 1));
        if (ct < 256) sts32(sb + OFF_HIST + ct * 4, 0u);
        if (lane == 0) smem[OFF_PROBE + pw] = pw < NPAGE ? near_half(p.ring + (size_t)pw * PAGE + PROBE + (blockIdx.x & 31) * 128 + (blockIdx.x >> 5 & 3) * 16384 + (blockIdx.x >> 7 << 20), p.zero) : 0;
        TKX(1)
        bar_sync(BAR_PROBE, (2 * NC + 1) * 32);
        {
            const uint32_t m0 = row_max(sm.x, sm.y), m1 = row_max(sm.z, sm.w);
            if (m0) atoms_add<OFF_HIST>(sb + (m0 >> 7) * 4, 1u);
            if (m1) atoms_add<OFF_HIST>(sb + (m1 >> 7) * 4, 1u);
        }
        bar_arrive(BAR_HIST, (2 * NC + 1) * 32);
        base = __reduce_or_sync(0xffffffffu, base);
        for (int i = ct; i < R2MAX / 2; i += CT) reinterpret_cast<uint4*>(smem + OFF_ACC)[i] = make_uint4(0x40004000u, 0x40004000u, 0x40004000u, 0x40004000u);
        bar_sync(BAR_ROLE, (2 * NC + 2) * 32);
        const int role = __reduce_max_sync(0xffffffffu, lds32(sb + W_ROLE));
        TKX(2)
        {
            const int e = lds32(sb + W_EXP), q0 = (role >= NG ? role - NG : role) * (p.R1 >> 1), nq = min(p.R1 >> 1, (p.E >> 1) - q0);
            const uint32_t sc = (uint32_t)(254 - e) * 0x800080u;
            constexpr int CH = (R1MAX / 2 + CT - 1) / CT;
            uint4 v[CH];
#pragma unroll
            for (int u = 0; u < CH; u++) v[u] = __ldg(reinterpret_cast<const uint4*>(p.m) + min(q0 + ct + u * CT, (p.E >> 1) - 1));
            auto conv = [&](uint32_t& x, uint32_t& y) {
                const uint32_t mx = row_max(x, y);
                const int d = e - (int)(mx >> 7);
                x = hmul_bf2(x, sc); y = hmul_bf2(y, sc);
                if (d >= EWIN) y |= 0x40000000u;
                if (d < 0 || (d >= EWIN && e > 127)) { x = 0x40000000u; y = x; }
                if (mx == 0) { x = 0; y = 0; }
            };
#pragma unroll
            for (int u = 0; u < CH; u++) {
                conv(v[u].x, v[u].y); conv(v[u].z, v[u].w);
                if (ct + u * CT < nq) sts128<OFF_M>(sb + (ct + u * CT) * 16, v[u]);
            }
        }
        TKX(3)
        if (hw < W_M1) {
            stage2(p, sb, pw, lane, role, base);
            __threadfence();
            bar_arrive(BAR_DONE, (NS1 + NC + 2) * 32);
        } else {
            stage3(p, sb, pw - NC, lane, role, base);
            __threadfence();
        }
    }
    TKX(4)
    epilogue(p, sb);
}

__global__ void fb_scatter(const uint2* __restrict__ m, const int* __restrict__ idx_in, const int* __restrict__ idx_out,
                           const uint16_t* __restrict__ angle, const __nv_bfloat16* __restrict__ ang_freq, int T, int e0, int e1) {
    const uint32_t fb = *reinterpret_cast<const uint16_t*>(ang_freq);
    for (long long t = blockIdx.x * (long long)blockDim.x + threadIdx.x; t < T; t += (long long)gridDim.x * blockDim.x) {
        int o = idx_out[t];
        if (o < e0 || o >= e1) continue;
        float c = bf16r(cos_bf(hmul_bf2(angle[t], fb) & 0xffffu));
        uint2 v = __ldg(m + idx_in[t]);
        red4(&g_ovf[o - e0], c * bf_lo(v.x), c * bf_hi(v.x), c * bf_lo(v.y), c * bf_hi(v.y));
    }
}
__global__ void fb_final(const Params p, int e0, int e1) {
    int e = e0 + blockIdx.x * blockDim.x + threadIdx.x;
    if (e >= e1) return;
    float4 a4 = g_ovf[e - e0];
    g_ovf[e - e0] = make_float4(0.f, 0.f, 0.f, 0.f);
    float a[4] = {a4.x, a4.y, a4.z, a4.w};
    float d = __bfloat162float(p.dist[e]);
    float g[4] = {0, 0, 0, 0}, h[4] = {0, 0, 0, 0};
    for (int r = 0; r < 8; r++) {
        float df = bf16r(d - __bfloat162float(p.centers[r]));
        float rb = bf16r(expf(bf16r(-10.0f * bf16r(df * df))));
        for (int k = 0; k < 4; k++) {
            g[k] += rb * __bfloat162float(p.w_sbf[r * 4 + k]);
            h[k] += rb * __bfloat162float(p.w_rbf[r * 4 + k]);
        }
    }
    float ag[4];
    for (int k = 0; k < 4; k++) {
        float s = 0.f;
        for (int j = 0; j < 4; j++) s += a[j] * __bfloat162float(p.w_down[j * 4 + k]);
        ag[k] = bf16r(s * g[k]);
    }
    uint2 mv = p.m[e];
    float mm[4] = {bf_lo(mv.x), bf_hi(mv.x), bf_lo(mv.y), bf_hi(mv.y)};
    __nv_bfloat16 o[4];
    for (int k = 0; k < 4; k++) {
        float u = 0.f;
        for (int j = 0; j < 4; j++) u += ag[j] * __bfloat162float(p.w_up[j * 4 + k]);
        o[k] = __float2bfloat16_rn(mm[k] + bf16r(bf16r(u) * bf16r(h[k])));
    }
    p.out[e] = *reinterpret_cast<uint2*>(o);
}

}

static bool exact_div(int E, int lo, int hi, int* R, uint32_t* magic) {
    for (int r = lo + (lo & 1); r <= hi; r += 2) {
        unsigned long long mg = ((1ull << 32) + r - 1) / r, err = mg * r - (1ull << 32);
        if (err * (unsigned long long)E < (1ull << 32)) { *R = r; *magic = (uint32_t)mg; return true; }
    }
    return false;
}

static cudaTextureObject_t make_tex(const void* ptr, size_t bytes, int words) {
    cudaResourceDesc rd = {}; cudaTextureDesc td = {};
    rd.resType = cudaResourceTypeLinear; rd.res.linear.devPtr = const_cast<void*>(ptr); rd.res.linear.sizeInBytes = bytes;
    rd.res.linear.desc = cudaCreateChannelDesc(32, words > 1 ? 32 : 0, words > 2 ? 32 : 0, words > 2 ? 32 : 0, cudaChannelFormatKindUnsigned);
    td.readMode = cudaReadModeElementType;
    cudaTextureObject_t t = 0;
    if (cudaCreateTextureObject(&t, &rd, &td, nullptr) != cudaSuccess) { t = 0; (void)cudaGetLastError(); }
    return t;
}

extern "C" void kernel_launch(void* const* d_in, const int* in_sizes, int n_in, void* d_out, int out_size) {
    typedef const __nv_bfloat16* B;
    Params p;
    p.m = (const uint2*)d_in[0]; p.idx_in = (const uint2*)d_in[1]; p.idx_out = (const uint2*)d_in[2]; p.dist = (B)d_in[3];
    p.angle = (const uint32_t*)d_in[4]; p.centers = (B)d_in[5]; p.ang_freq = (B)d_in[6]; p.w_rbf = (B)d_in[7]; p.w_sbf = (B)d_in[8];
    p.w_down = (B)d_in[9]; p.w_up = (B)d_in[10]; p.out = (uint2*)d_out;
    p.E = in_sizes[3]; p.T = in_sizes[1]; p.T2 = p.T >> 1; p.zero = 0;
    p.R1 = p.R2 = p.rounds = p.lastn = p.qfull = 0; p.mg1 = p.mg2 = p.k1 = p.k2 = 0;
    static int ok = -1;
    static unsigned char* ring = nullptr;
    if (ok < 0) {
        void* ra = nullptr;
        cudaGetSymbolAddress(&ra, g_ring);
        ring = reinterpret_cast<unsigned char*>(((uintptr_t)ra + PAGE - 1) & ~(uintptr_t)(PAGE - 1));
        int dev = 0, sms = 0, occ = 0;
        cudaGetDevice(&dev);
        cudaDeviceGetAttribute(&sms, cudaDevAttrMultiProcessorCount, dev);
        cudaError_t e = cudaFuncSetAttribute(fused_kernel, cudaFuncAttributeMaxDynamicSharedMemorySize, SMEM_BYTES);
        if (e == cudaSuccess) e = cudaOccupancyMaxActiveBlocksPerMultiprocessor(&occ, fused_kernel, NTHR, SMEM_BYTES);
        ok = (e == cudaSuccess && occ >= 1 && sms >= NB) ? 1 : 0;
        (void)cudaGetLastError();
    }
    p.ring = ring;
    static cudaTextureObject_t tx[3];
    if (!tx[0]) { tx[0] = make_tex(p.idx_in, (size_t)(p.T >> 2) * 16, 4); tx[1] = make_tex(p.idx_out, (size_t)(p.T >> 2) * 16, 4); tx[2] = make_tex(p.angle, (size_t)(p.T >> 2) * 8, 2); }
    p.ti = tx[0]; p.to = tx[1]; p.ta = tx[2];
    const bool fused = ok == 1 && p.E <= EMAX && p.E >= 2 * NB && p.E % 2 == 0 && p.T >= 2 && exact_div(p.E, (p.E + NG - 1) / NG, R1MAX, &p.R1, &p.mg1) &&
                       exact_div(p.E, (p.E + NB - 1) / NB, R2MAX, &p.R2, &p.mg2);
    if (fused) {
        p.k1 = 0u - (uint32_t)p.R1; p.k2 = 0u - 8u * (uint32_t)p.R2;
        const int per = NB * NPR;
        int full = p.T2 / per, rest = p.T2 - full * per;
        p.qfull = full * per;
        p.lastn = (rest + NB - 1) / NB;
        if (p.lastn > NPR / 2) { full++; p.lastn = 0; }
        if (full < D) { full = D; p.lastn = 0; }
        p.rounds = full + 1;
        fused_kernel<<<NB, NTHR, SMEM_BYTES>>>(p);
    } else {
        for (int e0 = 0; e0 < p.E; e0 += EMAX) {
            int e1 = p.E - e0 < EMAX ? p.E : e0 + EMAX;
            fb_scatter<<<1056, 256>>>(p.m, (const int*)d_in[1], (const int*)d_in[2], (const uint16_t*)d_in[4], p.ang_freq, p.T, e0, e1);
            fb_final<<<(e1 - e0 + 255) / 256, 256>>>(p, e0, e1);
        }
    }
}
```

```cpp
#include <cuda_runtime.h>
#include <cuda_bf16.h>
#include <stdint.h>

namespace {

constexpr int NB = 132, NG = 66;
constexpr int R2MAX = 6062, R1MAX = 12124;
constexpr int EMAX = NB * R2MAX;
constexpr int NTHR = 1024;
constexpr int NS1 = 8, NC = 11, J = 6;
#define TILES 30
#define TEXIN 1
#define DEFER 0
#define G1 4
#define PRE3 6
#define CAP1 64
constexpr int NPR = TILES * 32;
constexpr int D = 3;
constexpr int WIN = 16896;
constexpr int NDUM = 16;
constexpr uint32_t DUMMY = 0xc0000000u;

constexpr int OFF_ACC = WIN, OFF_BAR = OFF_ACC + R2MAX * 8;
constexpr int OFF_H1 = 0x10000 + WIN, OFF_M = OFF_H1 + WIN, OFF_WSM = OFF_M + R1MAX * 8;
constexpr int OFF_CNT1 = OFF_H1 + 0x20000 + WIN, OFF_CNT2 = OFF_CNT1 + (NG + NDUM + 2) * 4, W_RND = OFF_CNT2 + (NB + NDUM) * 4, OFF_WG = W_RND + 16;
constexpr int OFF_HIST = OFF_M;
constexpr int OFF_PROBE = OFF_WSM + 128;
constexpr int SMEM_BYTES = OFF_WG + 272;
static_assert(SMEM_BYTES <= 232448 && OFF_BAR + 64 <= 0x10000 && OFF_PROBE + 32 <= 0x30000, "smem");
static_assert(OFF_BAR % 8 == 0 && OFF_WG % 16 == 0 && OFF_WSM % 16 == 0 && OFF_CNT2 % 16 == 0, "align");
static_assert(NC * J == NG && NC * 32 * 6 * 16 == 2 * WIN, "shape");

template <int HOP> struct H {
    static constexpr int S = HOP == 1 ? 32 : 16, NBIN = HOP == 1 ? NG : NB, CAP = HOP == 1 ? CAP1 : 32, SH = HOP == 1 ? 11 : 12;
    static constexpr int TB = HOP == 1 ? 20 : 28, CNT = HOP == 1 ? OFF_CNT1 : OFF_CNT2, STG = HOP == 1 ? OFF_H1 : 0;
    static constexpr uint32_t INC = (1u << SH) + 8u, PM = (S - 1) * 8, TAG = 7u << TB;
    static __device__ __forceinline__ uint32_t tag(uint32_t R) { return R << TB & TAG; }
    static __device__ __forceinline__ uint32_t init(uint32_t R) { return tag(R) | ((1u << TB) - 0x10000u); }
    static __device__ __forceinline__ uint32_t mark(uint32_t R, uint32_t line) { return ((HOP == 1 ? R >> 1 : R) + line) & 3u; }
    static __device__ __forceinline__ uint32_t win(int r) { return HOP == 1 ? (r & 1) << 17 : (0x310u >> (r % 3 * 4) & 3u) << 16; }
};

constexpr uint32_t PAGE = 1u << 21;
constexpr int NPAGE = NC + 2;
__device__ __align__(256) unsigned char g_ring[(size_t)(NPAGE + 1) * PAGE];
constexpr int MISC = 0xa0000;
constexpr int M_CNT = MISC + 1024, M_PAR = MISC + 1088;
constexpr int M_FLAG = MISC + 2048;
constexpr int PROBE = MISC + 0x40000;
#define CSTR 16384
__device__ __forceinline__ uint32_t cred_off(uint32_t role) { return role * 4 + min(role >> 5, 3u) * (CSTR - 128); }
struct Ring {
    uint64_t main, mid;
    uint32_t par;
    __device__ __forceinline__ Ring(const unsigned char* ring, uint32_t pars, int k) {
        main = reinterpret_cast<uint64_t>(ring) + ((uint64_t)k << 20);
        par = pars >> (k >> 1) & 1u;
        mid = reinterpret_cast<uint64_t>(ring) + (uint64_t)NC * PAGE + (((k >> 3 << 20) + (k >> 2 & 1) * 0x11000u + (k & 1) * 2048) ^ (k >> 1 & 1) * 0x3000u ^ (pars >> (NC + (k >> 4)) & 1u) << 12);
    }
};
constexpr int NLO = 60, NHI = 72;
__host__ __device__ constexpr uint32_t src_off(int j) { return (j % 3) << 14 | (j / 3) << 18; }
__device__ __forceinline__ uint32_t slot_off(uint32_t s) { return (0xa930u >> s * 4 & 15u) << 16; }
__device__ __forceinline__ uint32_t slot_steps(uint32_t R) { return (uint32_t)(0x30a09030aull >> (2 - R % 3) * 8) & 0xffffffu; }
__device__ __forceinline__ void slot_next(uint32_t& a, uint32_t st) { a ^= st & 0xf0000u; }
__device__ __forceinline__ uint32_t slot_rot(uint32_t st) { return __byte_perm(st, 0u, 0x4102); }
constexpr int RPAD = 6064, DROW = 6144;
__device__ __align__(128) uint8_t g_dirty[NB * DROW];
__device__ uint32_t g_base = 1;
__device__ __align__(128) float4 g_ovf[NB * RPAD];

struct Params {
    const uint2* m; const uint2* idx_in; const uint2* idx_out; const __nv_bfloat16* dist; const uint32_t* angle;
    const __nv_bfloat16* centers; const __nv_bfloat16* ang_freq; const __nv_bfloat16* w_rbf; const __nv_bfloat16* w_sbf;
    const __nv_bfloat16* w_down; const __nv_bfloat16* w_up; uint2* out; unsigned char* ring;
    cudaTextureObject_t ti, to, ta;
    int E, T, T2, R1, R2, rounds, lastn, qfull; uint32_t mg1, mg2, k1, k2, zero;
};

__device__ __forceinline__ float bf16r(float x) { return __bfloat162float(__float2bfloat16_rn(x)); }
__device__ __forceinline__ float bf_lo(uint32_t v) { return __uint_as_float(v << 16); }
__device__ __forceinline__ float bf_hi(uint32_t v) { return __uint_as_float(v & 0xffff0000u); }
__device__ __forceinline__ void red4(float4* a, float x, float y, float z, float w) {
    asm volatile("red.global.add.v4.f32 [%0], {%1,%2,%3,%4};" ::"l"(a), "f"(x), "f"(y), "f"(z), "f"(w) : "memory");
}
__device__ __forceinline__ void bar_sync(int id, int n) { __syncwarp(); asm volatile("bar.sync %0, %1;" ::"r"(id), "r"(n) : "memory"); }
__device__ __forceinline__ void bar_arrive(int id, int n) { __syncwarp(); asm volatile("bar.arrive %0, %1;" ::"r"(id), "r"(n) : "memory"); }
template <int OFF> __device__ __forceinline__ uint32_t atoms_add(uint32_t addr, uint32_t v) {
    uint32_t r; asm volatile("atom.shared.add.u32 %0, [%1+%3], %2;" : "=r"(r) : "r"(addr), "r"(v), "n"(OFF) : "memory"); return r;
}
__device__ __forceinline__ void sts64(uint32_t addr, uint32_t x, uint32_t y) {
    asm volatile("st.shared.v2.u32 [%0], {%1,%2};" ::"r"(addr), "r"(x), "r"(y) : "memory");
}
__device__ __forceinline__ void sts32(uint32_t addr, uint32_t x) { asm volatile("st.shared.u32 [%0], %1;" ::"r"(addr), "r"(x) : "memory"); }
template <int OFF = 0> __device__ __forceinline__ uint2 lds64(uint32_t addr) {
    uint2 v; asm volatile("ld.shared.v2.u32 {%0,%1}, [%2+%3];" : "=r"(v.x), "=r"(v.y) : "r"(addr), "n"(OFF) : "memory"); return v;
}
__device__ __forceinline__ uint32_t lds32(uint32_t addr) {
    uint32_t v; asm volatile("ld.shared.u32 %0, [%1];" : "=r"(v) : "r"(addr) : "memory"); return v;
}
__device__ __forceinline__ uint32_t ld_rlx32(const uint32_t* p) {
    uint32_t v; asm volatile("ld.relaxed.gpu.global.u32 %0, [%1];" : "=r"(v) : "l"(p) : "memory"); return v;
}
__device__ __forceinline__ uint2 ld_rlx64(const void* p) {
    uint2 v; asm volatile("ld.relaxed.gpu.global.v2.u32 {%0,%1}, [%2];" : "=r"(v.x), "=r"(v.y) : "l"(p) : "memory"); return v;
}
__device__ __forceinline__ float4 ld_rlx128f(const float4* p) {
    float4 v; asm volatile("ld.relaxed.gpu.global.v4.f32 {%0,%1,%2,%3}, [%4];" : "=f"(v.x), "=f"(v.y), "=f"(v.z), "=f"(v.w) : "l"(p) : "memory"); return v;
}
__device__ __forceinline__ void take3(float4* p, uint32_t mask, float4 (&v)[3]) {
    asm volatile("{ .reg .b128 a, b, c; .reg .b64 x, y; .reg .pred q0, q1, q2; .reg .b32 t;\n"
                 "mov.b64 x, 0; mov.b128 a, {x, x}; mov.b128 b, {x, x}; mov.b128 c, {x, x};\n"
                 "and.b32 t, %13, 1; setp.ne.u32 q0, t, 0; and.b32 t, %13, 2; setp.ne.u32 q1, t, 0; and.b32 t, %13, 4; setp.ne.u32 q2, t, 0;\n"
                 "@q0 atom.relaxed.gpu.global.exch.b128 a, [%12], a; @q1 atom.relaxed.gpu.global.exch.b128 b, [%12+16384], b;\n"
                 "@q2 atom.relaxed.gpu.global.exch.b128 c, [%12+32768], c;\n"
                 "mov.b128 {x, y}, a; mov.b64 {%0,%1}, x; mov.b64 {%2,%3}, y; mov.b128 {x, y}, b; mov.b64 {%4,%5}, x; mov.b64 {%6,%7}, y;\n"
                 "mov.b128 {x, y}, c; mov.b64 {%8,%9}, x; mov.b64 {%10,%11}, y; }"
                 : "=f"(v[0].x), "=f"(v[0].y), "=f"(v[0].z), "=f"(v[0].w), "=f"(v[1].x), "=f"(v[1].y), "=f"(v[1].z), "=f"(v[1].w),
                   "=f"(v[2].x), "=f"(v[2].y), "=f"(v[2].z), "=f"(v[2].w) : "l"(p), "r"(mask) : "memory");
}
__device__ __forceinline__ void st_rlx32(uint32_t* p, uint32_t v) { asm volatile("st.relaxed.gpu.global.u32 [%0], %1;" ::"l"(p), "r"(v) : "memory"); }
__device__ __forceinline__ uint32_t hmul_bf2(uint32_t a, uint32_t b) {
    uint32_t r; asm("mul.rn.bf16x2 %0, %1, %2;" : "=r"(r) : "r"(a), "r"(b)); return r;
}
__device__ __forceinline__ uint32_t hsub_bf2(uint32_t a, uint32_t b) {
    uint32_t r; asm("sub.rn.bf16x2 %0, %1, %2;" : "=r"(r) : "r"(a), "r"(b)); return r;
}
constexpr int SPIN_LIMIT = 1 << 22;

__constant__ uint32_t c_inv2pi[8] = {0u, 0x28be60dbu, 0x9391054au, 0x7f09d5f4u, 0x7d4d3770u, 0x36d8a566u, 0x4f10e410u, 0x7f9458eau};
constexpr uint32_t BIGX = 0x4280u;
__device__ __forceinline__ float cos_big(uint32_t xb) {
    uint32_t e = (xb >> 7) & 0xffu, M = (xb & 0x7fu) | 0x80u;
    uint32_t pp = e - 102u;
    uint32_t wi = pp >> 5;
    uint32_t t0 = c_inv2pi[wi], t1 = c_inv2pi[wi + 1], t2 = c_inv2pi[wi + 2];
    uint32_t f = M * __funnelshift_l(t1, t0, pp) + __umulhi(M, __funnelshift_l(t2, t1, pp));
    float c = __cosf((float)(int)f * 1.4629180792671596e-9f);
    return e == 255u ? __uint_as_float(0x7fc00000u) : c;
}
__device__ __forceinline__ float cos_bf(uint32_t xb) {
    return (xb & 0x7fffu) > BIGX ? cos_big(xb) : __cosf(__uint_as_float(xb << 16));
}
__device__ __forceinline__ uint32_t pack_bf2(float lo, float hi) {
    uint32_t r; asm("cvt.rn.bf16x2.f32 %0, %1, %2;" : "=r"(r) : "f"(hi), "f"(lo)); return r;
}
template <int N> __device__ __forceinline__ uint32_t pick(int k, const uint32_t (&a)[N]) {
    uint32_t v = a[0];
#pragma unroll
    for (int i = 1; i < N; i++) if (k == i) v = a[i];
    return v;
}
template <int N> __device__ __forceinline__ uint2 pick(int k, const uint2 (&a)[N]) {
    uint2 v = a[0];
#pragma unroll
    for (int i = 1; i < N; i++) if (k == i) v = a[i];
    return v;
}
__device__ __forceinline__ void side_add(uint32_t bin, uint32_t row, float a, float b, float c, float d) {
    red4(&g_ovf[bin * RPAD + row], a, b, c, d);
    g_dirty[bin * DROW + row] = 1;
}
__device__ __forceinline__ void slow_triplet(const Params& p, uint32_t ii, uint32_t oo, float c) {
    const uint2 v = __ldg(p.m + ii);
    const uint32_t bo = __umulhi(oo, p.mg2);
    side_add(bo, oo - bo * p.R2, c * bf_lo(v.x), c * bf_hi(v.x), c * bf_lo(v.y), c * bf_hi(v.y));
}
__device__ __forceinline__ void slow_rec1(const Params& p, uint32_t x, uint32_t y, uint32_t bin) {
    const uint2 v = __ldg(p.m + bin * p.R1 + (y & 0xffffu));
    const float c = bf_hi(y);
    side_add(x & 0xffu, __byte_perm(x, 0u, 0x4413) >> 3, c * bf_lo(v.x), c * bf_hi(v.x), c * bf_lo(v.y), c * bf_hi(v.y));
}
__device__ __forceinline__ uint32_t aux_of(uint32_t w0, uint32_t w1, uint32_t k = 0) {
    uint32_t u; asm("lop3.b32 %0, %1, %2, 0xf000f000, 0xe4;" : "=r"(u) : "r"(w0), "r"((w1 >> 4) + k));
    return __byte_perm(u, 0u, 0x4413);
}
__device__ __forceinline__ void slow_rec2(const Params& p, uint32_t w0, uint32_t w1, uint32_t bin, float unit) {
    side_add(bin, aux_of(w0, w1) >> 3, (float)((int)(w0 & 0xfffu) - 2048) * unit, (float)((int)(w0 >> 16 & 0xfffu) - 2048) * unit,
             (float)((int)(w1 & 0xfffu) - 2048) * unit, (float)((int)(w1 >> 16 & 0xfffu) - 2048) * unit);
}
template <uint32_t M> __device__ __forceinline__ uint32_t and_or(uint32_t a, uint32_t c) {
    uint32_t r; asm("lop3.b32 %0, %1, %2, %3, 0xea;" : "=r"(r) : "r"(a), "n"(M), "r"(c)); return r;
}
template <uint32_t M> __device__ __forceinline__ uint32_t xor_and(uint32_t a, uint32_t c) {
    uint32_t r; asm("lop3.b32 %0, %1, %2, %3, 0x48;" : "=r"(r) : "r"(a), "n"(M), "r"(c)); return r;
}
__device__ __forceinline__ uint32_t mux(uint32_t a, uint32_t b, uint32_t m) {
    uint32_t r; asm("lop3.b32 %0, %1, %2, %3, 0xd8;" : "=r"(r) : "r"(a), "r"(b), "r"(m)); return r;
}
__device__ __forceinline__ uint32_t and_xor(uint32_t a, uint32_t m, uint32_t c) {
    uint32_t r; asm("lop3.b32 %0, %1, %2, %3, 0x6a;" : "=r"(r) : "r"(a), "r"(m), "r"(c)); return r;
}
__device__ __forceinline__ uint2 ld_in(const uint2* a) {
    uint2 v; asm volatile("ld.global.nc.L1::no_allocate.v2.u32 {%0,%1}, [%2];" : "=r"(v.x), "=r"(v.y) : "l"(a)); return v;
}
__device__ __forceinline__ uint32_t ld_in(const uint32_t* a) {
    uint32_t v; asm volatile("ld.global.nc.L1::no_allocate.u32 %0, [%1];" : "=r"(v) : "l"(a)); return v;
}
__device__ __forceinline__ void ld_in4(const uint2* p, uint2& a, uint2& b) {
    asm volatile("ld.global.nc.L1::no_allocate.v4.u32 {%0,%1,%2,%3}, [%4];" : "=r"(a.x), "=r"(a.y), "=r"(b.x), "=r"(b.y) : "l"(p));
}
__device__ __forceinline__ void tex4(cudaTextureObject_t t, int i, uint2& a, uint2& b) {
    asm volatile("tex.1d.v4.u32.s32 {%0,%1,%2,%3}, [%4, {%5}];" : "=r"(a.x), "=r"(a.y), "=r"(b.x), "=r"(b.y) : "l"(t), "r"(i));
}
__device__ __forceinline__ void tex2(cudaTextureObject_t t, int i, uint32_t& a, uint32_t& b) {
    asm volatile("{ .reg .b32 z, w; tex.1d.v4.u32.s32 {%0,%1,z,w}, [%2, {%3}]; }" : "=r"(a), "=r"(b) : "l"(t), "r"(i) : "memory");
}
template <int OFF> __device__ __forceinline__ void put_rec(uint32_t ret, uint32_t lim, uint32_t addr, uint32_t x, uint32_t y) {
    asm volatile("{ .reg .pred q; setp.lt.u32 q, %0, %1; @q st.shared.v2.u32 [%2+%5], {%3,%4}; }" ::"r"(ret), "r"(lim), "r"(addr), "r"(x), "r"(y), "n"(OFF) : "memory");
}
__device__ __forceinline__ uint32_t mbar_try(uint32_t mb, uint32_t parity) {
    uint32_t ok;
    asm volatile("{ .reg .pred q; mbarrier.try_wait.parity.shared::cta.b64 q, [%1], %2; selp.u32 %0, 1, 0, q; }" : "=r"(ok) : "r"(mb), "r"(parity) : "memory");
    return ok;
}
__device__ __forceinline__ void mbar_wait(uint32_t mb, uint32_t parity) {
    if (!mbar_try(mb, parity)) {
        int it = 0;
        while (!mbar_try(mb, parity)) if (++it > SPIN_LIMIT) __trap();
    }
}
__device__ __forceinline__ void mbar_init(uint32_t mb, uint32_t n) { asm volatile("mbarrier.init.shared::cta.b64 [%0], %1;" ::"r"(mb), "r"(n) : "memory"); }
__device__ __forceinline__ void mbar_arrive(uint32_t mb) { asm volatile("mbarrier.arrive.shared::cta.b64 _, [%0];" ::"r"(mb) : "memory"); }
constexpr int B_FULL = OFF_BAR, B_OPEN = OFF_BAR + 16, B_FREE = OFF_BAR + 32;
constexpr int W_END = OFF_BAR + 40, W_SIDE = OFF_BAR + 44, W_PAR = OFF_BAR + 48, W_ROLE = OFF_BAR + 52, W_EXP = OFF_BAR + 56, W_UNIT = OFF_BAR + 60;
enum { BAR_S1 = 1, BAR_PROBE, BAR_HIST, BAR_ROLE, BAR_TABLE, BAR_H1, BAR_DONE };
constexpr int W_M1 = NS1 + NC, W_M2 = 31;

extern __shared__ __align__(1024) unsigned char smem[];
#define TK_DECL
#define TK(i)
#define TK_CNT(i)
#define TK_OUT
#define TK_ARG
#define TK_PASS
#define TKX(i)
#define TKY(i)

constexpr int NR = (R2MAX + NTHR - 1) / NTHR;
__device__ __forceinline__ void gates(const Params& p, int e0, int e1, int e2, uint4* gh) {
    constexpr int NH = 3;
    const int e[NH] = {e0, e1, e2};
    uint32_t dd[NH];
    float g[NH][4], h[NH][4];
#pragma unroll
    for (int u = 0; u < NH; u++) {
        dd[u] = reinterpret_cast<const uint16_t*>(p.dist)[min(e[u], p.E - 1)] * 0x10001u;
#pragma unroll
        for (int k = 0; k < 4; k++) { g[u][k] = 0.f; h[u][k] = 0.f; }
    }
#pragma unroll 1
    for (int r2 = 0; r2 < 4; r2++) {
        const uint32_t cen = reinterpret_cast<const uint32_t*>(smem + OFF_WG + 256)[r2];
        uint32_t rb[NH];
#pragma unroll
        for (int u = 0; u < NH; u++) {
            const uint32_t df = hsub_bf2(dd[u], cen);
            const uint32_t ar = hmul_bf2(hmul_bf2(df, df), 0xc120c120u);
            rb[u] = pack_bf2(__expf(bf_lo(ar)), __expf(bf_hi(ar)));
        }
#pragma unroll
        for (int i = 0; i < 2; i++) {
            const float4 ws = reinterpret_cast<const float4*>(smem + OFF_WG)[r2 * 2 + i], wr = reinterpret_cast<const float4*>(smem + OFF_WG + 128)[r2 * 2 + i];
#pragma unroll
            for (int u = 0; u < NH; u++) {
                const float x = i ? bf_hi(rb[u]) : bf_lo(rb[u]);
                g[u][0] += x * ws.x; g[u][1] += x * ws.y; g[u][2] += x * ws.z; g[u][3] += x * ws.w;
                h[u][0] += x * wr.x; h[u][1] += x * wr.y; h[u][2] += x * wr.z; h[u][3] += x * wr.w;
            }
        }
    }
#pragma unroll
    for (int u = 0; u < NH; u++)
        gh[u] = make_uint4(pack_bf2(g[u][0], g[u][1]), pack_bf2(g[u][2], g[u][3]), pack_bf2(h[u][0], h[u][1]), pack_bf2(h[u][2], h[u][3]));
}
__device__ __forceinline__ void prefetch_l2(const void* a) { asm volatile("prefetch.global.L2 [%0];" ::"l"(a)); }
__device__ __forceinline__ uint4* gate_slot(int k) { return reinterpret_cast<uint4*>(smem + OFF_H1 + (k >= WIN / 16 ? 0x20000 - WIN : 0)) + k; }
__device__ __forceinline__ void wait_flags(const Params& p, uint32_t sb, int lane, uint32_t need) {
    const unsigned char* f = p.ring + M_FLAG + (lds32(sb + W_SIDE) << 12);
    int it = 0;
    while (true) {
        const float4 a = ld_rlx128f(reinterpret_cast<const float4*>(f) + lane);
        const uint32_t b = ld_rlx32(reinterpret_cast<const uint32_t*>(f) + 128 + (lane & 3));
        const uint32_t d = (__float_as_uint(a.x) ^ need) | (__float_as_uint(a.y) ^ need) | (__float_as_uint(a.z) ^ need) | (__float_as_uint(a.w) ^ need) | (b ^ need);
        if (__all_sync(0xffffffffu, d == 0)) break;
        __nanosleep(50);
        if (++it > SPIN_LIMIT) __trap();
    }
    __threadfence();
}
__device__ __forceinline__ void epilogue(const Params& p, uint32_t sb) {
    int tid;
    asm volatile("mov.u32 %0, %%tid.x;" : "=r"(tid));
    const int role = lds32(sb + W_ROLE), row0 = role * p.R2, nrows = min(p.R2, p.E - row0), hw = tid >> 5;
    const bool s3 = hw > W_M1 && hw < W_M2;
    constexpr int T3 = (W_M1 + 1) * 32, N3 = NC * 32;
    uint4 gh[NR];
    if (hw < NS1) {
        if (tid * 64 < nrows) prefetch_l2(p.dist + row0 + tid * 64);
        for (int i = tid * 16; i < nrows; i += NS1 * 32 * 16) prefetch_l2(p.m + row0 + i);
    }
    if (!s3) gates(p, row0 + tid + 3 * NTHR, row0 + tid + 4 * NTHR, row0 + tid + 5 * NTHR, gh + 3);
    if (hw < NS1) {
        bar_sync(BAR_H1, (NS1 + 1) * 32);
#pragma unroll 1
        for (int k0 = tid; k0 < NR * N3; k0 += 3 * NS1 * 32) {
            int k[3], e[3];
#pragma unroll
            for (int u = 0; u < 3; u++) { k[u] = k0 + u * NS1 * 32; e[u] = row0 + T3 + k[u] + k[u] / N3 * (NTHR - N3); }
            gates(p, e[0], e[1], e[2], gh);
#pragma unroll
            for (int u = 0; u < 3; u++) if (k[u] < NR * N3) *gate_slot(k[u]) = gh[u];
        }
#pragma unroll
        for (int i = tid; i < DROW / 8; i += NS1 * 32) {
            const uint2 f = ld_rlx64(g_dirty + role * DROW + i * 8);
            if (f.x | f.y) prefetch_l2(g_ovf + role * RPAD + i * 8);
        }
    }
    if (!s3) gates(p, row0 + tid, row0 + tid + NTHR, row0 + tid + 2 * NTHR, gh);
    if (hw == W_M1) wait_flags(p, sb, tid & 31, lds32(sb + W_END));
    TKX(5)
    bar_sync(0, NTHR);
    TKX(6)
    uint32_t dirty = 0;
#pragma unroll
    for (int it = 0; it < NR; it++) {
        uint32_t f;
        asm volatile("ld.relaxed.gpu.global.u8 %0, [%1];" : "=r"(f) : "l"(g_dirty + role * DROW + tid + it * NTHR) : "memory");
        dirty |= f << it;
    }
    if (s3) {
#pragma unroll
        for (int it = 0; it < NR; it++) gh[it] = *gate_slot(tid - T3 + it * N3);
    }
    if (hw == W_M1 && blockIdx.x == 0) {
        if (tid == W_M1 * 32) g_base = lds32(sb + W_END);
        if (tid < W_M1 * 32 + 3) *reinterpret_cast<uint32_t*>(p.ring + (tid & 2 ? M_PAR : M_CNT + (tid & 1) * 4096)) = 0;
    }
    const float unit = *reinterpret_cast<const float*>(smem + W_UNIT);
    const float4* w4 = reinterpret_cast<const float4*>(smem + OFF_WSM);
#pragma unroll
    for (int i0 = 0; i0 < NR; i0 += 3) {
        uint2 mv[3];
        float4 o[3];
#pragma unroll
        for (int u = 0; u < 3; u++) mv[u] = __ldg(p.m + min(row0 + tid + (i0 + u) * NTHR, p.E - 1));
        take3(&g_ovf[role * RPAD + tid + i0 * NTHR], dirty >> i0, o);
#pragma unroll
        for (int u = 0; u < 3; u++) {
            const int it = i0 + u, i = tid + it * NTHR;
            if (dirty >> it & 1) g_dirty[role * DROW + i] = 0;
            if (i < nrows) {
                const uint2 ac = reinterpret_cast<const uint2*>(smem + OFF_ACC)[i];
                const uint32_t u0 = ac.x + 0x40004000u, u1 = ac.y + 0x40004000u;
                const float a[4] = {(float)((int)(u0 & 0xffffu) - 0x8000) * unit + o[u].x, (float)((int)(u0 >> 16) - 0x8000) * unit + o[u].y,
                                    (float)((int)(u1 & 0xffffu) - 0x8000) * unit + o[u].z, (float)((int)(u1 >> 16) - 0x8000) * unit + o[u].w};
                float sd[4] = {0, 0, 0, 0}, uu[4] = {0, 0, 0, 0};
#pragma unroll
                for (int j = 0; j < 4; j++) {
                    float4 w = w4[j];
                    sd[0] += a[j] * w.x; sd[1] += a[j] * w.y; sd[2] += a[j] * w.z; sd[3] += a[j] * w.w;
                }
                const uint32_t a01 = pack_bf2(sd[0] * bf_lo(gh[it].x), sd[1] * bf_hi(gh[it].x)), a23 = pack_bf2(sd[2] * bf_lo(gh[it].y), sd[3] * bf_hi(gh[it].y));
                const float ag[4] = {bf_lo(a01), bf_hi(a01), bf_lo(a23), bf_hi(a23)};
#pragma unroll
                for (int j = 0; j < 4; j++) {
                    float4 w = w4[4 + j];
                    uu[0] += ag[j] * w.x; uu[1] += ag[j] * w.y; uu[2] += ag[j] * w.z; uu[3] += ag[j] * w.w;
                }
                const uint32_t t01 = hmul_bf2(pack_bf2(uu[0], uu[1]), gh[it].z);
                const uint32_t t23 = hmul_bf2(pack_bf2(uu[2], uu[3]), gh[it].w);
                uint2 q;
                asm("add.rn.bf16x2 %0, %1, %2;" : "=r"(q.x) : "r"(mv[u].x), "r"(t01));
                asm("add.rn.bf16x2 %0, %1, %2;" : "=r"(q.y) : "r"(mv[u].y), "r"(t23));
                p.out[row0 + i] = q;
            }
        }
        if (i0 == 0) { TKY(3) }
    }
}

template <int HOP> __device__ __forceinline__ uint2 null_rec(int lane, uint32_t R) {
    if (HOP == 1) return make_uint2(0x800000u | H<1>::tag(R), (OFF_CNT1 - OFF_M) / 8);
    return make_uint2(0x08000800u | lane << 28, 0x08000800u | H<2>::tag(R));
}
template <int OFF> __device__ __forceinline__ void sts128(uint32_t a, const uint4& v) {
    asm volatile("st.shared.v4.u32 [%0+%5], {%1,%2,%3,%4};" ::"r"(a), "r"(v.x), "r"(v.y), "r"(v.z), "r"(v.w), "n"(OFF) : "memory");
}
template <int HOP> __device__ __forceinline__ void fill(uint32_t win, int lane, uint32_t R) {
    const uint2 v = null_rec<HOP>(lane, R);
#pragma unroll 11
    for (int i = 0; i < WIN / 512; i++) sts128<0>(win + lane * 16 + i * 512, make_uint4(v.x, v.y, v.x, v.y));
}
template <int HOP> __device__ __forceinline__ void reset(uint32_t win, int lane, uint32_t R) {
    const uint2 v = null_rec<HOP>(lane, R);
    const uint32_t a = win + lane * 32 + H<HOP>::mark(R, lane >> 2) * 8;
#pragma unroll
    for (int i = 0; i < 16; i++) sts64(a + i * 1024, v.x, v.y);
    if (lane < 16) sts64(a + 16384, v.x, v.y);
}
__device__ __forceinline__ bool elect() {
    uint32_t q; asm volatile("{ .reg .pred q; elect.sync _|q, 0xffffffff; selp.u32 %0, 1, 0, q; }" : "=r"(q)); return q;
}
__device__ __forceinline__ const unsigned char* mk_ptr(uint32_t lo, uint32_t hi) { return reinterpret_cast<const unsigned char*>((uint64_t)hi << 32 | lo); }
__device__ __forceinline__ void bulk_store(uint32_t lo, uint32_t hi, uint32_t src, uint32_t n) {
    asm volatile("cp.async.bulk.global.shared::cta.bulk_group [%0], [%1], %2;" ::"l"(mk_ptr(lo, hi)), "r"(src), "r"(n) : "memory");
}
#define CRED_NS 100
#define CRED_SKIP 1
template <int HOP>
__device__ __forceinline__ void manager(const Params& p, uint32_t sb, int lane, int role, uint32_t base) {
    typedef H<HOP> h;
    constexpr int V = h::NBIN / 32, PB = h::S * 8;
    const int RT = p.rounds, lo = HOP == 1 && role >= NG ? NG : 0, hi = lo + h::NBIN;
    const int w = (role - lo) / (HOP * J), j = (role - lo - w * HOP * J) / HOP;
    const Ring rg(p.ring, __reduce_or_sync(0xffffffffu, lds32(sb + W_PAR)), 2 * w + HOP - 1);
    const uint32_t side = lds32(sb + W_SIDE), dhi = rg.main >> 32, mhi = rg.mid >> 32;
    const uint32_t c0 = HOP == 2 ? role & 1 : 0, up = (HOP == 1 && lo) ^ rg.par ^ c0;
    uint32_t dA = ((uint32_t)rg.main + src_off(j) + (c0 << 16) + (up ? 4096 : 12288)) ^ slot_off(base % 3);
    uint32_t dM = ((uint32_t)rg.mid + src_off(j) + c0 * 1024) ^ slot_off(base % 3);
    const int a0 = max(64, lo), b1 = min(68, hi);
    int n0 = (min(NHI, hi) - a0) * PB, a1 = (max(NLO, lo) - lo) * PB;
    const unsigned char* cr = reinterpret_cast<const unsigned char*>(rg.main) + MISC + ((side ^ rg.par) << 12);
    const unsigned char* cr0 = cr + cred_off(lo + lane * V), *cr1 = cr + cred_off(lo + 32 * V + min(lane, V - 1));
    const uint32_t ca0 = sb + h::CNT + lane * V * 4, ca1 = sb + h::CNT + (32 * V + min(lane, V + NDUM)) * 4;
    const uint32_t rot0 = (lane * V & 7) * 16, rot1 = lane * 16;
    uint32_t st = slot_steps(base);
    uint32_t init = h::init(base), prim = sb + h::STG + (HOP == 1 ? h::win(base) : 0u);
    uint32_t cs[5];
    auto sample = [&]() {
        if (V == 2) asm volatile("ld.relaxed.gpu.global.v2.u32 {%0,%1}, [%2];" : "=r"(cs[0]), "=r"(cs[1]) : "l"(cr0) : "memory");
        else asm volatile("ld.relaxed.gpu.global.v4.u32 {%0,%1,%2,%3}, [%4];" : "=r"(cs[0]), "=r"(cs[1]), "=r"(cs[2]), "=r"(cs[3]) : "l"(cr0) : "memory");
        cs[V] = ld_rlx32(reinterpret_cast<const uint32_t*>(cr1));
    };
    sample();
    uint32_t c[5];
    TK_DECL
#pragma unroll 1
    for (int r = 0;; r++) {
        const uint32_t R = base + r, ninit = h::init(R + 1), done = prim;
        TK(5)
        mbar_wait(sb + B_FULL + (HOP - 1) * 8, r & 1);
        TK(0)
        if (V == 2) asm volatile("ld.shared.v2.u32 {%0,%1}, [%2];" : "=r"(c[0]), "=r"(c[1]) : "r"(ca0) : "memory");
        else asm volatile("ld.shared.v4.u32 {%0,%1,%2,%3}, [%4];" : "=r"(c[0]), "=r"(c[1]), "=r"(c[2]), "=r"(c[3]) : "r"(ca0) : "memory");
        c[V] = lds32(ca1);
        uint32_t nc[5];
#pragma unroll
        for (int k = 0; k <= V; k++) {
            const uint32_t z = ninit + (k < V ? rot0 + k * 16 : rot1);
            nc[k] = min(max(c[k] + (ninit - init - h::S * h::INC), z), z + (h::CAP - h::S) * h::INC);
        }
        if (V == 2) sts64(ca0, nc[0], nc[1]); else sts128<0>(ca0, make_uint4(nc[0], nc[1], nc[2], nc[3]));
        sts32(ca1, lane < V ? nc[V] : lane < V + NDUM ? DUMMY : r);
        __syncwarp();
        if (lane == 0) mbar_arrive(sb + B_OPEN + (HOP - 1) * 8);
        TK(1)
        TK(2)
        asm volatile("fence.proxy.async.shared::cta;" ::: "memory");
        TK(6)
        if (r >= D) {
            int it = 0;
            while (true) {
                uint32_t bad = 0;
#pragma unroll
                for (int k = 0; k <= V; k++) bad |= cs[k] - (R - D + 1);
                if (!__any_sync(0xffffffffu, bad >> 20)) break;
                if (++it > SPIN_LIMIT) __trap();
                if (it > CRED_SKIP) __nanosleep(CRED_NS);
                sample();
            }
        }
        TK(3)
        if (elect()) {
            const uint32_t dB = (HOP == 1 ? dA ^ 0x10000u : dA) + (up ? 8192 : -8192), sm = prim + (lo ? 2 * PB : 0);
            bulk_store(dA, dhi, sm, 8192);
            bulk_store(dB, dhi, HOP == 1 ? sm + 8192 : prim + 68 * PB, 8192);
            if (n0 > 0) bulk_store(dM + (a0 - 64) * PB, mhi, prim + (a0 - lo) * PB, n0);
            if (a1 < (b1 - lo) * PB) bulk_store((dM ^ 4096u) + (uint32_t)((lo - NLO) * PB + a1), mhi, prim + a1, (b1 - lo) * PB - a1);
            asm volatile("cp.async.bulk.commit_group;" ::: "memory");
            asm volatile("cp.async.bulk.wait_group.read 0;" ::: "memory");
        }
        __syncwarp();
        TK(4)
        prim = HOP == 1 ? prim ^ 0x20000u : prim >= sb + 0x30000u ? sb : prim + (prim - sb) + 0x10000u;
        if (r == RT - 1) break;
        reset<HOP>(done, lane, R + HOP + 1);
        if (HOP == 1) {
            __syncwarp();
            if (lane == 0) mbar_arrive(sb + B_FREE);
        }
        if (r == D - 1 || r == RT - D - 1) {
            uint32_t n = NHI, m = NLO;
            if (r < RT - D - 1) {
                int it = 0;
                while (true) {
                    n = ld_rlx32(reinterpret_cast<const uint32_t*>(p.ring + M_CNT + (side << 12)));
                    if ((n & 0xffffu) + (n >> 16) == NB) break;
                    if (++it > SPIN_LIMIT) __trap();
                }
                m = n = min(max(__reduce_or_sync(0xffffffffu, n) & 0xffffu, (uint32_t)NLO), (uint32_t)NHI);
            }
            n0 = (min((int)n, hi) - a0) * PB;
            a1 = (max((int)m, lo) - lo) * PB;
        }
        sample();
        slot_next(dA, st); slot_next(dM, st);
        st = slot_rot(st);
        init = ninit;
    }
#pragma unroll 1
    for (int k = 0; k <= V; k++) {
        const uint32_t bin = k < V ? lane * V + k : 32 * V + lane, n = bin < h::NBIN ? min((pick(k, c) - init) >> h::SH, (uint32_t)h::CAP) : 0u;
#pragma unroll 1
        for (uint32_t x = h::S; x < n; x++) {
            const uint2 w = lds64(prim + bin * PB + ((x + (bin & 7) * 2) & (h::S - 1)) * 8);
            if (HOP == 1) slow_rec1(p, w.x, w.y, bin);
            else slow_rec2(p, w.x, w.y, bin, __uint_as_float(lds32(sb + W_UNIT)));
        }
    }
    asm volatile("cp.async.bulk.wait_group 0;" ::: "memory");
    TK_OUT
}

#define POLL_NS 200
#define POLL_NS3 1500
template <int HOP> struct Reader {
    uint32_t lo, hi, st, line;
    uint32_t* cred;
    __device__ __forceinline__ void init(const Params& p, uint32_t sb, int w, int lane, int role, uint32_t base) {
        constexpr int PB = H<HOP>::S * 8;
        const int first = HOP == 1 ? (role >= NG ? NG : 0) + w * J : w * 2 * J;
        const Ring rg(p.ring, lds32(sb + W_PAR), 2 * w + HOP - 1);
        const uint32_t side = lds32(sb + W_SIDE);
        const bool mid = side ? role < 68 : role >= 64;
        const uint32_t i = role - (side ? (mid ? NLO : 68) : (mid ? 64 : 0));
        const uint32_t c = HOP == 1 ? i >> 5 : lane >> 3 & 1, in = (HOP == 1 ? (i & 31) * PB + (lane & 15) * 16 : i * PB + (lane & 7) * 16) + (lane >> 4) * src_off(3);
        lo = (in + (mid ? ((uint32_t)rg.mid ^ side << 12) + c * 1024 : (uint32_t)rg.main + (c << 16) + (side ^ rg.par ^ c ? 4096 : 12288))) ^ slot_off(base % 3);
        hi = __reduce_or_sync(0xffffffffu, (uint32_t)((mid ? rg.mid : rg.main) >> 32));
        st = slot_steps(base);
        line = (HOP == 1 ? 2 * (role % NG) + (lane >> 3 & 1) : role) + (lane & 1) * 2;
        const bool both = first >= NLO && first < NHI;
        cred = lane < 1 + both ? reinterpret_cast<uint32_t*>(rg.main + MISC + (((both ? lane : first >= NG) ^ rg.par) << 12) + cred_off(role)) : nullptr;
    }
    template <int K> __device__ __forceinline__ void load1(uint2 (&v)[J]) const {
        asm volatile("ld.relaxed.gpu.global.v4.u32 {%0,%1,%2,%3}, [%4+%5];" : "=r"(v[2 * K].x), "=r"(v[2 * K].y), "=r"(v[2 * K + 1].x), "=r"(v[2 * K + 1].y)
                     : "l"(mk_ptr(lo, hi)), "n"(src_off(K)) : "memory");
    }
    static __device__ __forceinline__ uint32_t word(const uint2& v) { return HOP == 1 ? v.x : v.y; }
    template <int K> __device__ __forceinline__ void again(uint2 (&v)[J], uint32_t want, uint32_t m0, uint32_t m1, uint32_t grp) const {
        if (__ballot_sync(0xffffffffu, ((word(v[2 * K]) ^ want) & m0) | ((word(v[2 * K + 1]) ^ want) & m1)) & grp) load1<K>(v);
    }
    __device__ __forceinline__ void load(uint2 (&rec)[J]) const { load1<0>(rec); load1<1>(rec); load1<2>(rec); }
    __device__ __forceinline__ void check(uint2 (&rec)[J], uint32_t R, uint32_t ns TK_ARG) {
        const uint32_t want = H<HOP>::tag(R), mk = H<HOP>::mark(R, line);
        const uint32_t m0 = mk == 0 ? H<HOP>::TAG : 0u, m1 = mk == 1 ? H<HOP>::TAG : 0u;
        int it = 0;
        while (true) {
            uint32_t b0 = 0, b1 = 0;
#pragma unroll
            for (int j = 0; j < J; j += 2) { b0 |= word(rec[j]) ^ want; b1 |= word(rec[j + 1]) ^ want; }
            if (!__any_sync(0xffffffffu, (b0 & m0) | (b1 & m1))) break;
            if (++it > SPIN_LIMIT) __trap();
            __nanosleep(ns);
            TK_CNT(7)
            const uint32_t grp = 0xffu << (threadIdx.x & 24u);
            again<0>(rec, want, m0, m1, grp); again<1>(rec, want, m0, m1, grp); again<2>(rec, want, m0, m1, grp);
        }
        if (cred) st_rlx32(cred, R + 1);
        __syncwarp();
        slot_next(lo, st);
        st = slot_rot(st);
    }
    __device__ __forceinline__ void finish() const { if (cred) st_rlx32(cred, 0u); }
};

#define NPROBE 9
__device__ __forceinline__ uint32_t near_half(unsigned char* pair, uint32_t zero) {
#pragma unroll
    for (int i = 0; i < 4; i++) *reinterpret_cast<uint4*>(pair + (i >> 1) * 4096 + (i & 1) * 16) = make_uint4(0u, 0u, 0u, 0u);
    uint32_t best[2] = {~0u, ~0u}, v = 0, prev = 0;
    asm volatile("red.relaxed.gpu.global.add.u32 [%0], 1;" ::"l"(pair + 4096) : "memory");
#pragma unroll
    for (int t = 0; t <= NPROBE; t++) {
        uint32_t now;
        asm volatile("atom.relaxed.gpu.global.add.u32 %0, [%1], 1;" : "=r"(v) : "l"(pair + (t & 1) * 4096 + (v & zero)) : "memory");
        asm volatile("mov.u32 %0, %%clock;" : "=r"(now) :: "memory");
        if (t > 1) best[(t - 1) & 1] = min(best[(t - 1) & 1], now - prev);
        prev = now;
    }
    return (best[1] < best[0] ? 1u : 0u) | (v & zero);
}
template <bool B> struct BoolC { static constexpr bool value = B; };

template <int NP>
__device__ __forceinline__ void stage1(const Params& p, uint32_t sb, const int pos0, int lane, uint32_t base) {
    typedef H<1> h;
    const int RT = p.rounds;
    uint32_t ff = *reinterpret_cast<const uint16_t*>(p.ang_freq) * 0x10001u;
    auto pair_of = [&](int r, int pos) {
        const int q = r < RT - 1 ? (r * NB + blockIdx.x) * NPR + pos : (RT - 1) * NB * NPR + blockIdx.x * p.lastn + pos;
        return (r < RT - 1 || (r == RT - 1 && pos < p.lastn)) && q < p.T2 ? q : -1;
    };
    uint2 vi[NP], vo[NP]; uint32_t va[NP];
    auto load_edge = [&](int r) {
#pragma unroll
        for (int u = 0; u < NP; u++) {
            const int q = max(pair_of(r, pos0 + u * 32), 0);
            vi[u] = ld_in(p.idx_in + q); vo[u] = ld_in(p.idx_out + q); va[u] = ld_in(p.angle + q);
        }
    };
    load_edge(0);
    if (blockIdx.x == 0 && pos0 == 0 && (p.T & 1)) {
        const int t = p.T - 1;
        slow_triplet(p, reinterpret_cast<const uint32_t*>(p.idx_in)[t], reinterpret_cast<const uint32_t*>(p.idx_out)[t],
                     bf16r(cos_bf(hmul_bf2(reinterpret_cast<const uint16_t*>(p.angle)[t], ff) & 0xffffu)));
    }
    for (int i = threadIdx.x * 16; i < p.R2 && blockIdx.x * p.R2 + i < p.E; i += NS1 * 32 * 16) prefetch_l2(p.m + blockIdx.x * p.R2 + i);
    uint32_t R = __reduce_or_sync(0xffffffffu, base);
    ff = __reduce_or_sync(0xffffffffu, ff);
    bar_sync(BAR_S1, (NS1 + 1) * 32);
    TK_DECL
    auto step = [&](const int r, const int qn, auto edge) {
        constexpr bool EDGE = decltype(edge)::value;
        uint32_t cc[NP], big = 0;
#pragma unroll
        for (int u = 0; u < NP; u++) {
            va[u] = hmul_bf2(va[u], ff);
            cc[u] = pack_bf2(__cosf(bf_lo(va[u])), __cosf(bf_hi(va[u])));
            big = __vmaxu2(big, va[u] & 0x7fff7fffu);
        }
        if ((big + (0x7fffu - BIGX) * 0x10001u) & 0x80008000u) {
#pragma unroll 1
            for (int u = 0; u < NP; u++) {
                const uint32_t a = pick(u, va);
                float c0 = cos_bf(a & 0xffffu), c1 = cos_bf(a >> 16);
                if ((c0 != c0 || c1 != c1) && (!EDGE || pair_of(r, pos0 + u * 32) >= 0)) {
                    const uint2 i2 = pick(u, vi), o2 = pick(u, vo);
                    if (c0 != c0) slow_triplet(p, i2.x, o2.x, c0);
                    if (c1 != c1) slow_triplet(p, i2.y, o2.y, c1);
                }
                const uint32_t v = pack_bf2(c0 != c0 ? 0.f : c0, c1 != c1 ? 0.f : c1);
#pragma unroll
                for (int k = 0; k < NP; k++) if (k == u) cc[k] = v;
            }
        }
        uint32_t bin[2 * NP], x[2 * NP], y[2 * NP];
        uint32_t dep = 0;
        auto loads = [&]() {
            const int q = qn + (dep & p.zero);
#pragma unroll
            for (int u = 0; u + 1 < NP; u += 2) {
                if (TEXIN) { tex2(p.ta, q + u * 16, va[u], va[u + 1]); tex4(p.to, q + u * 16, vo[u], vo[u + 1]); tex4(p.ti, q + u * 16, vi[u], vi[u + 1]); }
                else {
                    const uint2 v = ld_in(reinterpret_cast<const uint2*>(p.angle) + q + u * 16); va[u] = v.x; va[u + 1] = v.y;
                    ld_in4(p.idx_out + 2 * (q + u * 16), vo[u], vo[u + 1]); ld_in4(p.idx_in + 2 * (q + u * 16), vi[u], vi[u + 1]);
                }
            }
            if (NP & 1) {
                const int k = 2 * q - lane + (NP - 1) * 32;
                va[NP - 1] = ld_in(p.angle + k); vo[NP - 1] = ld_in(p.idx_out + k); vi[NP - 1] = ld_in(p.idx_in + k);
            }
        };
#pragma unroll
        for (int j = 0; j < 2 * NP; j++) {
            const uint32_t ii = j & 1 ? vi[j >> 1].y : vi[j >> 1].x, oo = j & 1 ? vo[j >> 1].y : vo[j >> 1].x;
            bin[j] = __umulhi(ii, p.mg1);
            y[j] = __byte_perm(bin[j] * p.k1 + ii, cc[j >> 1], j & 1 ? 0x7610 : 0x5410);
            const uint32_t bo = __umulhi(oo, p.mg2);
            x[j] = __byte_perm(bo * p.k2 + oo * 8u, bo, 0x0514);
            dep |= x[j] | y[j];
            if (EDGE && pair_of(r, pos0 + (j >> 1) * 32) < 0) bin[j] = NG + (lane & (NDUM - 1));
        }
        if (EDGE) load_edge(r + 1);
        else loads();
        const uint32_t init = h::init(R), kb = sb + h::win(R + 1), lim = init + (h::CAP << h::SH);
        TK(0)
        mbar_wait(sb + B_OPEN, ~R & 1);
        TK(1)
        bool freed = false;
        uint32_t over = 0;
#pragma unroll
        for (int g = 0; g < 2 * NP; g += G1) {
            constexpr int G = G1;
            uint32_t ret[G];
            int mx = 0;
#pragma unroll
            for (int j = 0; j < G; j++) if (g + j < 2 * NP) ret[j] = atoms_add<h::CNT>(sb + bin[g + j] * 4, h::INC);
#pragma unroll
            for (int j = 0; j < G; j++) if (g + j < 2 * NP) mx = j ? max(mx, (int)ret[j]) : (int)ret[j];
            if (!DEFER && !freed && __any_sync(0xffffffffu, mx >= (int)(init + 0x10000u))) { TK(2) mbar_wait(sb + B_FREE, ~R & 1); freed = true; TK(3) }
            TK(2)
#pragma unroll
            for (int j = 0; j < G; j++) if (g + j < 2 * NP) {
                x[g + j] = and_or<h::TAG>(ret[j], x[g + j]);
                if (DEFER) {
                    bin[g + j] = and_xor(EDGE ? ret[j] | (ret[j] >> 14 & 0x20000u) : ret[j], 0x20000u | h::PM, bin[g + j] * 256 + kb);
                    put_rec<h::STG>(ret[j], init + 0x10000u, bin[g + j], x[g + j], y[g + j]);
                } else put_rec<h::STG>(ret[j], lim, and_xor(ret[j], 0x20000u | h::PM, bin[g + j] * 256 + kb), x[g + j], y[g + j]);
            }
            if (mx >= (int)lim) {
#pragma unroll
                for (int j = 0; j < G; j++) if (g + j < 2 * NP && (int)ret[j] >= (int)lim) { over |= 1u << (g + j); if (DEFER) bin[g + j] = mux(bin[g + j], ~kb, 0x20000u); }
            }
        }
        if (!DEFER || !EDGE) { __syncwarp(); if (elect()) mbar_arrive(sb + B_FULL); }
        if (DEFER) {
            TK(4)
            mbar_wait(sb + B_FREE, ~R & 1);
            TK(3)
#pragma unroll
            for (int j = 0; j < 2 * NP; j++) put_rec<h::STG>(xor_and<0x20000u>(bin[j], kb), 1u, bin[j], x[j], y[j]);
            if (EDGE) { __syncwarp(); if (elect()) mbar_arrive(sb + B_FULL); }
        }
        R++;
        TK(4)
#pragma unroll 1
        while (over) {
            TK_CNT(7)
            const int j = __ffs(over) - 1;
            over &= over - 1;
            slow_rec1(p, pick(j, x), pick(j, y), DEFER ? (pick(j, bin) - sb) >> 8 & 0xffu : pick(j, bin));
        }
        __syncwarp();
    };
#pragma unroll 1
    for (int q = (NB + blockIdx.x) * NPR; q < p.qfull; q += NB * NPR) step(q / (NB * NPR) - 1, (q + pos0 + lane) >> 1, BoolC<false>());
#pragma unroll 1
    for (int r = max(p.qfull / (NB * NPR) - 1, 0); r < RT; r++) step(r, 0, BoolC<true>());
    TK_OUT
}

__device__ __forceinline__ void stage2(const Params& p, uint32_t sb, int w, int lane, int role, uint32_t base) {
    typedef H<2> h;
    const int RT = p.rounds;
    Reader<1> rd;
    rd.init(p, sb, w, lane, role, base);
    uint2 rec[J];
    rd.load(rec);
    bar_sync(BAR_TABLE, 2 * NC * 32);
    uint32_t kb = sb + 0x10000u, am = 0x10000u | h::PM;
    const float unit = __uint_as_float(__reduce_or_sync(0xffffffffu, lds32(sb + W_UNIT)));
    TK_DECL
#pragma unroll 1
    for (int r = 0; r < RT; r++) {
        rd.check(rec, base + r, POLL_NS TK_PASS);
        const uint32_t want = H<1>::tag(base + r);
        TK(0)
        uint2 mv[J];
#pragma unroll
        for (int j = 0; j < J; j++) mv[j] = lds64<OFF_M>(sb + (rec[j].y & 0xffffu) * 8);
        uint32_t fl = 0;
#pragma unroll
        for (int j = 0; j < J; j++) fl |= mv[j].y;
        if (fl & 0x40000000u) {
#pragma unroll 1
            for (int j = 0; j < J; j++) {
                const uint2 v = pick(j, mv), w = pick(j, rec);
                if ((v.y & 0x40000000u) && !((w.x ^ want) & 0xf00000u)) {
                    if (v.x & 0x40000000u) slow_rec1(p, w.x, w.y, lds32(sb + W_ROLE) % NG);
                    else {
                        const float c = bf_hi(w.y), s = __uint_as_float(lds32(sb + W_UNIT)) * 1024.f;
                        side_add(w.x & 0xffu, __byte_perm(w.x, 0u, 0x4413) >> 3, c * (bf_lo(v.x) * s), c * (bf_hi(v.x) * s),
                                 c * (bf_lo(v.y) * s), c * (bf_hi(v.y & 0xbfffffffu) * s));
                    }
                }
            }
#pragma unroll
            for (int j = 0; j < J; j++) if (mv[j].y & 0x40000000u) rec[j].x = 0x800000u;
        }
        uint32_t w0[J], w1[J], bin[J], ret[J];
#pragma unroll
        for (int j = 0; j < J; j++) {
            const float c = bf_hi(rec[j].y), MG = 8194.0f;
            const uint32_t x = rec[j].x;
            w0[j] = and_or<0xf000f000u>(x, __byte_perm(__float_as_uint(fmaf(c, bf_lo(mv[j].x), MG)), __float_as_uint(fmaf(c, bf_hi(mv[j].x), MG)), 0x5410));
            w1[j] = and_or<0xf000f000u>(x << 4, __byte_perm(__float_as_uint(fmaf(c, bf_lo(mv[j].y), MG)), __float_as_uint(fmaf(c, bf_hi(mv[j].y), MG)), 0x5410));
            bin[j] = min(xor_and<0xf000ffu>(x, want), NB + (lane & (NDUM - 1)));
        }
        const uint32_t lim = h::init(base + r) + 0x20000u;
        rd.load(rec);
        TK(1)
        mbar_wait(sb + B_OPEN + 8, (r - 1) & 1);
        TK(2)
#pragma unroll
        for (int j = 0; j < J; j++) ret[j] = atoms_add<h::CNT>(sb + bin[j] * 4, h::INC);
        uint32_t mx = 0;
#pragma unroll
        for (int j = 0; j < J; j++) {
            w1[j] = and_or<h::TAG>(ret[j], w1[j]);
            put_rec<0>(ret[j], lim, and_xor(ret[j], am, bin[j] * 128 + kb), w0[j], w1[j]);
            mx = __viaddmax_u32(ret[j], 0u - DUMMY, mx);
        }
        __syncwarp();
        if (lane == 0) mbar_arrive(sb + B_FULL + 8);
        TK(3)
        if (mx >= lim - DUMMY) {
            uint32_t over = 0;
#pragma unroll
            for (int j = 0; j < J; j++) if (ret[j] - DUMMY >= lim - DUMMY) over |= 1u << j;
#pragma unroll 1
            do {
                const int j = __ffs(over) - 1;
                over &= over - 1;
                slow_rec2(p, pick(j, w0), pick(j, w1), pick(j, bin), unit);
            } while (over);
        }
        __syncwarp();
        am = am >= 0x30000u ? 0x10000u | h::PM : am + 0x10000u;
        kb ^= am & 0x30000u;
        TK(4)
    }
    rd.finish();
    TK_OUT
}

__device__ __forceinline__ float2 acc_fix(uint32_t old, uint32_t q) {
    const uint32_t u = old + 0x40004000u, n = u + q - 0x08000800u;
    return make_float2((float)((int)(u & 0xffffu) + (int)(q & 0xffffu) - 2048 - (int)(n & 0xffffu)), (float)((int)(u >> 16) + (int)(q >> 16) - 2048 - (int)(n >> 16)));
}
__device__ __forceinline__ void stage3(const Params& p, uint32_t sb, int w, int lane, int role, uint32_t base) {
    const int RT = p.rounds;
    Reader<2> rd;
    rd.init(p, sb, w, lane, role, base);
    uint2 nxt[J], rec[J];
    bar_sync(BAR_TABLE, 2 * NC * 32);
    if (PRE3 < J) rd.load(nxt);
    TK_DECL
#pragma unroll 1
    for (int r = 0; r < RT; r++) {
        if (PRE3 >= J) rd.load(nxt);
        rd.check(nxt, base + r, r < RT - 2 ? POLL_NS3 : 100 TK_PASS);
#pragma unroll
        for (int j = 0; j < J; j++) rec[j] = nxt[j];
        TK(0)
        const uint32_t want = H<2>::tag(base + r), t = 0u - (lane & 1u), k = (t & 1u << 26) - (want >> 4);
        uint32_t o0[J], o1[J], g = 0;
#pragma unroll
        for (int j = 0; j < J; j++) {
            if (j == PRE3) { rd.load(nxt); __syncwarp(); }
            o0[j] = 0; o1[j] = 0;
            if (!xor_and<H<2>::TAG>(rec[j].y, want)) {
                const uint32_t a = aux_of(rec[j].x, rec[j].y, k);
                const uint32_t v0 = (rec[j].x & 0x0fff0fffu) - 0x08000800u, v1 = (rec[j].y & 0x0fff0fffu) - 0x08000800u;
                o0[j] = atoms_add<OFF_ACC>(sb + a, mux(v0, v1, t));
                o1[j] = atoms_add<OFF_ACC>(sb + (a ^ 4u), mux(v1, v0, t));
            }
        }
#pragma unroll
        for (int j = 0; j < J; j++) g |= o0[j] | o1[j];
        if (__any_sync(0xffffffffu, g & 0x80008000u)) {
#pragma unroll 1
            for (int j = 0; j < J; j++) {
                const uint2 w = pick(j, rec);
                const uint32_t aux = aux_of(w.x, w.y), p0 = pick(j, o0), p1 = pick(j, o1);
                const float2 a = acc_fix(t ? p1 : p0, w.x & 0x0fff0fffu), b = acc_fix(t ? p0 : p1, w.y & 0x0fff0fffu);
                const float unit = __uint_as_float(lds32(sb + W_UNIT));
                if (!((w.y ^ want) & H<2>::TAG) && (a.x != 0.f || a.y != 0.f || b.x != 0.f || b.y != 0.f))
                    side_add(lds32(sb + W_ROLE), aux >> 3, a.x * unit, a.y * unit, b.x * unit, b.y * unit);
                __syncwarp();
            }
        }
        TK(1)
    }
    rd.finish();
    TK_OUT
}

__device__ __forceinline__ uint32_t row_max(uint32_t x, uint32_t y) {
    const uint32_t mx = __vmaxu2(x & 0x7fff7fffu, y & 0x7fff7fffu);
    return max(mx & 0xffffu, mx >> 16);
}
constexpr int EWIN = 5;

__global__ void __launch_bounds__(NTHR, 1) fused_kernel(const Params p) {
    const int tid = threadIdx.x, lane = tid & 31;
    const int hw = __reduce_max_sync(0xffffffffu, tid >> 5);
    const uint32_t sb = __reduce_or_sync(0xffffffffu, (uint32_t)__cvta_generic_to_shared(smem));
    TKX(0)
    const uint32_t epoch = ld_rlx32(&g_base);
    uint32_t base = epoch & 31u;

    if (hw < NS1) {
        if (hw < NS1 - 1 || NPR == 1024) stage1<4>(p, sb, hw * 128 + lane, lane, base);
        else stage1<NPR / 32 - (NS1 - 1) * 4>(p, sb, hw * 128 + lane, lane, base);
        __threadfence();
        bar_arrive(BAR_DONE, (NS1 + NC + 2) * 32);
    } else if (hw == W_M1) {
        if (lane == 0) {
            if (sb & 255u) __trap();
            mbar_init(sb + B_FULL, NS1); mbar_init(sb + B_OPEN, 1); mbar_init(sb + B_FREE, 1);
        }
        base = __reduce_or_sync(0xffffffffu, base);
        if (lane == 0 && (base & 1u)) { mbar_arrive(sb + B_OPEN); mbar_arrive(sb + B_FREE); }
        for (int i = lane; i < NG + NDUM; i += 32) sts32(sb + OFF_CNT1 + i * 4, i < NG ? H<1>::init(base) + (i & 7) * 16 : DUMMY);
#pragma unroll 1
        for (int i = 0; i < 2; i++) fill<1>(sb + OFF_H1 + H<1>::win(base + i), lane, base + i);
        bar_arrive(BAR_S1, (NS1 + 1) * 32);
        bar_sync(BAR_PROBE, (2 * NC + 1) * 32);
        {
            const uint32_t raw = __ballot_sync(0xffffffffu, lane < 2 * NC && smem[OFF_PROBE + lane]), side = raw & 1u;
            uint32_t v = 0;
            if (lane < 2) asm volatile("atom.relaxed.gpu.global.add.u32 %0, [%1], %2;" : "=r"(v) : "l"(p.ring + M_CNT + lane * 4096), "r"(side ? 0x10000u : 1u) : "memory");
            const uint32_t mine = (side ? ~raw : raw) | 0x80000000u;
            if (lane == 2) asm volatile("atom.relaxed.gpu.global.cas.b32 %0, [%1], 0, %2;" : "=r"(v) : "l"(p.ring + M_PAR), "r"(mine) : "memory");
            bar_sync(BAR_HIST, (2 * NC + 1) * 32);
            uint32_t best = 0;
#pragma unroll 1
            for (int e = 11 + lane; e <= 230; e += 32) {
                uint32_t c = 0;
#pragma unroll
                for (int i = 0; i < EWIN; i++) c += lds32(sb + OFF_HIST + (e - i) * 4);
                best = max(best, c << 8 | (255 - e));
            }
            const uint32_t e = 255 - (__reduce_max_sync(0xffffffffu, best) & 255u);
            if (lane == 0) {
                const uint32_t role = side ? NB - 1 - (v >> 16) : v & 0xffffu;
                sts32(sb + W_ROLE, role); sts32(sb + W_SIDE, role < NLO ? 0u : role >= NHI ? 1u : side);
                sts32(sb + W_EXP, e); sts32(sb + W_UNIT, (e - 10) << 23); sts32(sb + W_END, (epoch | 31u) + 1u + (base + p.rounds) % 24u);
            }
            if (lane == 2) sts32(sb + W_PAR, v ? v : mine);
        }
        bar_sync(BAR_ROLE, (2 * NC + 2) * 32);
        manager<1>(p, sb, lane, __reduce_max_sync(0xffffffffu, lds32(sb + W_ROLE)), base);
        bar_arrive(BAR_H1, (NS1 + 1) * 32);
        __threadfence();
        bar_arrive(BAR_DONE, (NS1 + NC + 2) * 32);
    } else if (hw == W_M2) {
        const float wd = __bfloat162float(lane & 16 ? p.w_up[lane & 15] : p.w_down[lane & 15]);
        const float ws = __bfloat162float(p.w_sbf[lane]), wr = __bfloat162float(p.w_rbf[lane]);
        const __nv_bfloat16 cen = p.centers[lane & 7];
        if (lane == 0) { mbar_init(sb + B_FULL + 8, NC); mbar_init(sb + B_OPEN + 8, 1); }
        base = __reduce_or_sync(0xffffffffu, base);
        for (int i = lane; i <= NB + NDUM; i += 32) sts32(sb + OFF_CNT2 + i * 4, i < NB ? H<2>::init(base) + (i & 7) * 16 : DUMMY);
#pragma unroll 1
        for (int i = 0; i < 3; i++) fill<2>(sb + H<2>::win(i), lane, base + i);
        reinterpret_cast<float*>(smem + OFF_WSM)[lane] = wd;
        reinterpret_cast<float*>(smem + OFF_WG)[lane] = ws;
        reinterpret_cast<float*>(smem + OFF_WG + 128)[lane] = wr;
        reinterpret_cast<__nv_bfloat16*>(smem + OFF_WG + 256)[lane & 7] = cen;
        bar_sync(BAR_ROLE, (2 * NC + 2) * 32);
        manager<2>(p, sb, lane, __reduce_max_sync(0xffffffffu, lds32(sb + W_ROLE)), base);
        __threadfence();
        bar_sync(BAR_DONE, (NS1 + NC + 2) * 32);
        if (lane < 2) { __threadfence(); st_rlx32(reinterpret_cast<uint32_t*>(p.ring + M_FLAG + lane * 4096) + blockIdx.x, lds32(sb + W_END)); }
    } else {
        const int pw = __reduce_max_sync(0xffffffffu, hw < W_M1 ? hw - NS1 : hw - NS1 - 1), ct = pw * 32 + lane;
        constexpr int CT = 2 * NC * 32;
        const uint4 sm = __ldg(reinterpret_cast<const uint4*>(p.m) + min((ct >> 3) * (p.E >> 1) / (CT / 8) + (lane & 7), (p.E >> 1) - 1));
        if (ct < 256) sts32(sb + OFF_HIST + ct * 4, 0u);
        if (lane == 0) smem[OFF_PROBE + pw] = pw < NPAGE ? near_half(p.ring + (size_t)pw * PAGE + PROBE + (blockIdx.x & 31) * 128 + (blockIdx.x >> 5 & 3) * 16384 + (blockIdx.x >> 7 << 20), p.zero) : 0;
        TKX(1)
        bar_sync(BAR_PROBE, (2 * NC + 1) * 32);
        {
            const uint32_t m0 = row_max(sm.x, sm.y), m1 = row_max(sm.z, sm.w);
            if (m0) atoms_add<OFF_HIST>(sb + (m0 >> 7) * 4, 1u);
            if (m1) atoms_add<OFF_HIST>(sb + (m1 >> 7) * 4, 1u);
        }
        bar_arrive(BAR_HIST, (2 * NC + 1) * 32);
        base = __reduce_or_sync(0xffffffffu, base);
        for (int i = ct; i < R2MAX / 2; i += CT) reinterpret_cast<uint4*>(smem + OFF_ACC)[i] = make_uint4(0x40004000u, 0x40004000u, 0x40004000u, 0x40004000u);
        bar_sync(BAR_ROLE, (2 * NC + 2) * 32);
        const int role = __reduce_max_sync(0xffffffffu, lds32(sb + W_ROLE));
        TKX(2)
        {
            const int e = lds32(sb + W_EXP), q0 = (role >= NG ? role - NG : role) * (p.R1 >> 1), nq = min(p.R1 >> 1, (p.E >> 1) - q0);
            const uint32_t sc = (uint32_t)(254 - e) * 0x800080u;
            constexpr int CH = (R1MAX / 2 + CT - 1) / CT;
            uint4 v[CH];
#pragma unroll
            for (int u = 0; u < CH; u++) v[u] = __ldg(reinterpret_cast<const uint4*>(p.m) + min(q0 + ct + u * CT, (p.E >> 1) - 1));
            auto conv = [&](uint32_t& x, uint32_t& y) {
                const uint32_t mx = row_max(x, y);
                const int d = e - (int)(mx >> 7);
                x = hmul_bf2(x, sc); y = hmul_bf2(y, sc);
                if (d >= EWIN) y |= 0x40000000u;
                if (d < 0 || (d >= EWIN && e > 127)) { x = 0x40000000u; y = x; }
                if (mx == 0) { x = 0; y = 0; }
            };
#pragma unroll
            for (int u = 0; u < CH; u++) {
                conv(v[u].x, v[u].y); conv(v[u].z, v[u].w);
                if (ct + u * CT < nq) sts128<OFF_M>(sb + (ct + u * CT) * 16, v[u]);
            }
        }
        TKX(3)
        if (hw < W_M1) {
            stage2(p, sb, pw, lane, role, base);
            __threadfence();
            bar_arrive(BAR_DONE, (NS1 + NC + 2) * 32);
        } else {
            stage3(p, sb, pw - NC, lane, role, base);
            __threadfence();
        }
    }
    TKX(4)
    epilogue(p, sb);
}

__global__ void fb_scatter(const uint2* __restrict__ m, const int* __restrict__ idx_in, const int* __restrict__ idx_out,
                           const uint16_t* __restrict__ angle, const __nv_bfloat16* __restrict__ ang_freq, int T, int e0, int e1) {
    const uint32_t fb = *reinterpret_cast<const uint16_t*>(ang_freq);
    for (long long t = blockIdx.x * (long long)blockDim.x + threadIdx.x; t < T; t += (long long)gridDim.x * blockDim.x) {
        int o = idx_out[t];
        if (o < e0 || o >= e1) continue;
        float c = bf16r(cos_bf(hmul_bf2(angle[t], fb) & 0xffffu));
        uint2 v = __ldg(m + idx_in[t]);
        red4(&g_ovf[o - e0], c * bf_lo(v.x), c * bf_hi(v.x), c * bf_lo(v.y), c * bf_hi(v.y));
    }
}
__global__ void fb_final(const Params p, int e0, int e1) {
    int e = e0 + blockIdx.x * blockDim.x + threadIdx.x;
    if (e >= e1) return;
    float4 a4 = g_ovf[e - e0];
    g_ovf[e - e0] = make_float4(0.f, 0.f, 0.f, 0.f);
    float a[4] = {a4.x, a4.y, a4.z, a4.w};
    float d = __bfloat162float(p.dist[e]);
    float g[4] = {0, 0, 0, 0}, h[4] = {0, 0, 0, 0};
    for (int r = 0; r < 8; r++) {
        float df = bf16r(d - __bfloat162float(p.centers[r]));
        float rb = bf16r(expf(bf16r(-10.0f * bf16r(df * df))));
        for (int k = 0; k < 4; k++) {
            g[k] += rb * __bfloat162float(p.w_sbf[r * 4 + k]);
            h[k] += rb * __bfloat162float(p.w_rbf[r * 4 + k]);
        }
    }
    float ag[4];
    for (int k = 0; k < 4; k++) {
        float s = 0.f;
        for (int j = 0; j < 4; j++) s += a[j] * __bfloat162float(p.w_down[j * 4 + k]);
        ag[k] = bf16r(s * g[k]);
    }
    uint2 mv = p.m[e];
    float mm[4] = {bf_lo(mv.x), bf_hi(mv.x), bf_lo(mv.y), bf_hi(mv.y)};
    __nv_bfloat16 o[4];
    for (int k = 0; k < 4; k++) {
        float u = 0.f;
        for (int j = 0; j < 4; j++) u += ag[j] * __bfloat162float(p.w_up[j * 4 + k]);
        o[k] = __float2bfloat16_rn(mm[k] + bf16r(bf16r(u) * bf16r(h[k])));
    }
    p.out[e] = *reinterpret_cast<uint2*>(o);
}

}

static bool exact_div(int E, int lo, int hi, int* R, uint32_t* magic) {
    for (int r = lo + (lo & 1); r <= hi; r += 2) {
        unsigned long long mg = ((1ull << 32) + r - 1) / r, err = mg * r - (1ull << 32);
        if (err * (unsigned long long)E < (1ull << 32)) { *R = r; *magic = (uint32_t)mg; return true; }
    }
    return false;
}

static cudaTextureObject_t make_tex(const void* ptr, size_t bytes, int words) {
    cudaResourceDesc rd = {}; cudaTextureDesc td = {};
    rd.resType = cudaResourceTypeLinear; rd.res.linear.devPtr = const_cast<void*>(ptr); rd.res.linear.sizeInBytes = bytes;
    rd.res.linear.desc = cudaCreateChannelDesc(32, words > 1 ? 32 : 0, words > 2 ? 32 : 0, words > 2 ? 32 : 0, cudaChannelFormatKindUnsigned);
    td.readMode = cudaReadModeElementType;
    cudaTextureObject_t t = 0;
    if (cudaCreateTextureObject(&t, &rd, &td, nullptr) != cudaSuccess) { t = 0; (void)cudaGetLastError(); }
    return t;
}

extern "C" void kernel_launch(void* const* d_in, const int* in_sizes, int n_in, void* d_out, int out_size) {
    typedef const __nv_bfloat16* B;
    Params p;
    p.m = (const uint2*)d_in[0]; p.idx_in = (const uint2*)d_in[1]; p.idx_out = (const uint2*)d_in[2]; p.dist = (B)d_in[3];
    p.angle = (const uint32_t*)d_in[4]; p.centers = (B)d_in[5]; p.ang_freq = (B)d_in[6]; p.w_rbf = (B)d_in[7]; p.w_sbf = (B)d_in[8];
    p.w_down = (B)d_in[9]; p.w_up = (B)d_in[10]; p.out = (uint2*)d_out;
    p.E = in_sizes[3]; p.T = in_sizes[1]; p.T2 = p.T >> 1; p.zero = 0;
    p.R1 = p.R2 = p.rounds = p.lastn = p.qfull = 0; p.mg1 = p.mg2 = p.k1 = p.k2 = 0;
    static int ok = -1;
    static unsigned char* ring = nullptr;
    if (ok < 0) {
        void* ra = nullptr;
        cudaGetSymbolAddress(&ra, g_ring);
        ring = reinterpret_cast<unsigned char*>(((uintptr_t)ra + PAGE - 1) & ~(uintptr_t)(PAGE - 1));
        int dev = 0, sms = 0, occ = 0;
        cudaGetDevice(&dev);
        cudaDeviceGetAttribute(&sms, cudaDevAttrMultiProcessorCount, dev);
        cudaError_t e = cudaFuncSetAttribute(fused_kernel, cudaFuncAttributeMaxDynamicSharedMemorySize, SMEM_BYTES);
        if (e == cudaSuccess) e = cudaOccupancyMaxActiveBlocksPerMultiprocessor(&occ, fused_kernel, NTHR, SMEM_BYTES);
        ok = (e == cudaSuccess && occ >= 1 && sms >= NB) ? 1 : 0;
        (void)cudaGetLastError();
    }
    p.ring = ring;
    static cudaTextureObject_t tx[3];
    if (!tx[0]) { tx[0] = make_tex(p.idx_in, (size_t)(p.T >> 2) * 16, 4); tx[1] = make_tex(p.idx_out, (size_t)(p.T >> 2) * 16, 4); tx[2] = make_tex(p.angle, (size_t)(p.T >> 2) * 8, 2); }
    p.ti = tx[0]; p.to = tx[1]; p.ta = tx[2];
    const bool fused = ok == 1 && p.E <= EMAX && p.E >= 2 * NB && p.E % 2 == 0 && p.T >= 2 && exact_div(p.E, (p.E + NG - 1) / NG, R1MAX, &p.R1, &p.mg1) &&
                       exact_div(p.E, (p.E + NB - 1) / NB, R2MAX, &p.R2, &p.mg2);
    if (fused) {
        p.k1 = 0u - (uint32_t)p.R1; p.k2 = 0u - 8u * (uint32_t)p.R2;
        const int per = NB * NPR;
        int full = p.T2 / per, rest = p.T2 - full * per;
        p.qfull = full * per;
        p.lastn = (rest + NB - 1) / NB;
        if (p.lastn > NPR / 2) { full++; p.lastn = 0; }
        if (full < D) { full = D; p.lastn = 0; }
        p.rounds = full + 1;
        fused_kernel<<<NB, NTHR, SMEM_BYTES>>>(p);
    } else {
        for (int e0 = 0; e0 < p.E; e0 += EMAX) {
            int e1 = p.E - e0 < EMAX ? p.E : e0 + EMAX;
            fb_scatter<<<1056, 256>>>(p.m, (const int*)d_in[1], (const int*)d_in[2], (const uint16_t*)d_in[4], p.ang_freq, p.T, e0, e1);
            fb_final<<<(e1 - e0 + 255) / 256, 256>>>(p, e0, e1);
        }
    }
}
```

```cpp
#include <cuda_runtime.h>
#include <cuda_bf16.h>
#include <stdint.h>

#define RARE(x) __builtin_expect(!!(x), 0)
namespace {

constexpr int NB = 132, NG = 66;
constexpr int R2MAX = 6062, R1MAX = 12124;
constexpr int EMAX = NB * R2MAX;
constexpr int NTHR = 1024;
constexpr int NS1 = 8, NC = 11, J = 6;
#define TILES 30
#define TEXIN 1
#define G1 4
#define CAP1 64
constexpr int NPR = TILES * 32;
constexpr int D = 3;
constexpr int WIN = 16896;
constexpr int NDUM = 16;
constexpr uint32_t DUMMY = 0xc0000000u;

constexpr int OFF_ACC = WIN, OFF_BAR = OFF_ACC + R2MAX * 8;
constexpr int OFF_H1 = 0x10000 + WIN, OFF_M = OFF_H1 + WIN, OFF_WSM = OFF_M + R1MAX * 8;
constexpr int OFF_CNT1 = OFF_H1 + 0x20000 + WIN, OFF_CNT2 = OFF_CNT1 + (NG + NDUM + 2) * 4;
constexpr int OFF_HIST = OFF_ACC;
constexpr int OFF_PROBE = OFF_WSM + 128;
constexpr int SMEM_BYTES = OFF_CNT2 + (NB + NDUM) * 4 + 16;
static_assert(SMEM_BYTES <= 232448 && OFF_BAR + 64 <= 0x10000 && OFF_PROBE + 160 <= 0x30000, "smem");
static_assert(OFF_BAR % 8 == 0 && OFF_WSM % 16 == 0 && OFF_CNT2 % 16 == 0, "align");
static_assert(NC * J == NG && NC * 32 * 6 * 16 == 2 * WIN, "shape");

template <int HOP> struct H {
    static constexpr int S = HOP == 1 ? 32 : 16, NBIN = HOP == 1 ? NG : NB, CAP = HOP == 1 ? CAP1 : 32, SH = HOP == 1 ? 11 : 12;
    static constexpr int TB = HOP == 1 ? 20 : 28, CNT = HOP == 1 ? OFF_CNT1 : OFF_CNT2, STG = HOP == 1 ? OFF_H1 : 0;
    static_assert(CAP <= 2 * S, "two windows");
    static constexpr uint32_t INC = (1u << SH) + 8u, PM = (S - 1) * 8, TAG = 7u << TB;
    static __device__ __forceinline__ uint32_t tag(uint32_t R) { return R << TB & TAG; }
    static __device__ __forceinline__ uint32_t init(uint32_t R) { return tag(R) | ((1u << TB) - 0x10000u); }
    static __device__ __forceinline__ uint32_t mark(uint32_t R, uint32_t line) { return ((HOP == 1 ? R >> 1 : R) + line) & 3u; }
    static __device__ __forceinline__ uint32_t win(int r) { return HOP == 1 ? (r & 1) << 17 : (0x310u >> (r % 3 * 4) & 3u) << 16; }
};

constexpr uint32_t PAGE = 1u << 21;
constexpr int NPAGE = NC + 2;
__device__ __align__(256) unsigned char g_ring[(size_t)(NPAGE + 1) * PAGE];
constexpr int MISC = 0xa0000;
constexpr int M_CNT = MISC + 1024, M_PAR = MISC + 1088;
constexpr int M_FLAG = MISC + 2048;
constexpr int PROBE = MISC + 0x40000;
#define CSTR 16384
__device__ __forceinline__ uint32_t cred_off(uint32_t role) { return role * 4 + min(role >> 5, 3u) * (CSTR - 128); }
struct Ring {
    uint64_t main, mid;
    uint32_t par;
    __device__ __forceinline__ Ring(const unsigned char* ring, uint32_t pars, int k) {
        main = reinterpret_cast<uint64_t>(ring) + ((uint64_t)k << 20);
        par = pars >> (k >> 1) & 1u;
        mid = reinterpret_cast<uint64_t>(ring) + (uint64_t)NC * PAGE + (((k >> 3 << 20) + (k >> 2 & 1) * 0x11000u + (k & 1) * 2048) ^ (k >> 1 & 1) * 0x3000u ^ (pars >> (NC + (k >> 4)) & 1u) << 12);
    }
};
constexpr int NLO = 60, NHI = 72;
__host__ __device__ constexpr uint32_t src_off(int j) { return (j % 3) << 14 | (j / 3) << 18; }
__device__ __forceinline__ uint32_t slot_off(uint32_t s) { return (0xa930u >> s * 4 & 15u) << 16; }
__device__ __forceinline__ uint32_t slot_steps(uint32_t R) { return (uint32_t)(0x30a09030aull >> (2 - R % 3) * 8) & 0xffffffu; }
__device__ __forceinline__ void slot_next(uint32_t& a, uint32_t st) { a ^= st & 0xf0000u; }
__device__ __forceinline__ uint32_t slot_rot(uint32_t st) { return __byte_perm(st, 0u, 0x4102); }
constexpr int RPAD = 6064, DROW = 6144;
__device__ __align__(128) uint8_t g_dirty[NB * DROW];
#define XB 0
constexpr int BOX = 32, BOXN = 24, LATE = 8;
__device__ __align__(128) uint2 g_box[NB * NB * BOX];
__device__ uint32_t g_base = 1;
__device__ __align__(128) float4 g_ovf[NB * RPAD];

struct Params {
    const uint2* m; const uint2* idx_in; const uint2* idx_out; const __nv_bfloat16* dist; const uint32_t* angle;
    const __nv_bfloat16* centers; const __nv_bfloat16* ang_freq; const __nv_bfloat16* w_rbf; const __nv_bfloat16* w_sbf;
    const __nv_bfloat16* w_down; const __nv_bfloat16* w_up; uint2* out; unsigned char* ring;
    cudaTextureObject_t ti, to, ta;
    int E, T, T2, R1, R2, rounds, lastn, full; uint32_t mg1, mg2, k1, k2, zero;
};

__device__ __forceinline__ float bf16r(float x) { return __bfloat162float(__float2bfloat16_rn(x)); }
__device__ __forceinline__ float bf_lo(uint32_t v) { return __uint_as_float(v << 16); }
__device__ __forceinline__ float bf_hi(uint32_t v) { return __uint_as_float(v & 0xffff0000u); }
__device__ __forceinline__ void red4(float4* a, float x, float y, float z, float w) {
    asm volatile("red.global.add.v4.f32 [%0], {%1,%2,%3,%4};" ::"l"(a), "f"(x), "f"(y), "f"(z), "f"(w) : "memory");
}
__device__ __forceinline__ void bar_sync(int id, int n) { __syncwarp(); asm volatile("bar.sync %0, %1;" ::"r"(id), "r"(n) : "memory"); }
__device__ __forceinline__ void bar_arrive(int id, int n) { __syncwarp(); asm volatile("bar.arrive %0, %1;" ::"r"(id), "r"(n) : "memory"); }
template <int OFF> __device__ __forceinline__ uint32_t atoms_add(uint32_t addr, uint32_t v) {
    uint32_t r; asm volatile("atom.shared.add.u32 %0, [%1+%3], %2;" : "=r"(r) : "r"(addr), "r"(v), "n"(OFF) : "memory"); return r;
}
__device__ __forceinline__ void sts64(uint32_t addr, uint32_t x, uint32_t y) {
    asm volatile("st.shared.v2.u32 [%0], {%1,%2};" ::"r"(addr), "r"(x), "r"(y) : "memory");
}
__device__ __forceinline__ void sts32(uint32_t addr, uint32_t x) { asm volatile("st.shared.u32 [%0], %1;" ::"r"(addr), "r"(x) : "memory"); }
template <int OFF = 0> __device__ __forceinline__ uint2 lds64(uint32_t addr) {
    uint2 v; asm volatile("ld.shared.v2.u32 {%0,%1}, [%2+%3];" : "=r"(v.x), "=r"(v.y) : "r"(addr), "n"(OFF) : "memory"); return v;
}
__device__ __forceinline__ uint32_t lds32(uint32_t addr) {
    uint32_t v; asm volatile("ld.shared.u32 %0, [%1];" : "=r"(v) : "r"(addr) : "memory"); return v;
}
template <int OFF> __device__ __forceinline__ void sts128(uint32_t a, const uint4& v) {
    asm volatile("st.shared.v4.u32 [%0+%5], {%1,%2,%3,%4};" ::"r"(a), "r"(v.x), "r"(v.y), "r"(v.z), "r"(v.w), "n"(OFF) : "memory");
}
__device__ __forceinline__ uint4 lds128(uint32_t a) {
    uint4 v; asm volatile("ld.shared.v4.u32 {%0,%1,%2,%3}, [%4];" : "=r"(v.x), "=r"(v.y), "=r"(v.z), "=r"(v.w) : "r"(a) : "memory"); return v;
}
__device__ __forceinline__ uint32_t ld_rlx32(const uint32_t* p) {
    uint32_t v; asm volatile("ld.relaxed.gpu.global.u32 %0, [%1];" : "=r"(v) : "l"(p) : "memory"); return v;
}
__device__ __forceinline__ uint2 ld_rlx64(const void* p) {
    uint2 v; asm volatile("ld.relaxed.gpu.global.v2.u32 {%0,%1}, [%2];" : "=r"(v.x), "=r"(v.y) : "l"(p) : "memory"); return v;
}
__device__ __forceinline__ float4 ld_rlx128f(const float4* p) {
    float4 v; asm volatile("ld.relaxed.gpu.global.v4.f32 {%0,%1,%2,%3}, [%4];" : "=f"(v.x), "=f"(v.y), "=f"(v.z), "=f"(v.w) : "l"(p) : "memory"); return v;
}
__device__ __forceinline__ float4 take(float4* p, bool q) {
    float4 v;
    asm volatile("{ .reg .b128 a; .reg .b64 x, y; .reg .pred q; mov.b64 x, 0; mov.b128 a, {x, x}; setp.ne.u32 q, %5, 0;\n"
                 "@q atom.relaxed.gpu.global.exch.b128 a, [%4], a; mov.b128 {x, y}, a; mov.b64 {%0,%1}, x; mov.b64 {%2,%3}, y; }"
                 : "=f"(v.x), "=f"(v.y), "=f"(v.z), "=f"(v.w) : "l"(p), "r"((uint32_t)q) : "memory");
    return v;
}
__device__ __forceinline__ void fence_gpu() { asm volatile("fence.acq_rel.gpu;" ::: "memory"); }
__device__ __forceinline__ void st_rlx32(uint32_t* p, uint32_t v) { asm volatile("st.relaxed.gpu.global.u32 [%0], %1;" ::"l"(p), "r"(v) : "memory"); }
__device__ __forceinline__ uint32_t hmul_bf2(uint32_t a, uint32_t b) {
    uint32_t r; asm("mul.rn.bf16x2 %0, %1, %2;" : "=r"(r) : "r"(a), "r"(b)); return r;
}
__device__ __forceinline__ uint32_t hsub_bf2(uint32_t a, uint32_t b) {
    uint32_t r; asm("sub.rn.bf16x2 %0, %1, %2;" : "=r"(r) : "r"(a), "r"(b)); return r;
}
__device__ __forceinline__ uint32_t hadd_bf2(uint32_t a, uint32_t b) {
    uint32_t r; asm("add.rn.bf16x2 %0, %1, %2;" : "=r"(r) : "r"(a), "r"(b)); return r;
}
__device__ __forceinline__ int opaque(int v) { return __shfl_sync(0xffffffffu, v, threadIdx.x); }
constexpr int SPIN_LIMIT = 1 << 22;

__constant__ uint32_t c_inv2pi[8] = {0u, 0x28be60dbu, 0x9391054au, 0x7f09d5f4u, 0x7d4d3770u, 0x36d8a566u, 0x4f10e410u, 0x7f9458eau};
constexpr uint32_t BIGX = 0x4280u;
__device__ __forceinline__ float cos_big(uint32_t xb) {
    uint32_t e = (xb >> 7) & 0xffu, M = (xb & 0x7fu) | 0x80u;
    uint32_t pp = e - 102u;
    uint32_t wi = pp >> 5;
    uint32_t t0 = c_inv2pi[wi], t1 = c_inv2pi[wi + 1], t2 = c_inv2pi[wi + 2];
    uint32_t f = M * __funnelshift_l(t1, t0, pp) + __umulhi(M, __funnelshift_l(t2, t1, pp));
    float c = __cosf((float)(int)f * 1.4629180792671596e-9f);
    return e == 255u ? __uint_as_float(0x7fc00000u) : c;
}
__device__ __forceinline__ float cos_bf(uint32_t xb) {
    return (xb & 0x7fffu) > BIGX ? cos_big(xb) : __cosf(__uint_as_float(xb << 16));
}
__device__ __forceinline__ uint32_t pack_bf2(float lo, float hi) {
    uint32_t r; asm("cvt.rn.bf16x2.f32 %0, %1, %2;" : "=r"(r) : "f"(hi), "f"(lo)); return r;
}
template <int N> __device__ __forceinline__ uint32_t pick(int k, const uint32_t (&a)[N]) {
    uint32_t v = a[0];
#pragma unroll
    for (int i = 1; i < N; i++) if (k == i) v = a[i];
    return v;
}
template <int N> __device__ __forceinline__ uint2 pick(int k, const uint2 (&a)[N]) {
    uint2 v = a[0];
#pragma unroll
    for (int i = 1; i < N; i++) if (k == i) v = a[i];
    return v;
}
__device__ __forceinline__ void side_add(uint32_t bin, uint32_t row, float a, float b, float c, float d) {
    red4(&g_ovf[bin * RPAD + row], a, b, c, d);
    g_dirty[bin * DROW + row] = 1;
}
__device__ __forceinline__ void slow_triplet(const Params& p, uint32_t ii, uint32_t oo, float c) {
    const uint2 v = __ldg(p.m + ii);
    const uint32_t bo = __umulhi(oo, p.mg2);
    side_add(bo, oo - bo * p.R2, c * bf_lo(v.x), c * bf_hi(v.x), c * bf_lo(v.y), c * bf_hi(v.y));
}
__device__ __forceinline__ void slow_rec1(const Params& p, uint32_t x, uint32_t y, uint32_t bin) {
    const uint2 v = __ldg(p.m + bin * p.R1 + (y & 0xffffu));
    const float c = bf_hi(y);
    side_add(x & 0xffu, __byte_perm(x, 0u, 0x4413) >> 3, c * bf_lo(v.x), c * bf_hi(v.x), c * bf_lo(v.y), c * bf_hi(v.y));
}
__device__ __forceinline__ uint32_t aux_of(uint32_t w0, uint32_t w1, uint32_t k = 0) {
    uint32_t u; asm("lop3.b32 %0, %1, %2, 0xf000f000, 0xe4;" : "=r"(u) : "r"(w0), "r"((w1 >> 4) + k));
    return __byte_perm(u, 0u, 0x4413);
}
__device__ __forceinline__ void slow_rec2(const Params& p, uint32_t w0, uint32_t w1, uint32_t bin, float unit) {
    side_add(bin, aux_of(w0, w1) >> 3, (float)((int)(w0 & 0xfffu) - 2048) * unit, (float)((int)(w0 >> 16 & 0xfffu) - 2048) * unit,
             (float)((int)(w1 & 0xfffu) - 2048) * unit, (float)((int)(w1 >> 16 & 0xfffu) - 2048) * unit);
}
template <uint32_t M> __device__ __forceinline__ uint32_t and_or(uint32_t a, uint32_t c) {
    uint32_t r; asm("lop3.b32 %0, %1, %2, %3, 0xea;" : "=r"(r) : "r"(a), "n"(M), "r"(c)); return r;
}
template <uint32_t M> __device__ __forceinline__ uint32_t xor_and(uint32_t a, uint32_t c) {
    uint32_t r; asm("lop3.b32 %0, %1, %2, %3, 0x48;" : "=r"(r) : "r"(a), "n"(M), "r"(c)); return r;
}
__device__ __forceinline__ uint32_t mux(uint32_t a, uint32_t b, uint32_t m) {
    uint32_t r; asm("lop3.b32 %0, %1, %2, %3, 0xd8;" : "=r"(r) : "r"(a), "r"(b), "r"(m)); return r;
}
__device__ __forceinline__ uint32_t and_xor(uint32_t a, uint32_t m, uint32_t c) {
    uint32_t r; asm("lop3.b32 %0, %1, %2, %3, 0x6a;" : "=r"(r) : "r"(a), "r"(m), "r"(c)); return r;
}
__device__ __forceinline__ uint2 ld_in(const uint2* a) {
    uint2 v; asm volatile("ld.global.nc.L1::no_allocate.v2.u32 {%0,%1}, [%2];" : "=r"(v.x), "=r"(v.y) : "l"(a)); return v;
}
__device__ __forceinline__ uint32_t ld_in(const uint32_t* a) {
    uint32_t v; asm volatile("ld.global.nc.L1::no_allocate.u32 %0, [%1];" : "=r"(v) : "l"(a)); return v;
}
__device__ __forceinline__ void ld_in4(const uint2* p, uint2& a, uint2& b) {
    asm volatile("ld.global.nc.L1::no_allocate.v4.u32 {%0,%1,%2,%3}, [%4];" : "=r"(a.x), "=r"(a.y), "=r"(b.x), "=r"(b.y) : "l"(p));
}
__device__ __forceinline__ void tex4(cudaTextureObject_t t, int i, uint2& a, uint2& b) {
    asm volatile("tex.1d.v4.u32.s32 {%0,%1,%2,%3}, [%4, {%5}];" : "=r"(a.x), "=r"(a.y), "=r"(b.x), "=r"(b.y) : "l"(t), "r"(i));
}
__device__ __forceinline__ void tex2(cudaTextureObject_t t, int i, uint32_t& a, uint32_t& b) {
    asm volatile("{ .reg .b32 z, w; tex.1d.v4.u32.s32 {%0,%1,z,w}, [%2, {%3}]; }" : "=r"(a), "=r"(b) : "l"(t), "r"(i) : "memory");
}
template <int OFF> __device__ __forceinline__ void put_rec(uint32_t ret, uint32_t lim, uint32_t addr, uint32_t x, uint32_t y) {
    asm volatile("{ .reg .pred q; setp.lt.u32 q, %0, %1; @q st.shared.v2.u32 [%2+%5], {%3,%4}; }" ::"r"(ret), "r"(lim), "r"(addr), "r"(x), "r"(y), "n"(OFF) : "memory");
}
__device__ __forceinline__ uint32_t mbar_try(uint32_t mb, uint32_t parity) {
    uint32_t ok;
    asm volatile("{ .reg .pred q; mbarrier.try_wait.parity.shared::cta.b64 q, [%1], %2; selp.u32 %0, 1, 0, q; }" : "=r"(ok) : "r"(mb), "r"(parity) : "memory");
    return ok;
}
__device__ __forceinline__ void mbar_wait(uint32_t mb, uint32_t parity) {
    if (!mbar_try(mb, parity)) {
        int it = 0;
        while (!mbar_try(mb, parity)) if (++it > SPIN_LIMIT) __trap();
    }
}
__device__ __forceinline__ void mbar_init(uint32_t mb, uint32_t n) { asm volatile("mbarrier.init.shared::cta.b64 [%0], %1;" ::"r"(mb), "r"(n) : "memory"); }
__device__ __forceinline__ void mbar_arrive(uint32_t mb) { asm volatile("mbarrier.arrive.shared::cta.b64 _, [%0];" ::"r"(mb) : "memory"); }
constexpr int B_FULL = OFF_BAR, B_OPEN = OFF_BAR + 16, B_FREE = OFF_BAR + 32;
constexpr int W_END = OFF_BAR + 40, W_SIDE = OFF_BAR + 44, W_PAR = OFF_BAR + 48, W_ROLE = OFF_BAR + 52, W_EXP = OFF_BAR + 56, W_UNIT = OFF_BAR + 60, W_NLIST = OFF_PROBE + 112, W_WRAP = OFF_PROBE + 116, W_BASE = OFF_PROBE + 120, B_TAB = OFF_PROBE + 128;
enum { BAR_S1 = 1, BAR_SIDE, BAR_PROBE, BAR_PAR, BAR_TABLE, BAR_DONE, BAR_TFREE, BAR_ACC, BAR_FLAG, BAR_H1 };
constexpr int W_M1 = NS1 + NC, W_M2 = 31;

extern __shared__ __align__(1024) unsigned char smem[];
#define RTS(c, i)
#define TK_DECL
#define TK(i)
#define TK_CNT(i)
#define TK_OUT
#define TK_ARG
#define TK_PASS
#define TKS(i) TK(i)
#define TKX(i)
#define TKY(i) {}
#define TKZ(i, d)

__device__ __forceinline__ void prefetch_l2(const void* a) { asm volatile("prefetch.global.L2 [%0];" ::"l"(a)); }
__device__ __forceinline__ void wait_flags(const Params& p, uint32_t sb, int lane, uint32_t need) {
    const unsigned char* f = p.ring + M_FLAG + (lds32(sb + W_SIDE) << 12);
    int it = 0;
    while (true) {
        uint32_t a[5];
        asm volatile("ld.acquire.gpu.global.v4.u32 {%0,%1,%2,%3}, [%4];" : "=r"(a[0]), "=r"(a[1]), "=r"(a[2]), "=r"(a[3]) : "l"(f + lane * 16) : "memory");
        asm volatile("ld.acquire.gpu.global.u32 %0, [%1];" : "=r"(a[4]) : "l"(f + 512 + (lane & 3) * 4) : "memory");
        const uint32_t d = (a[0] ^ need) | (a[1] ^ need) | (a[2] ^ need) | (a[3] ^ need) | (a[4] ^ need);
        if (__all_sync(0xffffffffu, d == 0)) break;
        __nanosleep(50);
        if (++it > SPIN_LIMIT) __trap();
    }
}
__device__ __forceinline__ float exp_fast(float x) { float r; asm("ex2.approx.ftz.f32 %0, %1;" : "=f"(r) : "f"(x * 1.4426950408889634f)); return r; }
constexpr uint32_t BIAS = 0x3d803d80u, ZERO = 0x7d80u;
__device__ __forceinline__ float2 acc_fix(uint32_t old, uint32_t q) {
    const uint32_t u = old + BIAS, n = u + q - 0x08000800u;
    return make_float2((float)((int)(u & 0xffffu) + (int)(q & 0xffffu) - 2048 - (int)(n & 0xffffu)), (float)((int)(u >> 16) + (int)(q >> 16) - 2048 - (int)(n >> 16)));
}
constexpr int NE = NS1 + NC, NPAIR = (R2MAX / 2 + NE * 32 - 1) / (NE * 32), NTILE = 15, NG0 = NS1 * 8 * NTILE;
constexpr int OFF_G = OFF_M, GH = R2MAX * 8, OFF_LIST = OFF_G;
static_assert(2 * R2MAX <= R1MAX && NG0 * 16 <= WIN && NG0 + NE * 8 * NTILE >= R2MAX / 2 && NPAIR * NE * 64 <= DROW, "gates");
__device__ __forceinline__ int gate_g(int k) { return (k < NG0 ? OFF_H1 : OFF_G) + k * 16; }
__device__ __forceinline__ int gate_h(int k) { return (k < NG0 ? OFF_H1 + 0x20000 : OFF_G + GH) + k * 16; }
__device__ __forceinline__ uint2 out_row(int row, const float4& o, const float4& add, const uint2& mv) {
    const float* w = reinterpret_cast<const float*>(smem + OFF_WSM);
    const float unit = *reinterpret_cast<const float*>(smem + W_UNIT), K = 8388608.f + ZERO;
    const uint2 ac = reinterpret_cast<const uint2*>(smem + OFF_ACC)[row];
    const uint32_t* g = reinterpret_cast<const uint32_t*>(smem + gate_g(row >> 1)) + (row & 1), *h = reinterpret_cast<const uint32_t*>(smem + gate_h(row >> 1)) + (row & 1);
    const uint32_t c0 = ac.x + BIAS, c1 = ac.y + BIAS;
    const float a[4] = {fmaf(__uint_as_float(__byte_perm(c0, 0x4b00u, 0x5410)) - K, unit, o.x), fmaf(__uint_as_float(__byte_perm(c0, 0x4b00u, 0x5432)) - K, unit, o.y),
                        fmaf(__uint_as_float(__byte_perm(c1, 0x4b00u, 0x5410)) - K, unit, o.z), fmaf(__uint_as_float(__byte_perm(c1, 0x4b00u, 0x5432)) - K, unit, o.w)};
    float sd[4], uu[4];
#pragma unroll
    for (int k = 0; k < 4; k++) sd[k] = fmaf(a[3], w[12 + k], fmaf(a[2], w[8 + k], fmaf(a[1], w[4 + k], a[0] * w[k])));
    const uint32_t a01 = hmul_bf2(pack_bf2(sd[0] + add.x, sd[1] + add.y), g[0]), a23 = hmul_bf2(pack_bf2(sd[2] + add.z, sd[3] + add.w), g[2]);
#pragma unroll
    for (int k = 0; k < 4; k++) uu[k] = fmaf(bf_hi(a23), w[28 + k], fmaf(bf_lo(a23), w[24 + k], fmaf(bf_hi(a01), w[20 + k], bf_lo(a01) * w[16 + k])));
    return make_uint2(hadd_bf2(mv.x, hmul_bf2(pack_bf2(uu[0], uu[1]), h[0])), hadd_bf2(mv.y, hmul_bf2(pack_bf2(uu[2], uu[3]), h[2])));
}
__device__ __forceinline__ void mma16(float (&c)[4], const uint32_t (&a)[4], uint32_t b0, uint32_t b1) {
    asm volatile("mma.sync.aligned.m16n8k16.row.col.f32.bf16.bf16.f32 {%0,%1,%2,%3}, {%4,%5,%6,%7}, {%8,%9}, {%0,%1,%2,%3};"
                 : "+f"(c[0]), "+f"(c[1]), "+f"(c[2]), "+f"(c[3]) : "r"(a[0]), "r"(a[1]), "r"(a[2]), "r"(a[3]), "r"(b0), "r"(b1));
}
__device__ __forceinline__ void finish_rows(const Params& p, uint32_t sb) {
    int tid;
    asm volatile("mov.u32 %0, %%tid.x;" : "=r"(tid));
    const int role = lds32(sb + W_ROLE), row0 = role * p.R2, np = min(p.R2, p.E - row0) >> 1, lane = tid & 31;
    {
        const uint16_t* wg = reinterpret_cast<const uint16_t*>(lane & 16 ? p.w_rbf : p.w_sbf) + (lane & 3) * 8 + (lane >> 2 & 3);
        const uint16_t* cp = reinterpret_cast<const uint16_t*>(p.centers) + (lane & 3) * 2;
        const uint32_t wb = __ldg(wg) | (uint32_t)__ldg(wg + 4) << 16, cen = __ldg(cp) | (uint32_t)__ldg(cp + 1) << 16;
        if (tid < NS1 * 32) {
            if (tid * 32 < np) prefetch_l2(p.dist + row0 + tid * 64);
            for (int i = tid * 8; i < np; i += NS1 * 32 * 8) prefetch_l2(p.m + row0 + 2 * i);
        }
#pragma unroll 1
        for (int pass = tid >= NS1 * 32; pass < 2; pass++) {
            const int k0 = (pass ? NG0 : 0) + (tid >> 2), dk = pass ? NE * 8 : NS1 * 8;
            uint2 v[NTILE];
#pragma unroll
            for (int i = 0; i < NTILE; i++) v[i].x = ld_in(reinterpret_cast<const uint32_t*>(p.dist) + min((row0 >> 1) + k0 + i * dk, (p.E >> 1) - 1));
#pragma unroll
            for (int i = 0; i < NTILE; i++) {
                uint32_t rb[2];
#pragma unroll
                for (int u = 0; u < 2; u++) {
                    const uint32_t df = hsub_bf2(__byte_perm(v[i].x, 0u, u ? 0x3232 : 0x1010), cen);
                    const uint32_t ar = hmul_bf2(hmul_bf2(df, df), 0xc120c120u);
                    rb[u] = pack_bf2(exp_fast(bf_lo(ar)), exp_fast(bf_hi(ar)));
                }
                float c[4];
                asm volatile("mma.sync.aligned.m16n8k8.row.col.f32.bf16.bf16.f32 {%0,%1,%2,%3}, {%4,%5}, {%6}, {%7,%7,%7,%7};"
                             : "=f"(c[0]), "=f"(c[1]), "=f"(c[2]), "=f"(c[3]) : "r"(rb[0]), "r"(rb[1]), "r"(wb), "f"(0.f));
                v[i] = make_uint2(pack_bf2(c[0], c[1]), pack_bf2(c[2], c[3]));
            }
            if (pass) bar_sync(BAR_TFREE, NE * 32); else bar_sync(BAR_H1, (NS1 + 1) * 32);
            const uint32_t a = sb + (lane & 2 ? gate_h(k0) : gate_g(k0)) + (lane & 1) * 8;
#pragma unroll
            for (int i = 0; i < NTILE; i++) if (k0 + i * dk < R2MAX / 2) sts64(a + i * dk * 16, v[i].x, v[i].y);
            if (pass) TKY(1) else TKY(0)
        }
    }
    uint2 mv[2 * NPAIR];
#pragma unroll
    for (int i = 0; i < NPAIR; i++) ld_in4(p.m + 2 * min((row0 >> 1) + tid + i * NE * 32, (p.E >> 1) - 1), mv[2 * i], mv[2 * i + 1]);
    uint8_t* dirty = g_dirty + role * DROW + tid * 2;
    auto flags = [&]() {
        uint32_t f[NPAIR], m = 0;
#pragma unroll
        for (int i = 0; i < NPAIR; i++) asm volatile("ld.relaxed.gpu.global.u16 %0, [%1];" : "=r"(f[i]) : "l"(dirty + i * NE * 64) : "memory");
#pragma unroll
        for (int i = 0; i < NPAIR; i++) m |= ((f[i] | f[i] >> 7) & 3u) << 2 * i;
        return m;
    };
    auto row_of = [&](int j) { return 2 * tid + (j >> 1) * NE * 64 + (j & 1); };
    bar_sync(BAR_FLAG, (NE + 1) * 32);
    TKY(2)
    uint32_t kept = flags(), left = 0, bad = 0, at = 0;
    TKZ(3, kept)
    if (kept) {
        at = atoms_add<W_NLIST>(sb, __popc(kept));
        if (at + __popc(kept) > NG0) { left = kept; kept = 0; }
        at = sb + OFF_LIST + at * 16;
        uint32_t to = at;
#pragma unroll 1
        for (uint32_t m = kept; m; m &= m - 1) {
            float4 o[2];
            o[0] = take(&g_ovf[role * RPAD + row_of(__ffs(m) - 1)], true);
            m &= m - 1;
            o[1] = take(&g_ovf[role * RPAD + row_of(__ffs(m) - 1)], m);
            const float4* w = reinterpret_cast<const float4*>(smem + OFF_WSM);
#pragma unroll
            for (int u = 0; u < 2; u++) if (!u || m) {
                sts128<0>(to, make_uint4(__float_as_uint(fmaf(o[u].w, w[3].x, fmaf(o[u].z, w[2].x, fmaf(o[u].y, w[1].x, o[u].x * w[0].x)))),
                                         __float_as_uint(fmaf(o[u].w, w[3].y, fmaf(o[u].z, w[2].y, fmaf(o[u].y, w[1].y, o[u].x * w[0].y)))),
                                         __float_as_uint(fmaf(o[u].w, w[3].z, fmaf(o[u].z, w[2].z, fmaf(o[u].y, w[1].z, o[u].x * w[0].z)))),
                                         __float_as_uint(fmaf(o[u].w, w[3].w, fmaf(o[u].z, w[2].w, fmaf(o[u].y, w[1].w, o[u].x * w[0].w))))));
                to += 16;
            }
        }
    }
    uint32_t wb[8];
#pragma unroll
    for (int i = 0; i < 8; i++) {
        const uint32_t a = sb + OFF_WSM + ((i & 4) * 4 + (i & 1) * 8 + (i & 2) + (lane >> 2 & 1)) * 4;
        wb[i] = (lane & 3) == lane >> 3 ? __byte_perm(lds32(a), lds32(a + 16), 0x7632) : 0u;
    }
    const uint32_t k0 = (lds32(sb + W_UNIT) >> 16) * 0x10001u + 0x03800380u;
    TKX(5)
    bar_sync(BAR_ACC, (NE + NC) * 32);
    TKX(6)
    uint32_t from = at;
#pragma unroll
    for (int i = 0; i < NPAIR; i++) {
        const int k = tid + i * NE * 32;
        const uint4 ac = lds128(sb + OFF_ACC + k * 16), g = lds128(sb + gate_g(k)), h = lds128(sb + gate_h(k));
        const uint32_t u[4] = {ac.x + BIAS, ac.z + BIAS, ac.y + BIAS, ac.w + BIAS};
        uint32_t a[4];
        float c[4] = {0.f, 0.f, 0.f, 0.f}, d[4] = {0.f, 0.f, 0.f, 0.f};
#pragma unroll
        for (int j = 0; j < 2; j++)
            asm volatile("{ .reg .pred q; setp.ne.u32 q, %5, 0; @q ld.shared.v2.f32 {%0,%1}, [%4]; @q ld.shared.v2.f32 {%2,%3}, [%4+8]; @q add.u32 %4, %4, 16; }"
                         : "+f"(c[2 * j]), "+f"(c[2 * j + 1]), "+f"(d[2 * j]), "+f"(d[2 * j + 1]), "+r"(from) : "r"(kept & 1u << (2 * i + j)) : "memory");
#pragma unroll
        for (int j = 0; j < 4; j++) a[j] = hsub_bf2(and_or<0x007f007fu>(u[j] >> 9, k0 + 0x04800480u), k0 + 0x04c004c0u);
        mma16(c, a, wb[0], wb[1]); mma16(d, a, wb[2], wb[3]);
#pragma unroll
        for (int j = 0; j < 4; j++) a[j] = and_or<0x007f007fu>(u[j] >> 2, k0 + 0x01000100u);
        mma16(c, a, wb[0], wb[1]); mma16(d, a, wb[2], wb[3]);
#pragma unroll
        for (int j = 0; j < 4; j++) a[j] = and_or<0x00030003u>(u[j], k0);
        mma16(c, a, wb[0], wb[1]); mma16(d, a, wb[2], wb[3]);
        a[0] = hmul_bf2(pack_bf2(c[0], c[1]), g.x); a[1] = hmul_bf2(pack_bf2(c[2], c[3]), g.y);
        a[2] = hmul_bf2(pack_bf2(d[0], d[1]), g.z); a[3] = hmul_bf2(pack_bf2(d[2], d[3]), g.w);
#pragma unroll
        for (int j = 0; j < 4; j++) c[j] = d[j] = 0.f;
        mma16(c, a, wb[4], wb[5]); mma16(d, a, wb[6], wb[7]);
        if (k < np) {
            reinterpret_cast<uint4*>(p.out + row0)[k] = make_uint4(hadd_bf2(mv[2 * i].x, hmul_bf2(pack_bf2(c[0], c[1]), h.x)), hadd_bf2(mv[2 * i].y, hmul_bf2(pack_bf2(d[0], d[1]), h.z)),
                                                                   hadd_bf2(mv[2 * i + 1].x, hmul_bf2(pack_bf2(c[2], c[3]), h.y)), hadd_bf2(mv[2 * i + 1].y, hmul_bf2(pack_bf2(d[2], d[3]), h.w)));
            if (c[0] != c[0] || c[2] != c[2]) bad |= 3u << 2 * i;
        }
    }
    if (lds32(sb + W_WRAP)) left = flags();
#pragma unroll 1
    for (uint32_t m = left | bad; m; m &= m - 1) {
        const int j = __ffs(m) - 1, row = row_of(j);
        uint4 v = make_uint4(0u, 0u, 0u, 0u);
        if (kept >> j & 1u) v = lds128(at + __popc(kept & ((1u << j) - 1u)) * 16);
        p.out[row0 + row] = out_row(row, take(&g_ovf[role * RPAD + row], left >> j & 1u),
                                    make_float4(__uint_as_float(v.x), __uint_as_float(v.y), __uint_as_float(v.z), __uint_as_float(v.w)), p.m[row0 + row]);
    }
#pragma unroll 1
    for (uint32_t m = left | kept; m; m &= m - 1) g_dirty[role * DROW + row_of(__ffs(m) - 1)] = 0;
}

template <int HOP> __device__ __forceinline__ uint2 null_rec(int lane, uint32_t R) {
    if (HOP == 1) return make_uint2(0x800000u | H<1>::tag(R), (OFF_CNT1 - OFF_M) / 8);
    return make_uint2(0x08000800u | lane << 28, 0x08000800u | H<2>::tag(R));
}
template <int HOP> __device__ __forceinline__ void fill(uint32_t win, int lane, uint32_t R) {
    const uint2 v = null_rec<HOP>(lane, R);
#pragma unroll 11
    for (int i = 0; i < WIN / 512; i++) sts128<0>(win + lane * 16 + i * 512, make_uint4(v.x, v.y, v.x, v.y));
}
template <int HOP> __device__ __forceinline__ void reset(uint32_t win, int lane, uint32_t R) {
    const uint2 v = null_rec<HOP>(lane, R);
    const uint32_t a = win + lane * 32 + H<HOP>::mark(R, lane >> 2) * 8;
#pragma unroll
    for (int i = 0; i < 16; i++) sts64(a + i * 1024, v.x, v.y);
    if (lane < 16) sts64(a + 16384, v.x, v.y);
}
__device__ __forceinline__ bool elect() {
    uint32_t q; asm volatile("{ .reg .pred q; elect.sync _|q, 0xffffffff; selp.u32 %0, 1, 0, q; }" : "=r"(q)); return q;
}
__device__ __forceinline__ const unsigned char* mk_ptr(uint32_t lo, uint32_t hi) { return reinterpret_cast<const unsigned char*>((uint64_t)hi << 32 | lo); }
__device__ __forceinline__ void bulk_store(uint32_t lo, uint32_t hi, uint32_t src, uint32_t n) {
    asm volatile("cp.async.bulk.global.shared::cta.bulk_group [%0], [%1], %2;" ::"l"(mk_ptr(lo, hi)), "r"(src), "r"(n) : "memory");
}
#define CRED_NS 100
#define CRED_SKIP 1
template <int HOP>
__device__ __forceinline__ void manager(const Params& p, uint32_t sb, int lane, int role, uint32_t base) {
    typedef H<HOP> h;
    constexpr int V = h::NBIN / 32, PB = h::S * 8;
    const int RT = p.rounds, lo = HOP == 1 && role >= NG ? NG : 0, hi = lo + h::NBIN;
    const int w = (role - lo) / (HOP * J), j = (role - lo - w * HOP * J) / HOP;
    const Ring rg(p.ring, __reduce_or_sync(0xffffffffu, lds32(sb + W_PAR)), 2 * w + HOP - 1);
    const uint32_t side = lds32(sb + W_SIDE), dhi = rg.main >> 32, mhi = rg.mid >> 32;
    const uint32_t c0 = HOP == 2 ? role & 1 : 0, up = (HOP == 1 && lo) ^ rg.par ^ c0;
    uint32_t dA = ((uint32_t)rg.main + src_off(j) + (c0 << 16) + (up ? 4096 : 12288)) ^ slot_off(base % 3);
    uint32_t dM = ((uint32_t)rg.mid + src_off(j) + c0 * 1024) ^ slot_off(base % 3);
    const int a0 = max(64, lo), b1 = min(68, hi);
    int n0 = (min(NHI, hi) - a0) * PB, a1 = (max(NLO, lo) - lo) * PB;
    const unsigned char* cr = reinterpret_cast<const unsigned char*>(rg.main) + MISC + ((side ^ rg.par) << 12);
    const unsigned char* cr0 = cr + cred_off(lo + lane * V), *cr1 = cr + cred_off(lo + 32 * V + min(lane, V - 1));
    const uint32_t ca0 = sb + h::CNT + lane * V * 4, ca1 = sb + h::CNT + (32 * V + min(lane, V + NDUM)) * 4;
    const uint32_t rot0 = (lane * V & 7) * 16, rot1 = lane * 16;
    uint32_t st = slot_steps(base);
    uint32_t init = h::init(base), prim = sb + h::STG + (HOP == 1 ? h::win(base) : 0u);
    uint32_t cs[5] = {0, 0, 0, 0, 0};
    auto sample = [&]() {
        if (V == 2) asm volatile("ld.relaxed.gpu.global.v2.u32 {%0,%1}, [%2];" : "=r"(cs[0]), "=r"(cs[1]) : "l"(cr0) : "memory");
        else asm volatile("ld.relaxed.gpu.global.v4.u32 {%0,%1,%2,%3}, [%4];" : "=r"(cs[0]), "=r"(cs[1]), "=r"(cs[2]), "=r"(cs[3]) : "l"(cr0) : "memory");
        cs[V] = ld_rlx32(reinterpret_cast<const uint32_t*>(cr1));
    };
    uint32_t low[5] = {rot0, rot0 + 16, rot0 + 32, rot0 + 48, rot1};
    TK_DECL
#pragma unroll 1
    for (int r = 0;; r++) {
        const uint32_t R = base + r, ninit = h::init(R + 1), done = prim;
        TK(5)
        mbar_wait(sb + B_FULL + (HOP - 1) * 8, r & 1);
        TK(0)
        uint32_t c[5];
        if (V == 2) asm volatile("ld.shared.v2.u32 {%0,%1}, [%2];" : "=r"(c[0]), "=r"(c[1]) : "r"(ca0) : "memory");
        else asm volatile("ld.shared.v4.u32 {%0,%1,%2,%3}, [%4];" : "=r"(c[0]), "=r"(c[1]), "=r"(c[2]), "=r"(c[3]) : "r"(ca0) : "memory");
        c[V] = lds32(ca1);
        uint32_t nc[5];
#pragma unroll
        for (int k = 0; k <= V; k++) {
            const uint32_t rot = k < V ? rot0 + k * 16 : rot1, z = ninit + (HOP == 1 ? rot : low[k]);
            if (HOP == 2 && XB != 1) low[k] = min((max((int)(c[k] - low[k] - init - h::CAP * h::INC), 0) >> h::SH) * 128u + low[k], rot + BOXN * 128u);
            nc[k] = min(max(c[k] + (ninit - init - h::S * h::INC), z), (HOP == 1 ? z : ninit + low[k]) + (h::CAP - h::S) * h::INC);
        }
        if (V == 2) sts64(ca0, nc[0], nc[1]); else sts128<0>(ca0, make_uint4(nc[0], nc[1], nc[2], nc[3]));
        sts32(ca1, lane < V ? nc[V] : lane < V + NDUM ? DUMMY : r);
        __syncwarp();
        if (lane == 0) mbar_arrive(sb + B_OPEN + (HOP - 1) * 8);
        TK(1)
        TK(2)
        asm volatile("fence.proxy.async.shared::cta;" ::: "memory");
        TK(6)
        if (r >= D) {
            int it = 0;
            while (true) {
                uint32_t bad = 0;
#pragma unroll
                for (int k = 0; k <= V; k++) bad |= cs[k] - (R - D + 1);
                if (!__any_sync(0xffffffffu, bad >> 20)) break;
                if (++it > SPIN_LIMIT) __trap();
                if (it > CRED_SKIP) __nanosleep(CRED_NS);
                sample();
            }
        }
        TK(3)
        if (elect()) {
            const uint32_t dB = (HOP == 1 ? dA ^ 0x10000u : dA) + (up ? 8192 : -8192), sm = prim + (lo ? 2 * PB : 0);
            bulk_store(dA, dhi, sm, 8192);
            bulk_store(dB, dhi, HOP == 1 ? sm + 8192 : prim + 68 * PB, 8192);
            if (n0 > 0) bulk_store(dM + (a0 - 64) * PB, mhi, prim + (a0 - lo) * PB, n0);
            if (a1 < (b1 - lo) * PB) bulk_store((dM ^ 4096u) + (uint32_t)((lo - NLO) * PB + a1), mhi, prim + a1, (b1 - lo) * PB - a1);
            asm volatile("cp.async.bulk.commit_group;" ::: "memory");
            if (r != RT - 1) asm volatile("cp.async.bulk.wait_group.read 0;" ::: "memory");
        }
        __syncwarp();
        TK(4)
        prim = HOP == 1 ? prim ^ 0x20000u : prim >= sb + 0x30000u ? sb : prim + (prim - sb) + 0x10000u;
        if (r == RT - 1) break;
        reset<HOP>(done, lane, R + HOP + 1);
        if (HOP == 1) {
            __syncwarp();
            if (lane == 0) mbar_arrive(sb + B_FREE);
        }
        if (RARE(r == D - 1 || r == RT - D - 1)) {
            uint32_t n = NHI, m = NLO;
            if (r < RT - D - 1) {
                int it = 0;
                while (true) {
                    n = ld_rlx32(reinterpret_cast<const uint32_t*>(p.ring + M_CNT + (side << 12)));
                    if ((n & 0xffffu) + (n >> 16) == NB) break;
                    if (++it > SPIN_LIMIT) __trap();
                }
                m = n = min(max(__reduce_or_sync(0xffffffffu, n) & 0xffffu, (uint32_t)NLO), (uint32_t)NHI);
            }
            n0 = (min((int)n, hi) - a0) * PB;
            a1 = (max((int)m, lo) - lo) * PB;
        }
        if (HOP == 2 && RARE(r == RT - LATE)) fence_gpu();
        sample();
        slot_next(dA, st); slot_next(dM, st);
        st = slot_rot(st);
        init = ninit;
    }
    TK_OUT
}

#define POLL_NS 200
#define POLL_NS3 1500
template <int HOP> struct Reader {
    uint32_t lo, hi, st, line;
    uint32_t* cred;
    __device__ __forceinline__ void init(const Params& p, uint32_t sb, int w, int lane, int role, uint32_t base) {
        constexpr int PB = H<HOP>::S * 8;
        const int first = HOP == 1 ? (role >= NG ? NG : 0) + w * J : w * 2 * J;
        const Ring rg(p.ring, lds32(sb + W_PAR), 2 * w + HOP - 1);
        const uint32_t side = lds32(sb + W_SIDE);
        const bool mid = side ? role < 68 : role >= 64;
        const uint32_t i = role - (side ? (mid ? NLO : 68) : (mid ? 64 : 0));
        const uint32_t c = HOP == 1 ? i >> 5 : lane >> 3 & 1, in = (HOP == 1 ? (i & 31) * PB + (lane & 15) * 16 : i * PB + (lane & 7) * 16) + (lane >> 4) * src_off(3);
        lo = (in + (mid ? ((uint32_t)rg.mid ^ side << 12) + c * 1024 : (uint32_t)rg.main + (c << 16) + (side ^ rg.par ^ c ? 4096 : 12288))) ^ slot_off(base % 3);
        hi = __reduce_or_sync(0xffffffffu, (uint32_t)((mid ? rg.mid : rg.main) >> 32));
        st = slot_steps(base);
        line = opaque((HOP == 1 ? 2 * (role % NG) + (lane >> 3 & 1) : role) + (lane & 1) * 2);
        const bool both = first >= NLO && first < NHI;
        cred = lane < 1 + both ? reinterpret_cast<uint32_t*>(rg.main + MISC + (((both ? lane : first >= NG) ^ rg.par) << 12) + cred_off(role)) : nullptr;
    }
    template <int K> __device__ __forceinline__ void load1(uint2 (&v)[J]) const {
        asm volatile("ld.relaxed.gpu.global.v4.u32 {%0,%1,%2,%3}, [%4+%5];" : "=r"(v[2 * K].x), "=r"(v[2 * K].y), "=r"(v[2 * K + 1].x), "=r"(v[2 * K + 1].y)
                     : "l"(mk_ptr(lo, hi)), "n"(src_off(K)) : "memory");
    }
    static __device__ __forceinline__ uint32_t word(const uint2& v) { return HOP == 1 ? v.x : v.y; }
    template <int K> __device__ __forceinline__ void again(uint2 (&v)[J], uint32_t want, uint32_t m0, uint32_t m1, uint32_t grp) const {
        if (__ballot_sync(0xffffffffu, ((word(v[2 * K]) ^ want) & m0) | ((word(v[2 * K + 1]) ^ want) & m1)) & grp) load1<K>(v);
    }
    __device__ __forceinline__ void load(uint2 (&rec)[J]) const { load1<0>(rec); load1<1>(rec); load1<2>(rec); }
    __device__ __forceinline__ void check(uint2 (&rec)[J], uint32_t R, uint32_t ns, int lane TK_ARG) {
        const uint32_t want = H<HOP>::tag(R), mk = H<HOP>::mark(R, line);
        const uint32_t m0 = mk == 0 ? H<HOP>::TAG : 0u, m1 = mk == 1 ? H<HOP>::TAG : 0u;
        int it = 0;
        while (true) {
            uint32_t b0 = 0, b1 = 0;
#pragma unroll
            for (int j = 0; j < J; j += 2) { b0 |= word(rec[j]) ^ want; b1 |= word(rec[j + 1]) ^ want; }
            if (!__any_sync(0xffffffffu, (b0 & m0) | (b1 & m1))) break;
            if (++it > SPIN_LIMIT) __trap();
            __nanosleep(ns);
            TK_CNT(7)
            const uint32_t grp = 0xffu << (lane & 24u);
            again<0>(rec, want, m0, m1, grp); again<1>(rec, want, m0, m1, grp); again<2>(rec, want, m0, m1, grp);
        }
        if (cred) st_rlx32(cred, R + 1);
        __syncwarp();
        slot_next(lo, st);
        st = slot_rot(st);
    }
    __device__ __forceinline__ void finish() const { if (cred) st_rlx32(cred, 0u); }
};

#define NPROBE 4
__device__ __forceinline__ uint32_t probe(unsigned char* a, uint32_t zero) {
    *reinterpret_cast<uint4*>(a) = make_uint4(0u, 0u, 0u, 0u);
    *reinterpret_cast<uint4*>(a + 16) = make_uint4(0u, 0u, 0u, 0u);
    uint32_t best = ~0u, v = threadIdx.x, prev = 0;
#pragma unroll
    for (int t = 0; t <= NPROBE + 1; t++) {
        uint32_t now;
        if (t <= NPROBE) asm volatile("atom.relaxed.gpu.global.add.u32 %0, [%1], 1;" : "=r"(v) : "l"(a + (v & zero)) : "memory");
        else asm volatile("red.relaxed.gpu.global.add.u32 [%0], 1;" ::"l"(a + (v & zero)) : "memory");
        asm volatile("mov.u32 %0, %%clock;" : "=r"(now) :: "memory");
        if (t > 1) best = min(best, now - prev);
        prev = now;
    }
    return best;
}
template <bool B> struct BoolC { static constexpr bool value = B; };

__device__ __forceinline__ void stage1(const Params& p, uint32_t sb, const int pos0, int lane, const bool half) {
    typedef H<1> h;
    constexpr int NP = 4;
    static_assert(NPR == NS1 * NP * 32 - NP * 16 && G1 == NP, "tiles");
    const int RT = p.rounds;
    uint32_t ff = *reinterpret_cast<const uint16_t*>(p.ang_freq) * 0x10001u;
    auto pair_of = [&](int r, int pos) {
        const int q = r < RT - 1 ? (r * NB + blockIdx.x) * NPR + pos : (RT - 1) * NB * NPR + blockIdx.x * p.lastn + pos;
        return pos < (r < RT - 1 ? NPR : r == RT - 1 ? p.lastn : 0) && q < p.T2 ? q : -1;
    };
    uint2 vi[NP], vo[NP]; uint32_t va[NP];
    auto load_edge = [&](int r) {
#pragma unroll
        for (int u = 0; u < NP; u++) {
            const int q = max(pair_of(r, pos0 + u * 32), 0);
            vi[u] = ld_in(p.idx_in + q); vo[u] = ld_in(p.idx_out + q); va[u] = ld_in(p.angle + q);
        }
    };
    load_edge(0);
    if (blockIdx.x == 0 && pos0 == 0 && (p.T & 1)) {
        const int t = p.T - 1;
        slow_triplet(p, reinterpret_cast<const uint32_t*>(p.idx_in)[t], reinterpret_cast<const uint32_t*>(p.idx_out)[t],
                     bf16r(cos_bf(hmul_bf2(reinterpret_cast<const uint16_t*>(p.angle)[t], ff) & 0xffffu)));
    }
    ff = __reduce_or_sync(0xffffffffu, ff);
    bar_sync(BAR_S1, (NS1 + 1) * 32);
    uint32_t R = __reduce_or_sync(0xffffffffu, lds32(sb + W_BASE));
    TK_DECL
    auto step = [&](const int r, const int qn, auto edge) {
        constexpr bool EDGE = decltype(edge)::value;
        uint32_t cc[NP], big = 0;
#pragma unroll
        for (int u = 0; u < NP; u++) {
            va[u] = hmul_bf2(va[u], ff);
            cc[u] = pack_bf2(__cosf(bf_lo(va[u])), __cosf(bf_hi(va[u])));
            big = __vmaxu2(big, va[u] & 0x7fff7fffu);
        }
        if (RARE((big + (0x7fffu - BIGX) * 0x10001u) & 0x80008000u)) {
#pragma unroll 1
            for (int u = 0; u < NP; u++) {
                const uint32_t a = pick(u, va);
                float c0 = cos_bf(a & 0xffffu), c1 = cos_bf(a >> 16);
                if ((c0 != c0 || c1 != c1) && (EDGE ? pair_of(r, pos0 + u * 32) >= 0 : !half || u < 2)) {
                    const uint2 i2 = pick(u, vi), o2 = pick(u, vo);
                    if (c0 != c0) slow_triplet(p, i2.x, o2.x, c0);
                    if (c1 != c1) slow_triplet(p, i2.y, o2.y, c1);
                }
                const uint32_t v = pack_bf2(c0 != c0 ? 0.f : c0, c1 != c1 ? 0.f : c1);
#pragma unroll
                for (int k = 0; k < NP; k++) if (k == u) cc[k] = v;
            }
        }
        uint32_t bin[2 * NP], x[2 * NP], y[2 * NP];
        uint32_t dep = 0;
        auto loads = [&]() {
            const int q = qn + (dep & p.zero);
#pragma unroll
            for (int u = 0; u < NP; u += 2) {
                const int k = !u ? q : TEXIN ? q + (half ? 0x40000000 : 32) : half ? 0 : q + 32;
                if (TEXIN) { tex2(p.ta, k, va[u], va[u + 1]); tex4(p.to, k, vo[u], vo[u + 1]); tex4(p.ti, k, vi[u], vi[u + 1]); }
                else {
                    const uint2 v = ld_in(reinterpret_cast<const uint2*>(p.angle) + k); va[u] = v.x; va[u + 1] = v.y;
                    ld_in4(p.idx_out + 2 * k, vo[u], vo[u + 1]); ld_in4(p.idx_in + 2 * k, vi[u], vi[u + 1]);
                }
            }
        };
#pragma unroll
        for (int j = 0; j < 2 * NP; j++) {
            const uint32_t ii = j & 1 ? vi[j >> 1].y : vi[j >> 1].x, oo = j & 1 ? vo[j >> 1].y : vo[j >> 1].x;
            bin[j] = __umulhi(ii, p.mg1);
            y[j] = __byte_perm(bin[j] * p.k1 + ii, cc[j >> 1], j & 1 ? 0x7610 : 0x5410);
            const uint32_t bo = __umulhi(oo, p.mg2);
            x[j] = __byte_perm(bo * p.k2 + oo * 8u, bo, 0x0514);
            dep |= x[j] | y[j];
            if (EDGE && pair_of(r, pos0 + (j >> 1) * 32) < 0) bin[j] = NG + (lane & (NDUM - 1));
        }
        if (EDGE) load_edge(r + 1);
        else loads();
        const uint32_t init = h::init(R), kb = sb + h::win(R + 1), lim = init + ((EDGE && r == RT - 1 ? h::S : h::CAP) << h::SH);
        TKS(0)
        mbar_wait(sb + B_OPEN, ~R & 1);
        TKS(1)
        bool freed = false;
        uint32_t over = 0;
#pragma unroll
        for (int g = 0; g < 2 * NP; g += G1) if (!g || EDGE || !half) {
            constexpr int G = G1;
            uint32_t ret[G];
            int mx = 0;
#pragma unroll
            for (int j = 0; j < G; j++) if (g + j < 2 * NP) ret[j] = atoms_add<h::CNT>(sb + bin[g + j] * 4, h::INC);
#pragma unroll
            for (int j = 0; j < G; j++) if (g + j < 2 * NP) mx = j ? max(mx, (int)ret[j]) : (int)ret[j];
            if (!freed && __any_sync(0xffffffffu, mx >= (int)(init + 0x10000u))) { TKS(2) mbar_wait(sb + B_FREE, ~R & 1); freed = true; TKS(3) }
            TKS(2)
#pragma unroll
            for (int j = 0; j < G; j++) if (g + j < 2 * NP) {
                x[g + j] = and_or<h::TAG>(ret[j], x[g + j]);
                put_rec<h::STG>(ret[j], lim, and_xor(ret[j], 0x20000u | h::PM, bin[g + j] * 256 + kb), x[g + j], y[g + j]);
            }
            if (RARE(mx >= (int)lim)) {
#pragma unroll
                for (int j = 0; j < G; j++) if (g + j < 2 * NP && (int)ret[j] >= (int)lim) over |= 1u << (g + j);
            }
        }
        __syncwarp();
        if (elect()) mbar_arrive(sb + B_FULL);
        R++;
        TKS(4)
#pragma unroll 1
        while (RARE(over)) {
            TK_CNT(7)
            const int j = __ffs(over) - 1;
            over &= over - 1;
            slow_rec1(p, pick(j, x), pick(j, y), pick(j, bin));
        }
        __syncwarp();
    };
#pragma unroll 1
    for (int q = opaque(((NB + blockIdx.x) * NPR + pos0 + lane) >> 1), r = 1; r < p.full; r++, q += NB * NPR / 2) step(r - 1, q, BoolC<false>());
#pragma unroll 1
    for (int r = max(p.full - 1, 0); r < RT; r++) step(r, 0, BoolC<true>());
    TK_OUT
}

__device__ __forceinline__ void stage2(const Params& p, uint32_t sb, int w, int lane, int role, uint32_t base) {
    typedef H<2> h;
    const int RT = p.rounds;
    Reader<1> rd;
    rd.init(p, sb, w, lane, role, base);
    uint2 rec[J];
    rd.load(rec);
    bar_sync(BAR_TABLE, 2 * NC * 32);
    uint32_t kb = sb + 0x10000u, am = 0x10000u | h::PM;
    const float unit = __uint_as_float(__reduce_or_sync(0xffffffffu, lds32(sb + W_UNIT)));
    TK_DECL
#pragma unroll 1
    for (int r = 0; r < RT; r++) {
        rd.check(rec, base + r, POLL_NS, lane TK_PASS);
        const uint32_t want = H<1>::tag(base + r);
        TKS(0)
        uint2 mv[J];
#pragma unroll
        for (int j = 0; j < J; j++) mv[j] = lds64<OFF_M>(sb + (rec[j].y & 0xffffu) * 8);
        uint32_t fl = 0;
#pragma unroll
        for (int j = 0; j < J; j++) fl |= mv[j].y;
        if (RARE(fl & 0x40000000u)) {
#pragma unroll 1
            for (int j = 0; j < J; j++) {
                const uint2 v = pick(j, mv), w = pick(j, rec);
                if ((v.y & 0x40000000u) && !((w.x ^ want) & 0xf00000u)) {
                    if (v.x & 0x40000000u) slow_rec1(p, w.x, w.y, lds32(sb + W_ROLE) % NG);
                    else {
                        const float c = bf_hi(w.y), s = __uint_as_float(lds32(sb + W_UNIT)) * 1024.f;
                        side_add(w.x & 0xffu, __byte_perm(w.x, 0u, 0x4413) >> 3, c * (bf_lo(v.x) * s), c * (bf_hi(v.x) * s),
                                 c * (bf_lo(v.y) * s), c * (bf_hi(v.y & 0xbfffffffu) * s));
                    }
                }
            }
#pragma unroll
            for (int j = 0; j < J; j++) if (mv[j].y & 0x40000000u) rec[j].x = 0x800000u;
        }
        uint32_t w0[J], w1[J], bin[J], ret[J];
#pragma unroll
        for (int j = 0; j < J; j++) {
            const float c = bf_hi(rec[j].y), MG = 8194.0f;
            const uint32_t x = rec[j].x;
            w0[j] = and_or<0xf000f000u>(x, __byte_perm(__float_as_uint(fmaf(c, bf_lo(mv[j].x), MG)), __float_as_uint(fmaf(c, bf_hi(mv[j].x), MG)), 0x5410));
            w1[j] = and_or<0xf000f000u>(x << 4, __byte_perm(__float_as_uint(fmaf(c, bf_lo(mv[j].y), MG)), __float_as_uint(fmaf(c, bf_hi(mv[j].y), MG)), 0x5410));
            bin[j] = min(xor_and<0xf000ffu>(x, want), NB + (lane & (NDUM - 1)));
        }
        const uint32_t lim = h::init(base + r) + (r == RT - 1 ? 0x10000u : 0x20000u);
        rd.load(rec);
        TKS(1)
        mbar_wait(sb + B_OPEN + 8, (r - 1) & 1);
        TKS(2)
#pragma unroll
        for (int j = 0; j < J; j++) ret[j] = atoms_add<h::CNT>(sb + bin[j] * 4, h::INC);
        uint32_t mx = 0;
#pragma unroll
        for (int j = 0; j < J; j++) {
            w1[j] = and_or<h::TAG>(ret[j], w1[j]);
            put_rec<0>(ret[j], lim, and_xor(ret[j], am, bin[j] * 128 + kb), w0[j], w1[j]);
            mx = __viaddmax_u32(ret[j], 0u - DUMMY, mx);
        }
        __syncwarp();
        if (lane == 0) mbar_arrive(sb + B_FULL + 8);
        TKS(3)
        if (RARE(mx >= lim - DUMMY)) {
            uint32_t over = 0;
#pragma unroll
            for (int j = 0; j < J; j++) if (ret[j] - DUMMY >= lim - DUMMY) over |= 1u << j;
#pragma unroll 1
            do {
                const int j = __ffs(over) - 1;
                over &= over - 1;
                const uint32_t b = pick(j, bin), v = pick(j, ret) - lim, e = v >> h::SH, at = ((v - e * h::INC - (b & 7u) * 16u - h::CAP * 8) >> 7) + e;
                if (XB != 1 && XB != 2 && max(at, e) < BOXN && r < RT - LATE) g_box[(b * NB + role) * BOX + at] = make_uint2(pick(j, w0), pick(j, w1) | h::TAG);
                else slow_rec2(p, pick(j, w0), pick(j, w1), b, unit);
            } while (over);
        }
        __syncwarp();
        am = am >= 0x30000u ? 0x10000u | h::PM : am + 0x10000u;
        kb ^= am & 0x30000u;
        TKS(4)
    }
    rd.finish();
    TK_OUT
}

__device__ __forceinline__ void add_recs(uint32_t sb, int lane, const uint2 (&rec)[J], uint32_t want) {
    const uint32_t t = 0u - (lane & 1u), k = (t & 1u << 26) - (want >> 4);
    uint32_t o0[J], o1[J], g = 0;
#pragma unroll
    for (int j = 0; j < J; j++) {
        o0[j] = 0; o1[j] = 0;
        if (!xor_and<H<2>::TAG>(rec[j].y, want)) {
            const uint32_t a = aux_of(rec[j].x, rec[j].y, k);
            const uint32_t v0 = (rec[j].x & 0x0fff0fffu) - 0x08000800u, v1 = (rec[j].y & 0x0fff0fffu) - 0x08000800u;
            o0[j] = atoms_add<OFF_ACC>(sb + a, mux(v0, v1, t));
            o1[j] = atoms_add<OFF_ACC>(sb + (a ^ 4u), mux(v1, v0, t));
        }
    }
#pragma unroll
    for (int j = 0; j < J; j++) g |= o0[j] | o1[j];
    if (RARE(__any_sync(0xffffffffu, g & 0x80008000u))) {
#pragma unroll 1
        for (int j = 0; j < J; j++) {
            const uint2 w = pick(j, rec);
            const uint32_t aux = aux_of(w.x, w.y), p0 = pick(j, o0), p1 = pick(j, o1);
            const float2 a = acc_fix(t ? p1 : p0, w.x & 0x0fff0fffu), b = acc_fix(t ? p0 : p1, w.y & 0x0fff0fffu);
            const float unit = __uint_as_float(lds32(sb + W_UNIT));
            if (!((w.y ^ want) & H<2>::TAG) && (a.x != 0.f || a.y != 0.f || b.x != 0.f || b.y != 0.f)) {
                side_add(lds32(sb + W_ROLE), aux >> 3, a.x * unit, a.y * unit, b.x * unit, b.y * unit);
                sts32(sb + W_WRAP, 1u);
            }
            __syncwarp();
        }
    }
}
__device__ __forceinline__ void stage3(const Params& p, uint32_t sb, int w, int lane, int role, uint32_t base) {
    const int RT = p.rounds;
    Reader<2> rd;
    rd.init(p, sb, w, lane, role, base);
    uint2 rec[J];
    bar_sync(BAR_TABLE, 2 * NC * 32);
    TK_DECL
#pragma unroll 1
    for (int r = 0; r < RT; r++) {
        rd.load(rec);
        rd.check(rec, base + r, r < RT - 2 ? POLL_NS3 : 100, lane TK_PASS);
        RTS((r & 127) == 40 && w == 0, 1 + (r >> 7))
        TK(0)
        add_recs(sb, lane, rec, H<2>::tag(base + r));
        TK(1)
        if (RARE((uint32_t)(r - (RT - LATE + 1)) < 2u)) {
            static_assert(BOX == 32, "box");
            float4* box = reinterpret_cast<float4*>(g_box) + (lds32(sb + W_ROLE) * NB + (w * 2 + r - (RT - LATE + 1)) * J) * (BOX / 2) + lane;
            TKY(0)
#pragma unroll
            for (int j = 0; j < J / 2; j++) {
                const float4 v = ld_rlx128f(box + j * 32);
                rec[2 * j] = make_uint2(__float_as_uint(v.x), __float_as_uint(v.y)); rec[2 * j + 1] = make_uint2(__float_as_uint(v.z), __float_as_uint(v.w));
            }
#pragma unroll
            for (int j = 0; j < J / 2; j++) if (rec[2 * j].x) box[j * 32] = make_float4(0.f, 0.f, 0.f, 0.f);
            add_recs(sb, lane, rec, H<2>::TAG);
            TKY(1)
        }
    }
    rd.finish();
    TK_OUT
}

__device__ __forceinline__ uint32_t row_max(uint32_t x, uint32_t y) {
    const uint32_t mx = __vmaxu2(x & 0x7fff7fffu, y & 0x7fff7fffu);
    return max(mx & 0xffffu, mx >> 16);
}
constexpr int NTAB = 3, TABC = 3 * 2 * NC * 32 * 16;
static_assert(NTAB * TABC >= R1MAX * 8, "table");
constexpr int EWIN = 5;

__global__ void __launch_bounds__(NTHR, 1) fused_kernel(const Params p) {
    const int tid = threadIdx.x, lane = tid & 31;
    const int hw = __reduce_max_sync(0xffffffffu, tid >> 5);
    const uint32_t sb = __reduce_or_sync(0xffffffffu, (uint32_t)__cvta_generic_to_shared(smem));
    TKX(0)
    RTS(tid == 0, 0)
    uint32_t cta;
    asm volatile("mov.u32 %0, %%ctaid.x;" : "=r"(cta));
    if (hw != W_M1 && hw != W_M2) {
        const int job = hw < W_M1 ? hw : hw - 1;
        if (lane == 0 && job < 2 * NPAGE + 2)
            sts32(sb + OFF_PROBE + job * 4, probe(p.ring + (size_t)max(job / 2 - 1, 0) * PAGE + PROBE + (cta & 31) * 128 + (cta >> 5 & 3) * 16384 + (cta >> 7 << 20) +
                                                  ((job & 1) << 12 ^ (job < 2 ? 0x3000 : 0)), p.zero));
        if (job < 4) bar_arrive(BAR_SIDE, 5 * 32); else bar_arrive(BAR_PROBE, 27 * 32);
        TKX(1)
    }
    if (hw < NS1) {
        stage1(p, sb, hw * 128 + lane, lane, hw == NS1 - 1);
    } else if (hw == W_M1) {
        const uint32_t epoch = ld_rlx32(&g_base);
        if (lane == 0) {
            if (sb & 255u) __trap();
            mbar_init(sb + B_FULL, NS1); mbar_init(sb + B_OPEN, 1); mbar_init(sb + B_FREE, 1);
            for (int i = 0; i < NTAB; i++) mbar_init(sb + B_TAB + i * 8, 1);
            asm volatile("fence.proxy.async.shared::cta;" ::: "memory");
        }
        const uint32_t base = __reduce_or_sync(0xffffffffu, epoch) & 31u;
        if (lane == 0) { sts32(sb + W_BASE, base); sts64(sb + W_NLIST, 0u, 0u); }
        if (lane == 0 && (base & 1u)) { mbar_arrive(sb + B_OPEN); mbar_arrive(sb + B_FREE); }
        for (int i = lane; i < NG + NDUM; i += 32) sts32(sb + OFF_CNT1 + i * 4, i < NG ? H<1>::init(base) + (i & 7) * 16 : DUMMY);
#pragma unroll 1
        for (int i = 0; i < 2; i++) fill<1>(sb + OFF_H1 + H<1>::win(base + i), lane, base + i);
        bar_arrive(BAR_S1, (NS1 + 1) * 32);
        bar_sync(BAR_SIDE, 5 * 32);
        {
            const uint2 la = lds64<OFF_PROBE>(sb), lb = lds64<OFF_PROBE + 8>(sb);
            const uint32_t side = min(la.y, lb.y) < min(la.x, lb.x);
            uint32_t v = 0;
            if (lane < 2) asm volatile("atom.relaxed.gpu.global.add.u32 %0, [%1], %2;" : "=r"(v) : "l"(p.ring + M_CNT + lane * 4096), "r"(side ? 0x10000u : 1u) : "memory");
            if (lane == 0) {
                const uint32_t role = side ? NB - 1 - (v >> 16) : v & 0xffffu;
                const int r0 = (role >= NG ? role - NG : role) * p.R1, nb = min(p.R1, p.E - r0) * 8;
#pragma unroll
                for (int i = 0; i < NTAB; i++) {
                    const int n = max(min(nb - i * TABC, TABC), 0);
                    asm volatile("mbarrier.arrive.expect_tx.shared::cta.b64 _, [%0], %1;" ::"r"(sb + B_TAB + i * 8), "r"(n) : "memory");
                    if (n) asm volatile("cp.async.bulk.shared::cluster.global.mbarrier::complete_tx::bytes [%0], [%1], %2, [%3];"
                                        ::"r"(sb + OFF_M + i * TABC), "l"(p.m + r0 + i * (TABC / 8)), "r"(n), "r"(sb + B_TAB + i * 8) : "memory");
                }
                sts32(sb + W_ROLE, role); sts32(sb + W_SIDE, role < NLO ? 0u : role >= NHI ? 1u : side);
                sts32(sb + W_END, (epoch | 31u) + 1u + (base + p.rounds) % 24u);
            }
            TKX(2)
            bar_sync(BAR_PROBE, 27 * 32);
            const uint2 l = lds64<OFF_PROBE + 8>(sb + min(lane, NPAGE - 1) * 8);
            const uint32_t mine = (__ballot_sync(0xffffffffu, (l.y < l.x) != side) & ~1u) | 0x80000000u;
            if (lane == 0) {
                asm volatile("atom.relaxed.gpu.global.cas.b32 %0, [%1], 0, %2;" : "=r"(v) : "l"(p.ring + M_PAR), "r"(mine) : "memory");
                sts32(sb + W_PAR, v ? v : mine);
            }
        }
        bar_arrive(BAR_PAR, (2 * NC + 2) * 32);
        manager<1>(p, sb, opaque(lane), __reduce_max_sync(0xffffffffu, lds32(sb + W_ROLE)), base);
        asm volatile("cp.async.bulk.wait_group 0;" ::: "memory");
        bar_arrive(BAR_H1, (NS1 + 1) * 32);
        TKX(4)
        {
            const int role = lds32(sb + W_ROLE);
#pragma unroll 1
            for (int i = lane * 16; i < DROW; i += 4 * 512) {
                float4 f[4];
#pragma unroll
                for (int u = 0; u < 4; u++) f[u] = ld_rlx128f(reinterpret_cast<const float4*>(g_dirty + role * DROW + i + u * 512));
#pragma unroll
                for (int u = 0; u < 4; u++) {
                    if (__float_as_uint(f[u].x) | __float_as_uint(f[u].y)) prefetch_l2(g_ovf + role * RPAD + i + u * 512);
                    if (__float_as_uint(f[u].z) | __float_as_uint(f[u].w)) prefetch_l2(g_ovf + role * RPAD + i + u * 512 + 8);
                }
            }
        }
        bar_sync(BAR_DONE, (NE + 1) * 32);
        TKY(0)
        if (lane < 2) { fence_gpu(); st_rlx32(reinterpret_cast<uint32_t*>(p.ring + M_FLAG + lane * 4096) + blockIdx.x, lds32(sb + W_END)); }
        TKY(1)
        wait_flags(p, sb, lane, lds32(sb + W_END));
        TKX(5)
        bar_arrive(BAR_FLAG, (NE + 1) * 32);
        if (blockIdx.x == 0) {
            if (lane == 0) g_base = lds32(sb + W_END);
            if (lane < 3) *reinterpret_cast<uint32_t*>(p.ring + (lane & 2 ? M_PAR : M_CNT + (lane & 1) * 4096)) = 0;
        }
    } else if (hw == W_M2) {
        const uint32_t epoch = ld_rlx32(&g_base);
        uint2 sm[16];
#pragma unroll
        for (int i = 0; i < 8; i++) ld_in4(p.m + 2 * min((i * 8 + (lane >> 2)) * (p.E >> 7) + (lane & 3), (p.E >> 1) - 1), sm[2 * i], sm[2 * i + 1]);
        const float wd = __bfloat162float(lane & 16 ? p.w_up[lane & 15] : p.w_down[lane & 15]);
        if (lane == 0) { mbar_init(sb + B_FULL + 8, NC); mbar_init(sb + B_OPEN + 8, 1); }
        sts128<OFF_HIST>(sb + lane * 16, make_uint4(0u, 0u, 0u, 0u)); sts128<OFF_HIST + 512>(sb + lane * 16, make_uint4(0u, 0u, 0u, 0u));
        __syncwarp();
#pragma unroll
        for (int i = 0; i < 16; i++) atoms_add<OFF_HIST>(sb + (row_max(sm[i].x, sm[i].y) >> 7) * 4, 1u);
        __syncwarp();
        uint32_t best = 0;
#pragma unroll 1
        for (int e = 11 + lane; e <= 230; e += 32) {
            uint32_t c = 0;
#pragma unroll
            for (int i = 0; i < EWIN; i++) c += lds32(sb + OFF_HIST + (e - i) * 4);
            best = max(best, c << 8 | (255 - e));
        }
        const uint32_t e = 255 - (__reduce_max_sync(0xffffffffu, best) & 255u);
        if (lane == 0) { sts32(sb + W_EXP, e); sts32(sb + W_UNIT, (e - 10) << 23); }
        const uint32_t base = __reduce_or_sync(0xffffffffu, epoch) & 31u;
        for (int i = lane; i <= NB + NDUM; i += 32) sts32(sb + OFF_CNT2 + i * 4, i < NB ? H<2>::init(base) + (i & 7) * 16 : DUMMY);
#pragma unroll 1
        for (int i = 0; i < 3; i++) fill<2>(sb + H<2>::win(i), lane, base + i);
        reinterpret_cast<float*>(smem + OFF_WSM)[lane] = wd;
        bar_sync(BAR_PAR, (2 * NC + 2) * 32);
        manager<2>(p, sb, opaque(lane), __reduce_max_sync(0xffffffffu, lds32(sb + W_ROLE)), base);
        TKX(4)
        asm volatile("cp.async.bulk.wait_group 0;" ::: "memory");
    } else {
        const int pw = __reduce_max_sync(0xffffffffu, hw < W_M1 ? hw - NS1 : hw - NS1 - 1), ct = pw * 32 + lane;
        constexpr int CT = 2 * NC * 32;
        bar_sync(BAR_PAR, (2 * NC + 2) * 32);
        TKY(4)
        for (int i = ct; i < R2MAX / 2; i += CT) reinterpret_cast<uint4*>(smem + OFF_ACC)[i] = make_uint4(0x40004000u, 0x40004000u, 0x40004000u, 0x40004000u);
        const int role = __reduce_max_sync(0xffffffffu, lds32(sb + W_ROLE));
        {
            const int e = lds32(sb + W_EXP);
            const uint32_t sc = (uint32_t)(254 - e) * 0x800080u;
            auto conv = [&](uint32_t& x, uint32_t& y) {
                const uint32_t mx = row_max(x, y);
                const int d = e - (int)(mx >> 7);
                x = hmul_bf2(x, sc); y = hmul_bf2(y, sc);
                if (d >= EWIN) y |= 0x40000000u;
                if (d < 0 || (d >= EWIN && e > 127)) { x = 0x40000000u; y = x; }
                if (mx == 0) { x = 0; y = 0; }
            };
#pragma unroll 1
            for (int i = 0; i < NTAB; i++) {
                mbar_wait(sb + B_TAB + i * 8, 0);
                uint4* t = reinterpret_cast<uint4*>(smem + OFF_M + i * TABC) + ct;
#pragma unroll
                for (int u = 0; u < TABC / 16 / CT; u++) if (i * TABC + (ct + u * CT) * 16 < R1MAX * 8) {
                    uint4 v = t[u * CT];
                    conv(v.x, v.y); conv(v.z, v.w);
                    t[u * CT] = v;
                }
            }
        }
        TKX(3)
        const uint32_t base = __reduce_or_sync(0xffffffffu, lds32(sb + W_BASE));
        if (hw < W_M1) {
            stage2(p, sb, pw, opaque(lane), role, base);
        } else {
            stage3(p, sb, pw - NC, opaque(lane), role, base);
            TKX(4)
            bar_arrive(BAR_ACC, (NE + NC) * 32);
        }
    }
    if (hw < W_M1) {
        bar_arrive(BAR_DONE, (NE + 1) * 32);
        TKX(4)
        finish_rows(p, sb);
    }
}

__global__ void fb_scatter(const uint2* __restrict__ m, const int* __restrict__ idx_in, const int* __restrict__ idx_out,
                           const uint16_t* __restrict__ angle, const __nv_bfloat16* __restrict__ ang_freq, int T, int e0, int e1) {
    const uint32_t fb = *reinterpret_cast<const uint16_t*>(ang_freq);
    for (long long t = blockIdx.x * (long long)blockDim.x + threadIdx.x; t < T; t += (long long)gridDim.x * blockDim.x) {
        int o = idx_out[t];
        if (o < e0 || o >= e1) continue;
        float c = bf16r(cos_bf(hmul_bf2(angle[t], fb) & 0xffffu));
        uint2 v = __ldg(m + idx_in[t]);
        red4(&g_ovf[o - e0], c * bf_lo(v.x), c * bf_hi(v.x), c * bf_lo(v.y), c * bf_hi(v.y));
    }
}
__global__ void fb_final(const Params p, int e0, int e1) {
    int e = e0 + blockIdx.x * blockDim.x + threadIdx.x;
    if (e >= e1) return;
    float4 a4 = g_ovf[e - e0];
    g_ovf[e - e0] = make_float4(0.f, 0.f, 0.f, 0.f);
    float a[4] = {a4.x, a4.y, a4.z, a4.w};
    float d = __bfloat162float(p.dist[e]);
    float g[4] = {0, 0, 0, 0}, h[4] = {0, 0, 0, 0};
    for (int r = 0; r < 8; r++) {
        float df = bf16r(d - __bfloat162float(p.centers[r]));
        float rb = bf16r(expf(bf16r(-10.0f * bf16r(df * df))));
        for (int k = 0; k < 4; k++) {
            g[k] += rb * __bfloat162float(p.w_sbf[r * 4 + k]);
            h[k] += rb * __bfloat162float(p.w_rbf[r * 4 + k]);
        }
    }
    float ag[4];
    for (int k = 0; k < 4; k++) {
        float s = 0.f;
        for (int j = 0; j < 4; j++) s += a[j] * __bfloat162float(p.w_down[j * 4 + k]);
        ag[k] = bf16r(s * g[k]);
    }
    uint2 mv = p.m[e];
    float mm[4] = {bf_lo(mv.x), bf_hi(mv.x), bf_lo(mv.y), bf_hi(mv.y)};
    __nv_bfloat16 o[4];
    for (int k = 0; k < 4; k++) {
        float u = 0.f;
        for (int j = 0; j < 4; j++) u += ag[j] * __bfloat162float(p.w_up[j * 4 + k]);
        o[k] = __float2bfloat16_rn(mm[k] + bf16r(bf16r(u) * bf16r(h[k])));
    }
    p.out[e] = *reinterpret_cast<uint2*>(o);
}

}

static bool exact_div(int E, int lo, int hi, int* R, uint32_t* magic) {
    for (int r = lo + (lo & 1); r <= hi; r += 2) {
        unsigned long long mg = ((1ull << 32) + r - 1) / r, err = mg * r - (1ull << 32);
        if (err * (unsigned long long)E < (1ull << 32)) { *R = r; *magic = (uint32_t)mg; return true; }
    }
    return false;
}

static cudaTextureObject_t make_tex(const void* ptr, size_t bytes, int words) {
    cudaResourceDesc rd = {}; cudaTextureDesc td = {};
    rd.resType = cudaResourceTypeLinear; rd.res.linear.devPtr = const_cast<void*>(ptr); rd.res.linear.sizeInBytes = bytes;
    rd.res.linear.desc = cudaCreateChannelDesc(32, words > 1 ? 32 : 0, words > 2 ? 32 : 0, words > 2 ? 32 : 0, cudaChannelFormatKindUnsigned);
    td.readMode = cudaReadModeElementType;
    cudaTextureObject_t t = 0;
    if (cudaCreateTextureObject(&t, &rd, &td, nullptr) != cudaSuccess) { t = 0; (void)cudaGetLastError(); }
    return t;
}

extern "C" void kernel_launch(void* const* d_in, const int* in_sizes, int n_in, void* d_out, int out_size) {
    typedef const __nv_bfloat16* B;
    Params p;
    p.m = (const uint2*)d_in[0]; p.idx_in = (const uint2*)d_in[1]; p.idx_out = (const uint2*)d_in[2]; p.dist = (B)d_in[3];
    p.angle = (const uint32_t*)d_in[4]; p.centers = (B)d_in[5]; p.ang_freq = (B)d_in[6]; p.w_rbf = (B)d_in[7]; p.w_sbf = (B)d_in[8];
    p.w_down = (B)d_in[9]; p.w_up = (B)d_in[10]; p.out = (uint2*)d_out;
    p.E = in_sizes[3]; p.T = in_sizes[1]; p.T2 = p.T >> 1; p.zero = 0;
    p.R1 = p.R2 = p.rounds = p.lastn = p.full = 0; p.mg1 = p.mg2 = p.k1 = p.k2 = 0;
    static int ok = -1;
    static unsigned char* ring = nullptr;
    if (ok < 0) {
        void* ra = nullptr;
        cudaGetSymbolAddress(&ra, g_ring);
        ring = reinterpret_cast<unsigned char*>(((uintptr_t)ra + PAGE - 1) & ~(uintptr_t)(PAGE - 1));
        int dev = 0, sms = 0, occ = 0;
        cudaGetDevice(&dev);
        cudaDeviceGetAttribute(&sms, cudaDevAttrMultiProcessorCount, dev);
        cudaError_t e = cudaFuncSetAttribute(fused_kernel, cudaFuncAttributeMaxDynamicSharedMemorySize, SMEM_BYTES);
        if (e == cudaSuccess) e = cudaOccupancyMaxActiveBlocksPerMultiprocessor(&occ, fused_kernel, NTHR, SMEM_BYTES);
        ok = (e == cudaSuccess && occ >= 1 && sms >= NB) ? 1 : 0;
        (void)cudaGetLastError();
    }
    p.ring = ring;
    static cudaTextureObject_t tx[3];
    if (!tx[0]) { tx[0] = make_tex(p.idx_in, (size_t)(p.T >> 2) * 16, 4); tx[1] = make_tex(p.idx_out, (size_t)(p.T >> 2) * 16, 4); tx[2] = make_tex(p.angle, (size_t)(p.T >> 2) * 8, 2); }
    p.ti = tx[0]; p.to = tx[1]; p.ta = tx[2];
    const bool fused = ok == 1 && p.E <= EMAX && p.E >= 2 * NB && p.E % 2 == 0 && p.T >= 2 && exact_div(p.E, (p.E + NG - 1) / NG, R1MAX, &p.R1, &p.mg1) &&
                       exact_div(p.E, (p.E + NB - 1) / NB, R2MAX, &p.R2, &p.mg2);
    if (fused) {
        p.k1 = 0u - (uint32_t)p.R1; p.k2 = 0u - 8u * (uint32_t)p.R2;
        const int per = NB * NPR;
        int full = p.T2 / per, rest = p.T2 - full * per;
        p.full = full;
        p.lastn = (rest + NB - 1) / NB;
        if (p.lastn > NPR / 2) { full++; p.lastn = 0; }
        if (full < D) { full = D; p.lastn = 0; }
        p.rounds = full + 1;
        fused_kernel<<<NB, NTHR, SMEM_BYTES>>>(p);
    } else {
        for (int e0 = 0; e0 < p.E; e0 += EMAX) {
            int e1 = p.E - e0 < EMAX ? p.E : e0 + EMAX;
            fb_scatter<<<1056, 256>>>(p.m, (const int*)d_in[1], (const int*)d_in[2], (const uint16_t*)d_in[4], p.ang_freq, p.T, e0, e1);
            fb_final<<<(e1 - e0 + 255) / 256, 256>>>(p, e0, e1);
        }
    }
}
```

```cpp
#include <cuda_runtime.h>
#include <cuda_bf16.h>
#include <stdint.h>
#include <math.h>

#define RARE(x) __builtin_expect(!!(x), 0)
namespace {

constexpr int NB = 132, NG = 66;
constexpr int R2MAX = 6062, R1MAX = 12124;
constexpr int EMAX = NB * R2MAX;
constexpr int NTHR = 1024;
constexpr int NS1 = 8, NC = 11, J = 6;
#define U1 1
#define U2 1
#define U3 1
#define FI2 1
#define BG 1
#define NS3 1
#define GP 2
#define TEXIN 1
#define G1 4
#define CAP1 64
constexpr int NPR = 960;
constexpr int D = 3;
constexpr int WIN = 16896;
constexpr int NDUM = 16;
constexpr uint32_t DUMMY = 0xc0000000u;

constexpr int OFF_ACC = WIN, OFF_BAR = OFF_ACC + R2MAX * 8;
constexpr int OFF_H1 = 0x10000 + WIN, OFF_M = OFF_H1 + WIN, OFF_WSM = OFF_M + R1MAX * 8;
constexpr int OFF_CNT1 = OFF_H1 + 0x20000 + WIN, OFF_CNT2 = OFF_CNT1 + (NG + NDUM + 2) * 4;
constexpr int OFF_HIST = OFF_ACC;
constexpr int OFF_PROBE = OFF_WSM + 128;
constexpr int SMEM_BYTES = OFF_CNT2 + (NB + NDUM) * 4 + 16;
static_assert(SMEM_BYTES <= 232448 && OFF_BAR + 64 <= 0x10000 && OFF_PROBE + 160 <= 0x30000, "smem");
static_assert(OFF_BAR % 8 == 0 && OFF_WSM % 16 == 0 && OFF_CNT2 % 16 == 0, "align");
static_assert(NC * J == NG && NC * 32 * 6 * 16 == 2 * WIN, "shape");

template <int HOP> struct H {
    static constexpr int S = HOP == 1 ? 32 : 16, NBIN = HOP == 1 ? NG : NB, CAP = HOP == 1 ? CAP1 : 32, SH = HOP == 1 ? 11 : 12;
    static constexpr int TB = HOP == 1 ? 17 : 28, CNT = HOP == 1 ? OFF_CNT1 : OFF_CNT2, STG = HOP == 1 ? OFF_H1 : 0;
    static_assert(CAP <= 2 * S, "two windows");
    static constexpr uint32_t INC = (1u << SH) + 8u, PM = (S - 1) * 8, TAG = 7u << TB;
    static __device__ __forceinline__ uint32_t tag(uint32_t R) { return R << TB & TAG; }
    static __device__ __forceinline__ uint32_t init(uint32_t R) { return tag(R) | ((1u << TB) - 0x10000u); }
    static __device__ __forceinline__ uint32_t mark(uint32_t R, uint32_t line) { return ((HOP == 1 ? R >> 1 : R) + line) & 3u; }
    static __device__ __forceinline__ uint32_t win(int r) { return HOP == 1 ? (r & 1) << 17 : (0x310u >> (r % 3 * 4) & 3u) << 16; }
};

constexpr uint32_t PAGE = 1u << 21;
constexpr int NPAGE = NC + 2;
__device__ __align__(256) unsigned char g_ring[(size_t)(NPAGE + 1) * PAGE];
constexpr int MISC = 0xa0000;
constexpr int M_CNT = MISC + 1024, M_PAR = MISC + 1088;
constexpr int M_FLAG = MISC + 2048;
constexpr int PROBE = MISC + 0x40000;
#define CSTR 16384
__device__ __forceinline__ uint32_t cred_off(uint32_t role) { return role * 4 + min(role >> 5, 3u) * (CSTR - 128); }
struct Ring {
    uint64_t main, mid;
    uint32_t par;
    __device__ __forceinline__ Ring(const unsigned char* ring, uint32_t pars, int k) {
        main = reinterpret_cast<uint64_t>(ring) + ((uint64_t)k << 20);
        par = pars >> (k >> 1) & 1u;
        mid = reinterpret_cast<uint64_t>(ring) + (uint64_t)NC * PAGE + (((k >> 3 << 20) + (k >> 2 & 1) * 0x11000u + (k & 1) * 2048) ^ (k >> 1 & 1) * 0x3000u ^ (pars >> (NC + (k >> 4)) & 1u) << 12);
    }
};
constexpr int NLO = 60, NHI = 72;
__host__ __device__ constexpr uint32_t src_off(int j) { return (j % 3) << 14 | (j / 3) << 18; }
__device__ __forceinline__ uint32_t slot_off(uint32_t s) { return (0xa930u >> s * 4 & 15u) << 16; }
__device__ __forceinline__ uint32_t slot_steps(uint32_t R) { return (uint32_t)(0x30a09030aull >> (2 - R % 3) * 8) & 0xffffffu; }
__device__ __forceinline__ void slot_next(uint32_t& a, uint32_t st) { a ^= st & 0xf0000u; }
__device__ __forceinline__ uint32_t slot_rot(uint32_t st) { return __byte_perm(st, 0u, 0x4102); }
constexpr int RPAD = 6064, DROW = 6144;
__device__ __align__(128) uint8_t g_dirty[NB * DROW];
#define XB 0
constexpr int BOX = 32, BOXN = 24, LATE = 8;
__device__ __align__(128) uint2 g_box[NB * NB * BOX];
__device__ uint32_t g_base = 1;
__device__ __align__(128) float4 g_ovf[NB * RPAD];

struct Params {
    const uint2* m; const uint2* idx_in; const uint2* idx_out; const __nv_bfloat16* dist; const uint32_t* angle;
    const __nv_bfloat16* centers; const __nv_bfloat16* ang_freq; const __nv_bfloat16* w_rbf; const __nv_bfloat16* w_sbf;
    const __nv_bfloat16* w_down; const __nv_bfloat16* w_up; uint2* out; unsigned char* ring;
    cudaTextureObject_t ti, to, ta;
    int E, T, T2, R1, R2, rounds, lastn, full; uint32_t zero; float i1, i2, k1, k2;
};

__device__ __forceinline__ float bf16r(float x) { return __bfloat162float(__float2bfloat16_rn(x)); }
__device__ __forceinline__ float bf_lo(uint32_t v) { return __uint_as_float(v << 16); }
__device__ __forceinline__ float bf_hi(uint32_t v) { return __uint_as_float(v & 0xffff0000u); }
__device__ __forceinline__ void red4(float4* a, float x, float y, float z, float w) {
    asm volatile("red.global.add.v4.f32 [%0], {%1,%2,%3,%4};" ::"l"(a), "f"(x), "f"(y), "f"(z), "f"(w) : "memory");
}
__device__ __forceinline__ void bar_sync(int id, int n) { __syncwarp(); asm volatile("bar.sync %0, %1;" ::"r"(id), "r"(n) : "memory"); }
__device__ __forceinline__ void bar_arrive(int id, int n) { __syncwarp(); asm volatile("bar.arrive %0, %1;" ::"r"(id), "r"(n) : "memory"); }
template <int OFF> __device__ __forceinline__ uint32_t atoms_add(uint32_t addr, uint32_t v) {
    uint32_t r; asm volatile("atom.shared.add.u32 %0, [%1+%3], %2;" : "=r"(r) : "r"(addr), "r"(v), "n"(OFF) : "memory"); return r;
}
__device__ __forceinline__ void sts64(uint32_t addr, uint32_t x, uint32_t y) {
    asm volatile("st.shared.v2.u32 [%0], {%1,%2};" ::"r"(addr), "r"(x), "r"(y) : "memory");
}
__device__ __forceinline__ void sts32(uint32_t addr, uint32_t x) { asm volatile("st.shared.u32 [%0], %1;" ::"r"(addr), "r"(x) : "memory"); }
template <int OFF = 0> __device__ __forceinline__ uint2 lds64(uint32_t addr) {
    uint2 v; asm volatile("ld.shared.v2.u32 {%0,%1}, [%2+%3];" : "=r"(v.x), "=r"(v.y) : "r"(addr), "n"(OFF) : "memory"); return v;
}
__device__ __forceinline__ uint32_t lds32(uint32_t addr) {
    uint32_t v; asm volatile("ld.shared.u32 %0, [%1];" : "=r"(v) : "r"(addr) : "memory"); return v;
}
template <int OFF> __device__ __forceinline__ void sts128(uint32_t a, const uint4& v) {
    asm volatile("st.shared.v4.u32 [%0+%5], {%1,%2,%3,%4};" ::"r"(a), "r"(v.x), "r"(v.y), "r"(v.z), "r"(v.w), "n"(OFF) : "memory");
}
__device__ __forceinline__ uint4 lds128(uint32_t a) {
    uint4 v; asm volatile("ld.shared.v4.u32 {%0,%1,%2,%3}, [%4];" : "=r"(v.x), "=r"(v.y), "=r"(v.z), "=r"(v.w) : "r"(a) : "memory"); return v;
}
__device__ __forceinline__ uint32_t ld_rlx32(const uint32_t* p) {
    uint32_t v; asm volatile("ld.relaxed.gpu.global.u32 %0, [%1];" : "=r"(v) : "l"(p) : "memory"); return v;
}
__device__ __forceinline__ uint2 ld_rlx64(const void* p) {
    uint2 v; asm volatile("ld.relaxed.gpu.global.v2.u32 {%0,%1}, [%2];" : "=r"(v.x), "=r"(v.y) : "l"(p) : "memory"); return v;
}
__device__ __forceinline__ float4 ld_rlx128f(const float4* p) {
    float4 v; asm volatile("ld.relaxed.gpu.global.v4.f32 {%0,%1,%2,%3}, [%4];" : "=f"(v.x), "=f"(v.y), "=f"(v.z), "=f"(v.w) : "l"(p) : "memory"); return v;
}
__device__ __forceinline__ float4 take(float4* p, bool q) {
    float4 v;
    asm volatile("{ .reg .b128 a; .reg .b64 x, y; .reg .pred q; mov.b64 x, 0; mov.b128 a, {x, x}; setp.ne.u32 q, %5, 0;\n"
                 "@q atom.relaxed.gpu.global.exch.b128 a, [%4], a; mov.b128 {x, y}, a; mov.b64 {%0,%1}, x; mov.b64 {%2,%3}, y; }"
                 : "=f"(v.x), "=f"(v.y), "=f"(v.z), "=f"(v.w) : "l"(p), "r"((uint32_t)q) : "memory");
    return v;
}
__device__ __forceinline__ void fence_gpu() { asm volatile("fence.acq_rel.gpu;" ::: "memory"); }
__device__ __forceinline__ void st_rlx32(uint32_t* p, uint32_t v) { asm volatile("st.relaxed.gpu.global.u32 [%0], %1;" ::"l"(p), "r"(v) : "memory"); }
__device__ __forceinline__ uint32_t hmul_bf2(uint32_t a, uint32_t b) {
    uint32_t r; asm("mul.rn.bf16x2 %0, %1, %2;" : "=r"(r) : "r"(a), "r"(b)); return r;
}
__device__ __forceinline__ uint32_t hsub_bf2(uint32_t a, uint32_t b) {
    uint32_t r; asm("sub.rn.bf16x2 %0, %1, %2;" : "=r"(r) : "r"(a), "r"(b)); return r;
}
__device__ __forceinline__ uint32_t hadd_bf2(uint32_t a, uint32_t b) {
    uint32_t r; asm("add.rn.bf16x2 %0, %1, %2;" : "=r"(r) : "r"(a), "r"(b)); return r;
}
__device__ __forceinline__ int opaque(int v) { return __shfl_sync(0xffffffffu, v, threadIdx.x); }
constexpr int SPIN_LIMIT = 1 << 22;

__constant__ uint32_t c_inv2pi[8] = {0u, 0x28be60dbu, 0x9391054au, 0x7f09d5f4u, 0x7d4d3770u, 0x36d8a566u, 0x4f10e410u, 0x7f9458eau};
constexpr uint32_t BIGX = 0x4280u;
__device__ __forceinline__ float cos_big(uint32_t xb) {
    uint32_t e = (xb >> 7) & 0xffu, M = (xb & 0x7fu) | 0x80u;
    uint32_t pp = e - 102u;
    uint32_t wi = pp >> 5;
    uint32_t t0 = c_inv2pi[wi], t1 = c_inv2pi[wi + 1], t2 = c_inv2pi[wi + 2];
    uint32_t f = M * __funnelshift_l(t1, t0, pp) + __umulhi(M, __funnelshift_l(t2, t1, pp));
    float c = __cosf((float)(int)f * 1.4629180792671596e-9f);
    return e == 255u ? __uint_as_float(0x7fc00000u) : c;
}
__device__ __forceinline__ float cos_bf(uint32_t xb) {
    return (xb & 0x7fffu) > BIGX ? cos_big(xb) : __cosf(__uint_as_float(xb << 16));
}
__device__ __forceinline__ uint32_t pack_bf2(float lo, float hi) {
    uint32_t r; asm("cvt.rn.bf16x2.f32 %0, %1, %2;" : "=r"(r) : "f"(hi), "f"(lo)); return r;
}
template <int N> __device__ __forceinline__ uint32_t pick(int k, const uint32_t (&a)[N]) {
    uint32_t v = a[0];
#pragma unroll
    for (int i = 1; i < N; i++) if (k == i) v = a[i];
    return v;
}
template <int N> __device__ __forceinline__ uint2 pick(int k, const uint2 (&a)[N]) {
    uint2 v = a[0];
#pragma unroll
    for (int i = 1; i < N; i++) if (k == i) v = a[i];
    return v;
}
__device__ __forceinline__ uint32_t imul(uint32_t a, float s) { uint32_t r; asm("mul.rz.f32 %0, %1, %2;" : "=r"(r) : "r"(a), "f"(s)); return r; }
__device__ __forceinline__ uint32_t ifma(uint32_t a, float s, uint32_t c) { uint32_t r; asm("fma.rn.f32 %0, %1, %2, %3;" : "=r"(r) : "r"(a), "f"(s), "r"(c)); return r; }
__device__ __forceinline__ void side_add(uint32_t bin, uint32_t row, float a, float b, float c, float d) {
    red4(&g_ovf[bin * RPAD + row], a, b, c, d);
    g_dirty[bin * DROW + row] = 1;
}
__device__ __forceinline__ void slow_triplet(const Params& p, uint32_t ii, uint32_t oo, float c) {
    const uint2 v = __ldg(p.m + ii);
    const uint32_t bo = imul(oo, p.i2);
    side_add(bo, oo - bo * p.R2, c * bf_lo(v.x), c * bf_hi(v.x), c * bf_lo(v.y), c * bf_hi(v.y));
}
__device__ __forceinline__ void slow_rec1(const Params& p, uint32_t x, uint32_t y, uint32_t bin) {
    const uint2 v = __ldg(p.m + bin * p.R1 + (y & 0xffffu));
    const float c = bf_hi(y);
    side_add(x & 0xffu, __byte_perm(x, 0u, 0x4413) >> 3, c * bf_lo(v.x), c * bf_hi(v.x), c * bf_lo(v.y), c * bf_hi(v.y));
}
__device__ __forceinline__ uint32_t aux_of(uint32_t w0, uint32_t w1, uint32_t k = 0) {
    uint32_t u; asm("lop3.b32 %0, %1, %2, 0xf000f000, 0xe4;" : "=r"(u) : "r"(w0), "r"((w1 >> 4) + k));
    return __byte_perm(u, 0u, 0x4413);
}
__device__ __forceinline__ void slow_rec2(const Params& p, uint32_t w0, uint32_t w1, uint32_t bin, float unit) {
    side_add(bin, aux_of(w0, w1) >> 3, (float)((int)(w0 & 0xfffu) - 2048) * unit, (float)((int)(w0 >> 16 & 0xfffu) - 2048) * unit,
             (float)((int)(w1 & 0xfffu) - 2048) * unit, (float)((int)(w1 >> 16 & 0xfffu) - 2048) * unit);
}
template <uint32_t M> __device__ __forceinline__ uint32_t and_or(uint32_t a, uint32_t c) {
    uint32_t r; asm("lop3.b32 %0, %1, %2, %3, 0xea;" : "=r"(r) : "r"(a), "n"(M), "r"(c)); return r;
}
template <uint32_t M> __device__ __forceinline__ uint32_t xor_and(uint32_t a, uint32_t c) {
    uint32_t r; asm("lop3.b32 %0, %1, %2, %3, 0x48;" : "=r"(r) : "r"(a), "n"(M), "r"(c)); return r;
}
__device__ __forceinline__ uint32_t mux(uint32_t a, uint32_t b, uint32_t m) {
    uint32_t r; asm("lop3.b32 %0, %1, %2, %3, 0xd8;" : "=r"(r) : "r"(a), "r"(b), "r"(m)); return r;
}
__device__ __forceinline__ uint32_t and_xor(uint32_t a, uint32_t m, uint32_t c) {
    uint32_t r; asm("lop3.b32 %0, %1, %2, %3, 0x6a;" : "=r"(r) : "r"(a), "r"(m), "r"(c)); return r;
}
__device__ __forceinline__ uint2 ld_in(const uint2* a) {
    uint2 v; asm volatile("ld.global.nc.L1::no_allocate.v2.u32 {%0,%1}, [%2];" : "=r"(v.x), "=r"(v.y) : "l"(a)); return v;
}
__device__ __forceinline__ uint32_t ld_in(const uint32_t* a) {
    uint32_t v; asm volatile("ld.global.nc.L1::no_allocate.u32 %0, [%1];" : "=r"(v) : "l"(a)); return v;
}
__device__ __forceinline__ void ld_in4(const uint2* p, uint2& a, uint2& b) {
    asm volatile("ld.global.nc.L1::no_allocate.v4.u32 {%0,%1,%2,%3}, [%4];" : "=r"(a.x), "=r"(a.y), "=r"(b.x), "=r"(b.y) : "l"(p));
}
__device__ __forceinline__ void tex4(cudaTextureObject_t t, int i, uint2& a, uint2& b) {
    asm volatile("tex.1d.v4.u32.s32 {%0,%1,%2,%3}, [%4, {%5}];" : "=r"(a.x), "=r"(a.y), "=r"(b.x), "=r"(b.y) : "l"(t), "r"(i));
}
__device__ __forceinline__ void tex2(cudaTextureObject_t t, int i, uint32_t& a, uint32_t& b) {
    asm volatile("{ .reg .b32 z, w; tex.1d.v4.u32.s32 {%0,%1,z,w}, [%2, {%3}]; }" : "=r"(a), "=r"(b) : "l"(t), "r"(i) : "memory");
}
template <int OFF> __device__ __forceinline__ void put_rec(uint32_t ret, uint32_t lim, uint32_t addr, uint32_t x, uint32_t y) {
    asm volatile("{ .reg .pred q; setp.lt.u32 q, %0, %1; @q st.shared.v2.u32 [%2+%5], {%3,%4}; }" ::"r"(ret), "r"(lim), "r"(addr), "r"(x), "r"(y), "n"(OFF) : "memory");
}
__device__ __forceinline__ uint32_t mbar_try(uint32_t mb, uint32_t parity) {
    uint32_t ok;
    asm volatile("{ .reg .pred q; mbarrier.try_wait.parity.shared::cta.b64 q, [%1], %2; selp.u32 %0, 1, 0, q; }" : "=r"(ok) : "r"(mb), "r"(parity) : "memory");
    return ok;
}
__device__ __forceinline__ void mbar_wait(uint32_t mb, uint32_t parity) {
    if (!mbar_try(mb, parity)) {
        int it = 0;
        while (!mbar_try(mb, parity)) if (++it > SPIN_LIMIT) __trap();
    }
}
__device__ __forceinline__ void mbar_init(uint32_t mb, uint32_t n) { asm volatile("mbarrier.init.shared::cta.b64 [%0], %1;" ::"r"(mb), "r"(n) : "memory"); }
__device__ __forceinline__ void mbar_arrive(uint32_t mb) { asm volatile("mbarrier.arrive.shared::cta.b64 _, [%0];" ::"r"(mb) : "memory"); }
constexpr int B_FULL = OFF_BAR, B_OPEN = OFF_BAR + 16, B_FREE = OFF_BAR + 32;
constexpr int W_END = OFF_BAR + 40, W_SIDE = OFF_BAR + 44, W_PAR = OFF_BAR + 48, W_ROLE = OFF_BAR + 52, W_EXP = OFF_BAR + 56, W_UNIT = OFF_BAR + 60, W_NLIST = OFF_PROBE + 112, W_WRAP = OFF_PROBE + 116, W_BASE = OFF_PROBE + 120, B_TAB = OFF_PROBE + 128;
enum { BAR_S1 = 1, BAR_SIDE, BAR_PROBE, BAR_PAR, BAR_TABLE, BAR_DONE, BAR_TFREE, BAR_ACC, BAR_FLAG, BAR_H1 };
constexpr int W_M1 = NS1 + NC, W_M2 = 31;

extern __shared__ __align__(1024) unsigned char smem[];
#define RTS(c, i)
#define TK_DECL
#define TK(i)
#define TK_CNT(i)
#define TK_OUT
#define TK_ARG
#define TK_PASS
#define TKS(i) TK(i)
#define TKX(i)
#define TKY(i) {}
#define TKZ(i, d)

__device__ __forceinline__ void prefetch_l2(const void* a) { asm volatile("prefetch.global.L2 [%0];" ::"l"(a)); }
__device__ __forceinline__ void wait_flags(const Params& p, uint32_t sb, int lane, uint32_t need) {
    const unsigned char* f = p.ring + M_FLAG + (lds32(sb + W_SIDE) << 12);
    int it = 0;
    while (true) {
        uint32_t a[5];
        asm volatile("ld.acquire.gpu.global.v4.u32 {%0,%1,%2,%3}, [%4];" : "=r"(a[0]), "=r"(a[1]), "=r"(a[2]), "=r"(a[3]) : "l"(f + lane * 16) : "memory");
        asm volatile("ld.acquire.gpu.global.u32 %0, [%1];" : "=r"(a[4]) : "l"(f + 512 + (lane & 3) * 4) : "memory");
        const uint32_t d = (a[0] ^ need) | (a[1] ^ need) | (a[2] ^ need) | (a[3] ^ need) | (a[4] ^ need);
        if (__all_sync(0xffffffffu, d == 0)) break;
        __nanosleep(50);
        if (++it > SPIN_LIMIT) __trap();
    }
}
__device__ __forceinline__ float exp_fast(float x) { float r; asm("ex2.approx.ftz.f32 %0, %1;" : "=f"(r) : "f"(x * 1.4426950408889634f)); return r; }
constexpr uint32_t BIAS = 0x3d803d80u, ZERO = 0x7d80u;
__device__ __forceinline__ float2 acc_fix(uint32_t old, uint32_t q) {
    const uint32_t u = old + BIAS, n = u + q - 0x08000800u;
    return make_float2((float)((int)(u & 0xffffu) + (int)(q & 0xffffu) - 2048 - (int)(n & 0xffffu)), (float)((int)(u >> 16) + (int)(q >> 16) - 2048 - (int)(n >> 16)));
}
constexpr int NE = NS1 + NC, NPAIR = (R2MAX / 2 + NE * 32 - 1) / (NE * 32), NTILE = 15, NG0 = NS1 * 8 * NTILE;
constexpr int OFF_G = OFF_M, GH = R2MAX * 8, OFF_LIST = OFF_G;
static_assert(2 * R2MAX <= R1MAX && NG0 * 16 <= WIN && NG0 + NE * 8 * NTILE >= R2MAX / 2 && NPAIR * NE * 64 <= DROW, "gates");
__device__ __forceinline__ int gate_g(int k) { return (k < NG0 ? OFF_H1 : OFF_G) + k * 16; }
__device__ __forceinline__ int gate_h(int k) { return (k < NG0 ? OFF_H1 + 0x20000 : OFF_G + GH) + k * 16; }
__device__ __forceinline__ uint2 out_row(int row, const float4& o, const float4& add, const uint2& mv) {
    const float* w = reinterpret_cast<const float*>(smem + OFF_WSM);
    const float unit = *reinterpret_cast<const float*>(smem + W_UNIT), K = 8388608.f + ZERO;
    const uint2 ac = reinterpret_cast<const uint2*>(smem + OFF_ACC)[row];
    const uint32_t* g = reinterpret_cast<const uint32_t*>(smem + gate_g(row >> 1)) + (row & 1), *h = reinterpret_cast<const uint32_t*>(smem + gate_h(row >> 1)) + (row & 1);
    const uint32_t c0 = ac.x + BIAS, c1 = ac.y + BIAS;
    const float a[4] = {fmaf(__uint_as_float(__byte_perm(c0, 0x4b00u, 0x5410)) - K, unit, o.x), fmaf(__uint_as_float(__byte_perm(c0, 0x4b00u, 0x5432)) - K, unit, o.y),
                        fmaf(__uint_as_float(__byte_perm(c1, 0x4b00u, 0x5410)) - K, unit, o.z), fmaf(__uint_as_float(__byte_perm(c1, 0x4b00u, 0x5432)) - K, unit, o.w)};
    float sd[4], uu[4];
#pragma unroll
    for (int k = 0; k < 4; k++) sd[k] = fmaf(a[3], w[12 + k], fmaf(a[2], w[8 + k], fmaf(a[1], w[4 + k], a[0] * w[k])));
    const uint32_t a01 = hmul_bf2(pack_bf2(sd[0] + add.x, sd[1] + add.y), g[0]), a23 = hmul_bf2(pack_bf2(sd[2] + add.z, sd[3] + add.w), g[2]);
#pragma unroll
    for (int k = 0; k < 4; k++) uu[k] = fmaf(bf_hi(a23), w[28 + k], fmaf(bf_lo(a23), w[24 + k], fmaf(bf_hi(a01), w[20 + k], bf_lo(a01) * w[16 + k])));
    return make_uint2(hadd_bf2(mv.x, hmul_bf2(pack_bf2(uu[0], uu[1]), h[0])), hadd_bf2(mv.y, hmul_bf2(pack_bf2(uu[2], uu[3]), h[2])));
}
__device__ __forceinline__ void mma16(float (&c)[4], const uint32_t (&a)[4], uint32_t b0, uint32_t b1) {
    asm volatile("mma.sync.aligned.m16n8k16.row.col.f32.bf16.bf16.f32 {%0,%1,%2,%3}, {%4,%5,%6,%7}, {%8,%9}, {%0,%1,%2,%3};"
                 : "+f"(c[0]), "+f"(c[1]), "+f"(c[2]), "+f"(c[3]) : "r"(a[0]), "r"(a[1]), "r"(a[2]), "r"(a[3]), "r"(b0), "r"(b1));
}
__device__ __forceinline__ void finish_rows(const Params& p, uint32_t sb) {
    int tid;
    asm volatile("mov.u32 %0, %%tid.x;" : "=r"(tid));
    const int role = lds32(sb + W_ROLE), row0 = role * p.R2, np = min(p.R2, p.E - row0) >> 1, lane = tid & 31;
    {
        const uint16_t* wg = reinterpret_cast<const uint16_t*>(lane & 16 ? p.w_rbf : p.w_sbf) + (lane & 3) * 8 + (lane >> 2 & 3);
        const uint16_t* cp = reinterpret_cast<const uint16_t*>(p.centers) + (lane & 3) * 2;
        const uint32_t wb = __ldg(wg) | (uint32_t)__ldg(wg + 4) << 16, cen = __ldg(cp) | (uint32_t)__ldg(cp + 1) << 16;
        if (tid < NS1 * 32) {
            if (tid * 32 < np) prefetch_l2(p.dist + row0 + tid * 64);
            for (int i = tid * 8; i < np; i += NS1 * 32 * 8) prefetch_l2(p.m + row0 + 2 * i);
        }
#pragma unroll 1
        for (int pass = tid >= NS1 * 32; pass < 2; pass++) {
            const int k0 = (pass ? NG0 : 0) + (tid >> 2), dk = pass ? NE * 8 : NS1 * 8;
            uint2 v[NTILE];
#pragma unroll
            for (int i = 0; i < NTILE; i++) v[i].x = ld_in(reinterpret_cast<const uint32_t*>(p.dist) + min((row0 >> 1) + k0 + i * dk, (p.E >> 1) - 1));
#pragma unroll
            for (int i = 0; i < NTILE; i++) {
                uint32_t rb[2];
#pragma unroll
                for (int u = 0; u < 2; u++) {
                    const uint32_t df = hsub_bf2(__byte_perm(v[i].x, 0u, u ? 0x3232 : 0x1010), cen);
                    const uint32_t ar = hmul_bf2(hmul_bf2(df, df), 0xc120c120u);
                    rb[u] = pack_bf2(exp_fast(bf_lo(ar)), exp_fast(bf_hi(ar)));
                }
                float c[4];
                asm volatile("mma.sync.aligned.m16n8k8.row.col.f32.bf16.bf16.f32 {%0,%1,%2,%3}, {%4,%5}, {%6}, {%7,%7,%7,%7};"
                             : "=f"(c[0]), "=f"(c[1]), "=f"(c[2]), "=f"(c[3]) : "r"(rb[0]), "r"(rb[1]), "r"(wb), "f"(0.f));
                v[i] = make_uint2(pack_bf2(c[0], c[1]), pack_bf2(c[2], c[3]));
            }
            if (pass) bar_sync(BAR_TFREE, NE * 32); else bar_sync(BAR_H1, (NS1 + 1) * 32);
            const uint32_t a = sb + (lane & 2 ? gate_h(k0) : gate_g(k0)) + (lane & 1) * 8;
#pragma unroll
            for (int i = 0; i < NTILE; i++) if (k0 + i * dk < R2MAX / 2) sts64(a + i * dk * 16, v[i].x, v[i].y);
            if (pass) TKY(1) else TKY(0)
        }
    }
    uint2 mv[2 * NPAIR];
#pragma unroll
    for (int i = 0; i < NPAIR; i++) ld_in4(p.m + 2 * min((row0 >> 1) + tid + i * NE * 32, (p.E >> 1) - 1), mv[2 * i], mv[2 * i + 1]);
    uint8_t* dirty = g_dirty + role * DROW + tid * 2;
    auto flags = [&]() {
        uint32_t f[NPAIR], m = 0;
#pragma unroll
        for (int i = 0; i < NPAIR; i++) asm volatile("ld.relaxed.gpu.global.u16 %0, [%1];" : "=r"(f[i]) : "l"(dirty + i * NE * 64) : "memory");
#pragma unroll
        for (int i = 0; i < NPAIR; i++) m |= ((f[i] | f[i] >> 7) & 3u) << 2 * i;
        return m;
    };
    auto row_of = [&](int j) { return 2 * tid + (j >> 1) * NE * 64 + (j & 1); };
    bar_sync(BAR_FLAG, (NE + 1) * 32);
    TKY(2)
    uint32_t kept = flags(), left = 0, bad = 0, at = 0;
    TKZ(3, kept)
    if (kept) {
        at = atoms_add<W_NLIST>(sb, __popc(kept));
        if (at + __popc(kept) > NG0) { left = kept; kept = 0; }
        at = sb + OFF_LIST + at * 16;
        uint32_t to = at;
#pragma unroll 1
        for (uint32_t m = kept; m; m &= m - 1) {
            float4 o[2];
            o[0] = take(&g_ovf[role * RPAD + row_of(__ffs(m) - 1)], true);
            m &= m - 1;
            o[1] = take(&g_ovf[role * RPAD + row_of(__ffs(m) - 1)], m);
            const float4* w = reinterpret_cast<const float4*>(smem + OFF_WSM);
#pragma unroll
            for (int u = 0; u < 2; u++) if (!u || m) {
                sts128<0>(to, make_uint4(__float_as_uint(fmaf(o[u].w, w[3].x, fmaf(o[u].z, w[2].x, fmaf(o[u].y, w[1].x, o[u].x * w[0].x)))),
                                         __float_as_uint(fmaf(o[u].w, w[3].y, fmaf(o[u].z, w[2].y, fmaf(o[u].y, w[1].y, o[u].x * w[0].y)))),
                                         __float_as_uint(fmaf(o[u].w, w[3].z, fmaf(o[u].z, w[2].z, fmaf(o[u].y, w[1].z, o[u].x * w[0].z)))),
                                         __float_as_uint(fmaf(o[u].w, w[3].w, fmaf(o[u].z, w[2].w, fmaf(o[u].y, w[1].w, o[u].x * w[0].w))))));
                to += 16;
            }
        }
    }
    uint32_t wb[8];
#pragma unroll
    for (int i = 0; i < 8; i++) {
        const uint32_t a = sb + OFF_WSM + ((i & 4) * 4 + (i & 1) * 8 + (i & 2) + (lane >> 2 & 1)) * 4;
        wb[i] = (lane & 3) == lane >> 3 ? __byte_perm(lds32(a), lds32(a + 16), 0x7632) : 0u;
    }
    const uint32_t k0 = (lds32(sb + W_UNIT) >> 16) * 0x10001u + 0x03800380u;
    TKX(5)
    bar_sync(BAR_ACC, (NE + NC) * 32);
    TKX(6)
    uint32_t from = at;
#pragma unroll
    for (int i = 0; i < NPAIR; i++) {
        const int k = tid + i * NE * 32;
        const uint4 ac = lds128(sb + OFF_ACC + k * 16), g = lds128(sb + gate_g(k)), h = lds128(sb + gate_h(k));
        const uint32_t u[4] = {ac.x + BIAS, ac.z + BIAS, ac.y + BIAS, ac.w + BIAS};
        uint32_t a[4];
        float c[4] = {0.f, 0.f, 0.f, 0.f}, d[4] = {0.f, 0.f, 0.f, 0.f};
#pragma unroll
        for (int j = 0; j < 2; j++)
            asm volatile("{ .reg .pred q; setp.ne.u32 q, %5, 0; @q ld.shared.v2.f32 {%0,%1}, [%4]; @q ld.shared.v2.f32 {%2,%3}, [%4+8]; @q add.u32 %4, %4, 16; }"
                         : "+f"(c[2 * j]), "+f"(c[2 * j + 1]), "+f"(d[2 * j]), "+f"(d[2 * j + 1]), "+r"(from) : "r"(kept & 1u << (2 * i + j)) : "memory");
#pragma unroll
        for (int j = 0; j < 4; j++) a[j] = hsub_bf2(and_or<0x007f007fu>(u[j] >> 9, k0 + 0x04800480u), k0 + 0x04c004c0u);
        mma16(c, a, wb[0], wb[1]); mma16(d, a, wb[2], wb[3]);
#pragma unroll
        for (int j = 0; j < 4; j++) a[j] = and_or<0x007f007fu>(u[j] >> 2, k0 + 0x01000100u);
        mma16(c, a, wb[0], wb[1]); mma16(d, a, wb[2], wb[3]);
#pragma unroll
        for (int j = 0; j < 4; j++) a[j] = and_or<0x00030003u>(u[j], k0);
        mma16(c, a, wb[0], wb[1]); mma16(d, a, wb[2], wb[3]);
        a[0] = hmul_bf2(pack_bf2(c[0], c[1]), g.x); a[1] = hmul_bf2(pack_bf2(c[2], c[3]), g.y);
        a[2] = hmul_bf2(pack_bf2(d[0], d[1]), g.z); a[3] = hmul_bf2(pack_bf2(d[2], d[3]), g.w);
#pragma unroll
        for (int j = 0; j < 4; j++) c[j] = d[j] = 0.f;
        mma16(c, a, wb[4], wb[5]); mma16(d, a, wb[6], wb[7]);
        if (k < np) {
            reinterpret_cast<uint4*>(p.out + row0)[k] = make_uint4(hadd_bf2(mv[2 * i].x, hmul_bf2(pack_bf2(c[0], c[1]), h.x)), hadd_bf2(mv[2 * i].y, hmul_bf2(pack_bf2(d[0], d[1]), h.z)),
                                                                   hadd_bf2(mv[2 * i + 1].x, hmul_bf2(pack_bf2(c[2], c[3]), h.y)), hadd_bf2(mv[2 * i + 1].y, hmul_bf2(pack_bf2(d[2], d[3]), h.w)));
            if (c[0] != c[0] || c[2] != c[2]) bad |= 3u << 2 * i;
        }
    }
    if (lds32(sb + W_WRAP)) left = flags();
#pragma unroll 1
    for (uint32_t m = left | bad; m; m &= m - 1) {
        const int j = __ffs(m) - 1, row = row_of(j);
        uint4 v = make_uint4(0u, 0u, 0u, 0u);
        if (kept >> j & 1u) v = lds128(at + __popc(kept & ((1u << j) - 1u)) * 16);
        p.out[row0 + row] = out_row(row, take(&g_ovf[role * RPAD + row], left >> j & 1u),
                                    make_float4(__uint_as_float(v.x), __uint_as_float(v.y), __uint_as_float(v.z), __uint_as_float(v.w)), p.m[row0 + row]);
    }
#pragma unroll 1
    for (uint32_t m = left | kept; m; m &= m - 1) g_dirty[role * DROW + row_of(__ffs(m) - 1)] = 0;
}

template <int HOP> __device__ __forceinline__ uint2 null_rec(int lane, uint32_t R) {
    if (HOP == 1) return make_uint2(0x800000u | H<1>::tag(R), (OFF_CNT1 - OFF_M) / 8);
    return make_uint2(0x08000800u | lane << 28, (NS3 ? 0x0fff0000u : 0x08000800u) | H<2>::tag(R));
}
template <int HOP> __device__ __forceinline__ void fill(uint32_t win, int lane, uint32_t R) {
    const uint2 v = null_rec<HOP>(lane, R);
#pragma unroll 11
    for (int i = 0; i < WIN / 512; i++) sts128<0>(win + lane * 16 + i * 512, make_uint4(v.x, v.y, v.x, v.y));
}
template <int HOP> __device__ __forceinline__ void reset(uint32_t win, int lane, uint32_t R) {
    const uint2 v = null_rec<HOP>(lane, R);
    const uint32_t a = win + lane * 32 + H<HOP>::mark(R, lane >> 2) * 8;
#pragma unroll
    for (int i = 0; i < 16; i++) sts64(a + i * 1024, v.x, v.y);
    if (lane < 16) sts64(a + 16384, v.x, v.y);
}
__device__ __forceinline__ bool elect() {
    uint32_t q; asm volatile("{ .reg .pred q; elect.sync _|q, 0xffffffff; selp.u32 %0, 1, 0, q; }" : "=r"(q)); return q;
}
__device__ __forceinline__ const unsigned char* mk_ptr(uint32_t lo, uint32_t hi) { return reinterpret_cast<const unsigned char*>((uint64_t)hi << 32 | lo); }
__device__ __forceinline__ void bulk_store(uint32_t lo, uint32_t hi, uint32_t src, uint32_t n) {
    asm volatile("cp.async.bulk.global.shared::cta.bulk_group [%0], [%1], %2;" ::"l"(mk_ptr(lo, hi)), "r"(src), "r"(n) : "memory");
}
#define CRED_NS 100
#define CRED_SKIP 1
template <int HOP>
__device__ __forceinline__ void manager(const Params& p, uint32_t sb, int lane, int role, uint32_t base) {
    typedef H<HOP> h;
    constexpr int V = h::NBIN / 32, PB = h::S * 8;
    const int RT = p.rounds, lo = HOP == 1 && role >= NG ? NG : 0, hi = lo + h::NBIN;
    const int w = (role - lo) / (HOP * J), j = (role - lo - w * HOP * J) / HOP;
    const Ring rg(p.ring, __reduce_or_sync(0xffffffffu, lds32(sb + W_PAR)), 2 * w + HOP - 1);
    const uint32_t side = lds32(sb + W_SIDE), dhi = rg.main >> 32, mhi = rg.mid >> 32;
    const uint32_t c0 = HOP == 2 ? role & 1 : 0, up = (HOP == 1 && lo) ^ rg.par ^ c0;
    uint32_t dA = ((uint32_t)rg.main + src_off(j) + (c0 << 16) + (up ? 4096 : 12288)) ^ slot_off(base % 3);
    uint32_t dM = ((uint32_t)rg.mid + src_off(j) + c0 * 1024) ^ slot_off(base % 3);
    const int a0 = max(64, lo), b1 = min(68, hi);
    int n0 = (min(NHI, hi) - a0) * PB, a1 = (max(NLO, lo) - lo) * PB;
    const unsigned char* cr = reinterpret_cast<const unsigned char*>(rg.main) + MISC + ((side ^ rg.par) << 12);
    const unsigned char* cr0 = cr + cred_off(lo + lane * V), *cr1 = cr + cred_off(lo + 32 * V + min(lane, V - 1));
    const uint32_t ca0 = sb + h::CNT + lane * V * 4, ca1 = sb + h::CNT + (32 * V + min(lane, V + NDUM)) * 4;
    const uint32_t rot0 = (lane * V & 7) * 16, rot1 = lane * 16;
    uint32_t st = slot_steps(base);
    uint32_t init = h::init(base), prim = sb + h::STG + (HOP == 1 ? h::win(base) : 0u);
    uint32_t cs[5] = {0, 0, 0, 0, 0};
    auto sample = [&]() {
        if (V == 2) asm volatile("ld.relaxed.gpu.global.v2.u32 {%0,%1}, [%2];" : "=r"(cs[0]), "=r"(cs[1]) : "l"(cr0) : "memory");
        else asm volatile("ld.relaxed.gpu.global.v4.u32 {%0,%1,%2,%3}, [%4];" : "=r"(cs[0]), "=r"(cs[1]), "=r"(cs[2]), "=r"(cs[3]) : "l"(cr0) : "memory");
        cs[V] = ld_rlx32(reinterpret_cast<const uint32_t*>(cr1));
    };
    uint32_t low[5] = {rot0, rot0 + 16, rot0 + 32, rot0 + 48, rot1};
    TK_DECL
#pragma unroll 1
    for (int r = 0;; r++) {
        const uint32_t R = base + r, ninit = h::init(R + 1), done = prim;
        TK(5)
        mbar_wait(sb + B_FULL + (HOP - 1) * 8, r & 1);
        TK(0)
        uint32_t c[5];
        if (V == 2) asm volatile("ld.shared.v2.u32 {%0,%1}, [%2];" : "=r"(c[0]), "=r"(c[1]) : "r"(ca0) : "memory");
        else asm volatile("ld.shared.v4.u32 {%0,%1,%2,%3}, [%4];" : "=r"(c[0]), "=r"(c[1]), "=r"(c[2]), "=r"(c[3]) : "r"(ca0) : "memory");
        c[V] = lds32(ca1);
        uint32_t nc[5];
#pragma unroll
        for (int k = 0; k <= V; k++) {
            const uint32_t rot = k < V ? rot0 + k * 16 : rot1, z = ninit + (HOP == 1 ? rot : low[k]);
            if (HOP == 2 && XB != 1) low[k] = min((max((int)(c[k] - low[k] - init - h::CAP * h::INC), 0) >> h::SH) * 128u + low[k], rot + BOXN * 128u);
            nc[k] = min(max(c[k] + (ninit - init - h::S * h::INC), z), (HOP == 1 ? z : ninit + low[k]) + (h::CAP - h::S) * h::INC);
        }
        if (V == 2) sts64(ca0, nc[0], nc[1]); else sts128<0>(ca0, make_uint4(nc[0], nc[1], nc[2], nc[3]));
        sts32(ca1, lane < V ? nc[V] : lane < V + NDUM ? DUMMY : r);
        __syncwarp();
        if (lane == 0) mbar_arrive(sb + B_OPEN + (HOP - 1) * 8);
        TK(1)
        TK(2)
        asm volatile("fence.proxy.async.shared::cta;" ::: "memory");
        TK(6)
        if (r >= D) {
            int it = 0;
            while (true) {
                uint32_t bad = 0;
#pragma unroll
                for (int k = 0; k <= V; k++) bad |= cs[k] - (R - D + 1);
                if (!__any_sync(0xffffffffu, bad >> 20)) break;
                if (++it > SPIN_LIMIT) __trap();
                if (it > CRED_SKIP) __nanosleep(CRED_NS);
                sample();
            }
        }
        TK(3)
        if (elect()) {
            const uint32_t dB = (HOP == 1 ? dA ^ 0x10000u : dA) + (up ? 8192 : -8192), sm = prim + (lo ? 2 * PB : 0);
            bulk_store(dA, dhi, sm, 8192);
            bulk_store(dB, dhi, HOP == 1 ? sm + 8192 : prim + 68 * PB, 8192);
            if (n0 > 0) bulk_store(dM + (a0 - 64) * PB, mhi, prim + (a0 - lo) * PB, n0);
            if (a1 < (b1 - lo) * PB) bulk_store((dM ^ 4096u) + (uint32_t)((lo - NLO) * PB + a1), mhi, prim + a1, (b1 - lo) * PB - a1);
            asm volatile("cp.async.bulk.commit_group;" ::: "memory");
            if (r != RT - 1) asm volatile("cp.async.bulk.wait_group.read 0;" ::: "memory");
        }
        __syncwarp();
        TK(4)
        prim = HOP == 1 ? prim ^ 0x20000u : prim >= sb + 0x30000u ? sb : prim + (prim - sb) + 0x10000u;
        if (r == RT - 1) break;
        reset<HOP>(done, lane, R + HOP + 1);
        if (HOP == 1) {
            __syncwarp();
            if (lane == 0) mbar_arrive(sb + B_FREE);
        }
        if (RARE(r == D - 1 || r == RT - D - 1)) {
            uint32_t n = NHI, m = NLO;
            if (r < RT - D - 1) {
                int it = 0;
                while (true) {
                    n = ld_rlx32(reinterpret_cast<const uint32_t*>(p.ring + M_CNT + (side << 12)));
                    if ((n & 0xffffu) + (n >> 16) == NB) break;
                    if (++it > SPIN_LIMIT) __trap();
                }
                m = n = min(max(__reduce_or_sync(0xffffffffu, n) & 0xffffu, (uint32_t)NLO), (uint32_t)NHI);
            }
            n0 = (min((int)n, hi) - a0) * PB;
            a1 = (max((int)m, lo) - lo) * PB;
        }
        if (HOP == 2 && RARE(r == RT - LATE)) fence_gpu();
        sample();
        slot_next(dA, st); slot_next(dM, st);
        st = slot_rot(st);
        init = ninit;
    }
    TK_OUT
}

#define POLL_NS 200
#define POLL_NS3 1500
template <int HOP> struct Reader {
    uint32_t lo, hi, st, line;
    uint32_t* cred;
    __device__ __forceinline__ void init(const Params& p, uint32_t sb, int w, int lane, int role, uint32_t base) {
        constexpr int PB = H<HOP>::S * 8;
        const int first = HOP == 1 ? (role >= NG ? NG : 0) + w * J : w * 2 * J;
        const Ring rg(p.ring, lds32(sb + W_PAR), 2 * w + HOP - 1);
        const uint32_t side = lds32(sb + W_SIDE);
        const bool mid = side ? role < 68 : role >= 64;
        const uint32_t i = role - (side ? (mid ? NLO : 68) : (mid ? 64 : 0));
        const uint32_t c = HOP == 1 ? i >> 5 : lane >> 3 & 1, in = (HOP == 1 ? (i & 31) * PB + (lane & 15) * 16 : i * PB + (lane & 7) * 16) + (lane >> 4) * src_off(3);
        lo = (in + (mid ? ((uint32_t)rg.mid ^ side << 12) + c * 1024 : (uint32_t)rg.main + (c << 16) + (side ^ rg.par ^ c ? 4096 : 12288))) ^ slot_off(base % 3);
        hi = __reduce_or_sync(0xffffffffu, (uint32_t)((mid ? rg.mid : rg.main) >> 32));
        st = slot_steps(base);
        line = opaque((HOP == 1 ? 2 * (role % NG) + (lane >> 3 & 1) : role) + (lane & 1) * 2);
        const bool both = first >= NLO && first < NHI;
        cred = lane < 1 + both ? reinterpret_cast<uint32_t*>(rg.main + MISC + (((both ? lane : first >= NG) ^ rg.par) << 12) + cred_off(role)) : nullptr;
    }
    template <int K> __device__ __forceinline__ void load1(uint2 (&v)[J]) const {
        asm volatile("ld.relaxed.gpu.global.v4.u32 {%0,%1,%2,%3}, [%4+%5];" : "=r"(v[2 * K].x), "=r"(v[2 * K].y), "=r"(v[2 * K + 1].x), "=r"(v[2 * K + 1].y)
                     : "l"(mk_ptr(lo, hi)), "n"(src_off(K)) : "memory");
    }
    static __device__ __forceinline__ uint32_t word(const uint2& v) { return HOP == 1 ? v.x : v.y; }
    template <int K> __device__ __forceinline__ void again(uint2 (&v)[J], uint32_t want, uint32_t m0, uint32_t m1, uint32_t grp) const {
        if (__ballot_sync(0xffffffffu, ((word(v[2 * K]) ^ want) & m0) | ((word(v[2 * K + 1]) ^ want) & m1)) & grp) load1<K>(v);
    }
    __device__ __forceinline__ void load(uint2 (&rec)[J]) const { load1<0>(rec); load1<1>(rec); load1<2>(rec); }
    __device__ __forceinline__ void check(uint2 (&rec)[J], uint32_t R, uint32_t ns, int lane TK_ARG) {
        const uint32_t want = H<HOP>::tag(R), mk = H<HOP>::mark(R, line);
        const uint32_t m0 = mk == 0 ? H<HOP>::TAG : 0u, m1 = mk == 1 ? H<HOP>::TAG : 0u;
        int it = 0;
        while (true) {
            uint32_t b0 = 0, b1 = 0;
#pragma unroll
            for (int j = 0; j < J; j += 2) { b0 |= word(rec[j]) ^ want; b1 |= word(rec[j + 1]) ^ want; }
            if (!__any_sync(0xffffffffu, (b0 & m0) | (b1 & m1))) break;
            if (++it > SPIN_LIMIT) __trap();
            __nanosleep(ns);
            TK_CNT(7)
            const uint32_t grp = 0xffu << (lane & 24u);
            again<0>(rec, want, m0, m1, grp); again<1>(rec, want, m0, m1, grp); again<2>(rec, want, m0, m1, grp);
        }
        if (cred) st_rlx32(cred, R + 1);
        __syncwarp();
        slot_next(lo, st);
        st = slot_rot(st);
    }
    __device__ __forceinline__ void finish() const { if (cred) st_rlx32(cred, 0u); }
};

#define NPROBE 4
__device__ __forceinline__ uint32_t probe(unsigned char* a, uint32_t zero) {
    *reinterpret_cast<uint4*>(a) = make_uint4(0u, 0u, 0u, 0u);
    *reinterpret_cast<uint4*>(a + 16) = make_uint4(0u, 0u, 0u, 0u);
    uint32_t best = ~0u, v = threadIdx.x, prev = 0;
#pragma unroll
    for (int t = 0; t <= NPROBE + 1; t++) {
        uint32_t now;
        if (t <= NPROBE) asm volatile("atom.relaxed.gpu.global.add.u32 %0, [%1], 1;" : "=r"(v) : "l"(a + (v & zero)) : "memory");
        else asm volatile("red.relaxed.gpu.global.add.u32 [%0], 1;" ::"l"(a + (v & zero)) : "memory");
        asm volatile("mov.u32 %0, %%clock;" : "=r"(now) :: "memory");
        if (t > 1) best = min(best, now - prev);
        prev = now;
    }
    return best;
}
template <bool B> struct BoolC { static constexpr bool value = B; };

__device__ __forceinline__ void stage1(const Params& p, uint32_t sb, const int pos0, int lane, const bool half) {
    typedef H<1> h;
    constexpr int NP = 4;
    static_assert(NPR == NS1 * NP * 32 - NP * 16 && G1 == NP, "tiles");
    const int RT = p.rounds;
    uint32_t ff = *reinterpret_cast<const uint16_t*>(p.ang_freq) * 0x10001u;
    auto pair_of = [&](int r, int pos) {
        const int q = r < RT - 1 ? (r * NB + blockIdx.x) * NPR + pos : (RT - 1) * NB * NPR + blockIdx.x * p.lastn + pos;
        return pos < (r < RT - 1 ? NPR : r == RT - 1 ? p.lastn : 0) && q < p.T2 ? q : -1;
    };
    uint2 vi[NP], vo[NP]; uint32_t va[NP];
    auto load_edge = [&](int r) {
#pragma unroll
        for (int u = 0; u < NP; u++) {
            const int q = max(pair_of(r, pos0 + u * 32), 0);
            vi[u] = ld_in(p.idx_in + q); vo[u] = ld_in(p.idx_out + q); va[u] = ld_in(p.angle + q);
        }
    };
    load_edge(0);
    if (blockIdx.x == 0 && pos0 == 0 && (p.T & 1)) {
        const int t = p.T - 1;
        slow_triplet(p, reinterpret_cast<const uint32_t*>(p.idx_in)[t], reinterpret_cast<const uint32_t*>(p.idx_out)[t],
                     bf16r(cos_bf(hmul_bf2(reinterpret_cast<const uint16_t*>(p.angle)[t], ff) & 0xffffu)));
    }
    ff = __reduce_or_sync(0xffffffffu, ff);
    bar_sync(BAR_S1, (NS1 + 1) * 32);
    uint32_t R = U1 ? __reduce_or_sync(0xffffffffu, lds32(sb + W_BASE)) : lds32(sb + W_BASE) + (lane & p.zero);
    TK_DECL
    auto step = [&](const int r, const int qn, auto edge) {
        constexpr bool EDGE = decltype(edge)::value;
        uint32_t cc[NP], big = 0;
#pragma unroll
        for (int u = 0; u < NP; u++) {
            va[u] = hmul_bf2(va[u], ff);
            cc[u] = pack_bf2(__cosf(bf_lo(va[u])), __cosf(bf_hi(va[u])));
            if (BG) big |= hmul_bf2(va[u], 0x3d003d00u);
            else big = __vmaxu2(big, va[u] & 0x7fff7fffu);
        }
        if (RARE(BG == 2 ? __any_sync(0xffffffffu, big & 0x40004000u) : BG ? big & 0x40004000u : (big + (0x7fffu - BIGX) * 0x10001u) & 0x80008000u)) {
#pragma unroll 1
            for (int u = 0; u < NP; u++) {
                const uint32_t a = pick(u, va);
                float c0 = cos_bf(a & 0xffffu), c1 = cos_bf(a >> 16);
                if ((c0 != c0 || c1 != c1) && (EDGE ? pair_of(r, pos0 + u * 32) >= 0 : !half || u < 2)) {
                    const uint2 i2 = pick(u, vi), o2 = pick(u, vo);
                    if (c0 != c0) slow_triplet(p, i2.x, o2.x, c0);
                    if (c1 != c1) slow_triplet(p, i2.y, o2.y, c1);
                }
                const uint32_t v = pack_bf2(c0 != c0 ? 0.f : c0, c1 != c1 ? 0.f : c1);
#pragma unroll
                for (int k = 0; k < NP; k++) if (k == u) cc[k] = v;
                if (BG == 2) __syncwarp();
            }
        }
        uint32_t bin[2 * NP], x[2 * NP], y[2 * NP];
        uint32_t dep = 0;
        auto loads = [&]() {
            const int q = qn + (dep & p.zero);
#pragma unroll
            for (int u = 0; u < NP; u += 2) {
                const int k = !u ? q : TEXIN ? q + (half ? 0x40000000 : 32) : half ? 0 : q + 32;
                if (TEXIN) { tex2(p.ta, k, va[u], va[u + 1]); tex4(p.to, k, vo[u], vo[u + 1]); tex4(p.ti, k, vi[u], vi[u + 1]); }
                else {
                    const uint2 v = ld_in(reinterpret_cast<const uint2*>(p.angle) + k); va[u] = v.x; va[u + 1] = v.y;
                    ld_in4(p.idx_out + 2 * k, vo[u], vo[u + 1]); ld_in4(p.idx_in + 2 * k, vi[u], vi[u + 1]);
                }
            }
        };
#pragma unroll
        for (int j = 0; j < 2 * NP; j++) {
            const uint32_t ii = j & 1 ? vi[j >> 1].y : vi[j >> 1].x, oo = j & 1 ? vo[j >> 1].y : vo[j >> 1].x;
            bin[j] = imul(ii, p.i1);
            y[j] = __byte_perm(ifma(bin[j], p.k1, ii), cc[j >> 1], j & 1 ? 0x7610 : 0x5410);
            const uint32_t bo = imul(oo, p.i2);
            x[j] = __byte_perm(ifma(bo, p.k2, imul(oo, 8.f)), bo, 0x0514);
            dep |= x[j] | y[j];
            if (EDGE && pair_of(r, pos0 + (j >> 1) * 32) < 0) bin[j] = NG + (lane & (NDUM - 1));
        }
        if (EDGE) load_edge(r + 1);
        else loads();
        const uint32_t init = h::init(R), lim = init + ((EDGE && r == RT - 1 ? h::S : h::CAP) << h::SH);
        TKS(0)
        mbar_wait(sb + B_OPEN, ~R & 1);
        TKS(1)
        bool freed = false;
        uint32_t over = 0;
#pragma unroll
        for (int g = 0; g < 2 * NP; g += G1) if (!g || EDGE || !half) {
            constexpr int G = G1;
            uint32_t ret[G];
            int mx = 0;
#pragma unroll
            for (int j = 0; j < G; j++) if (g + j < 2 * NP) ret[j] = atoms_add<h::CNT>(sb + imul(bin[g + j], 4.f), h::INC);
#pragma unroll
            for (int j = 0; j < G; j++) if (g + j < 2 * NP) mx = j ? max(mx, (int)ret[j]) : (int)ret[j];
            if (!freed && __any_sync(0xffffffffu, mx >= (int)(init + 0x10000u))) { TKS(2) mbar_wait(sb + B_FREE, ~R & 1); freed = true; TKS(3) }
            TKS(2)
#pragma unroll
            for (int j = 0; j < G; j++) if (g + j < 2 * NP) {
                x[g + j] = and_or<h::TAG>(ret[j], x[g + j]);
                put_rec<h::STG>(ret[j], lim, sb + and_or<0x20000u | h::PM>(ret[j], imul(bin[g + j], 256.f)), x[g + j], y[g + j]);
            }
            if (RARE(mx >= (int)lim)) {
#pragma unroll
                for (int j = 0; j < G; j++) if (g + j < 2 * NP && (int)ret[j] >= (int)lim) over |= 1u << (g + j);
            }
        }
        __syncwarp();
        if (elect()) mbar_arrive(sb + B_FULL);
        R++;
        TKS(4)
#pragma unroll 1
        while (RARE(over)) {
            TK_CNT(7)
            const int j = __ffs(over) - 1;
            over &= over - 1;
            slow_rec1(p, pick(j, x), pick(j, y), pick(j, bin));
        }
        __syncwarp();
    };
#pragma unroll 1
    for (int q = opaque(((NB + blockIdx.x) * NPR + pos0 + lane) >> 1), r = 1; r < p.full; r++, q += NB * NPR / 2) step(r - 1, q, BoolC<false>());
#pragma unroll 1
    for (int r = max(p.full - 1, 0); r < RT; r++) step(r, 0, BoolC<true>());
    TK_OUT
}

__device__ __forceinline__ void stage2(const Params& p, uint32_t sb, int w, int lane, int role, uint32_t base) {
    typedef H<2> h;
    const int RT = p.rounds;
    Reader<1> rd;
    rd.init(p, sb, w, lane, role, base);
    uint2 rec[J];
    rd.load(rec);
    bar_sync(BAR_TABLE, 2 * NC * 32);
    uint32_t kb = sb + 0x10000u, am = 0x10000u | h::PM;
    const float unit = __uint_as_float(__reduce_or_sync(0xffffffffu, lds32(sb + W_UNIT)));
    TK_DECL
#pragma unroll 1
    for (int r = U2 & 2 ? lane & p.zero : 0; r < RT; r++) {
        rd.check(rec, base + r, POLL_NS, lane TK_PASS);
        const uint32_t want = H<1>::tag(base + r);
        TKS(0)
        uint2 mv[J];
#pragma unroll
        for (int j = 0; j < J; j++) {
            if (GP == 1) mv[j] = lds64<OFF_M>(sb + imul(min(__byte_perm(rec[j].y, xor_and<0x8e00ffu>(rec[j].x, want), 0x7610), (uint32_t)(OFF_CNT1 - OFF_M) / 8), 8.f));
            else if (GP == 2) {
                mv[j] = make_uint2(0u, 0u);
                const uint32_t a = sb + imul(rec[j].y & 0xffffu, 8.f);
                if (!xor_and<0x8e0000u>(rec[j].x, want)) mv[j] = lds64<OFF_M>(a);
            }
            else mv[j] = lds64<OFF_M>(sb + (FI2 ? imul(rec[j].y & 0xffffu, 8.f) : (rec[j].y & 0xffffu) * 8));
        }
        uint32_t fl = 0;
#pragma unroll
        for (int j = 0; j < J; j++) fl |= mv[j].y;
        if (RARE(fl & 0x40000000u)) {
#pragma unroll 1
            for (int j = 0; j < J; j++) {
                const uint2 v = pick(j, mv), w = pick(j, rec);
                if ((v.y & 0x40000000u) && !((w.x ^ want) & 0x8e0000u)) {
                    if (v.x & 0x40000000u) slow_rec1(p, w.x, w.y, lds32(sb + W_ROLE) % NG);
                    else {
                        const float c = bf_hi(w.y), s = __uint_as_float(lds32(sb + W_UNIT)) * 1024.f;
                        side_add(w.x & 0xffu, __byte_perm(w.x, 0u, 0x4413) >> 3, c * (bf_lo(v.x) * s), c * (bf_hi(v.x) * s),
                                 c * (bf_lo(v.y) * s), c * (bf_hi(v.y & 0xbfffffffu) * s));
                    }
                }
            }
#pragma unroll
            for (int j = 0; j < J; j++) if (mv[j].y & 0x40000000u) rec[j].x = 0x800000u;
        }
        uint32_t w0[J], w1[J], bin[J], ret[J];
#pragma unroll
        for (int j = 0; j < J; j++) {
            const float c = bf_hi(rec[j].y), MG = 8194.0f;
            const uint32_t x = rec[j].x;
            const float v[4] = {bf_lo(mv[j].x), bf_hi(mv[j].x), bf_lo(mv[j].y), bf_hi(mv[j].y)};
            w0[j] = and_or<0xf000f000u>(x, __byte_perm(__float_as_uint(fmaf(c, v[0], MG)), __float_as_uint(fmaf(c, v[1], MG)), 0x5410));
            w1[j] = and_or<0xf000f000u>(x << 4, __byte_perm(__float_as_uint(fmaf(c, v[2], MG)), __float_as_uint(fmaf(c, v[3], MG)), 0x5410));
            bin[j] = min(xor_and<0x8e00ffu>(x, want), NB + (lane & (NDUM - 1)));
        }
        const uint32_t lim = h::init(base + r) + (r == RT - 1 ? 0x10000u : 0x20000u);
        rd.load(rec);
        TKS(1)
        mbar_wait(sb + B_OPEN + 8, (r - 1) & 1);
        TKS(2)
#pragma unroll
        for (int j = 0; j < J; j++) ret[j] = atoms_add<h::CNT>(sb + (FI2 ? imul(bin[j], 4.f) : bin[j] * 4), h::INC);
        uint32_t mx = 0;
#pragma unroll
        for (int j = 0; j < J; j++) {
            w1[j] = and_or<h::TAG>(ret[j], w1[j]);
            put_rec<0>(ret[j], lim, and_xor(ret[j], am, FI2 == 2 ? ifma(bin[j], 128.f, kb) : bin[j] * 128 + kb), w0[j], w1[j]);
            mx = __viaddmax_u32(ret[j], 0u - DUMMY, mx);
        }
        __syncwarp();
        if (lane == 0) mbar_arrive(sb + B_FULL + 8);
        TKS(3)
        if (RARE(mx >= lim - DUMMY)) {
            uint32_t over = 0;
#pragma unroll
            for (int j = 0; j < J; j++) if (ret[j] - DUMMY >= lim - DUMMY) over |= 1u << j;
#pragma unroll 1
            do {
                const int j = __ffs(over) - 1;
                over &= over - 1;
                const uint32_t b = pick(j, bin), v = pick(j, ret) - lim, e = v >> h::SH, at = ((v - e * h::INC - (b & 7u) * 16u - h::CAP * 8) >> 7) + e;
                if (XB != 1 && XB != 2 && max(at, e) < BOXN && r < RT - LATE) g_box[(b * NB + role) * BOX + at] = make_uint2(pick(j, w0), pick(j, w1) | h::TAG);
                else slow_rec2(p, pick(j, w0), pick(j, w1), b, unit);
            } while (over);
        }
        __syncwarp();
        am = am >= 0x30000u ? 0x10000u | h::PM : am + 0x10000u;
        kb ^= am & 0x30000u;
        TKS(4)
    }
    rd.finish();
    TK_OUT
}

__device__ __forceinline__ void add_recs(uint32_t sb, int lane, const uint2 (&rec)[J], uint32_t want) {
    const uint32_t t = 0u - (lane & 1u), k = (t & 1u << 26) - (want >> 4);
    uint32_t o0[J], o1[J], g = 0;
#pragma unroll
    for (int j = 0; j < J; j++) {
        o0[j] = 0; o1[j] = 0;
        if (NS3 ? xor_and<0x7fffffffu>(rec[j].y, want) < 0x0ffc0000u : !xor_and<H<2>::TAG>(rec[j].y, want)) {
            const uint32_t a = aux_of(rec[j].x, rec[j].y, k);
            const uint32_t v0 = (rec[j].x & 0x0fff0fffu) - 0x08000800u, v1 = (rec[j].y & 0x0fff0fffu) - 0x08000800u;
            o0[j] = atoms_add<OFF_ACC>(sb + a, mux(v0, v1, t));
            o1[j] = atoms_add<OFF_ACC>(sb + (a ^ 4u), mux(v1, v0, t));
        }
    }
#pragma unroll
    for (int j = 0; j < J; j++) g |= o0[j] | o1[j];
    if (RARE(__any_sync(0xffffffffu, g & 0x80008000u))) {
#pragma unroll 1
        for (int j = 0; j < J; j++) {
            const uint2 w = pick(j, rec);
            const uint32_t aux = aux_of(w.x, w.y), p0 = pick(j, o0), p1 = pick(j, o1);
            const float2 a = acc_fix(t ? p1 : p0, w.x & 0x0fff0fffu), b = acc_fix(t ? p0 : p1, w.y & 0x0fff0fffu);
            const float unit = __uint_as_float(lds32(sb + W_UNIT));
            if ((NS3 ? xor_and<0x7fffffffu>(w.y, want) < 0x0ffc0000u : !((w.y ^ want) & H<2>::TAG)) && (a.x != 0.f || a.y != 0.f || b.x != 0.f || b.y != 0.f)) {
                side_add(lds32(sb + W_ROLE), aux >> 3, a.x * unit, a.y * unit, b.x * unit, b.y * unit);
                sts32(sb + W_WRAP, 1u);
            }
            __syncwarp();
        }
    }
}
__device__ __forceinline__ void stage3(const Params& p, uint32_t sb, int w, int lane, int role, uint32_t base) {
    const int RT = p.rounds;
    Reader<2> rd;
    rd.init(p, sb, w, lane, role, base);
    uint2 rec[J];
    bar_sync(BAR_TABLE, 2 * NC * 32);
    TK_DECL
#pragma unroll 1
    for (int r = U3 & 2 ? lane & p.zero : 0; r < RT; r++) {
        rd.load(rec);
        rd.check(rec, base + r, r < RT - 2 ? POLL_NS3 : 100, lane TK_PASS);
        RTS((r & 127) == 40 && w == 0, 1 + (r >> 7))
        TK(0)
        add_recs(sb, lane, rec, H<2>::tag(base + r));
        TK(1)
        if (RARE((uint32_t)(r - (RT - LATE + 1)) < 2u)) {
            static_assert(BOX == 32, "box");
            float4* box = reinterpret_cast<float4*>(g_box) + (lds32(sb + W_ROLE) * NB + (w * 2 + r - (RT - LATE + 1)) * J) * (BOX / 2) + lane;
            TKY(0)
#pragma unroll
            for (int j = 0; j < J / 2; j++) {
                const float4 v = ld_rlx128f(box + j * 32);
                rec[2 * j] = make_uint2(__float_as_uint(v.x), __float_as_uint(v.y)); rec[2 * j + 1] = make_uint2(__float_as_uint(v.z), __float_as_uint(v.w));
            }
#pragma unroll
            for (int j = 0; j < J / 2; j++) if (rec[2 * j].x) box[j * 32] = make_float4(0.f, 0.f, 0.f, 0.f);
            add_recs(sb, lane, rec, H<2>::TAG);
            TKY(1)
        }
    }
    rd.finish();
    TK_OUT
}

__device__ __forceinline__ uint32_t row_max(uint32_t x, uint32_t y) {
    const uint32_t mx = __vmaxu2(x & 0x7fff7fffu, y & 0x7fff7fffu);
    return max(mx & 0xffffu, mx >> 16);
}
constexpr int NTAB = 3, TABC = 3 * 2 * NC * 32 * 16;
static_assert(NTAB * TABC >= R1MAX * 8, "table");
constexpr int EWIN = 5;

__global__ void __launch_bounds__(NTHR, 1) fused_kernel(const Params p) {
    const int tid = threadIdx.x, lane = tid & 31;
    const int hw = __reduce_max_sync(0xffffffffu, tid >> 5);
    const uint32_t sb = __reduce_or_sync(0xffffffffu, (uint32_t)__cvta_generic_to_shared(smem));
    TKX(0)
    RTS(tid == 0, 0)
    uint32_t cta;
    asm volatile("mov.u32 %0, %%ctaid.x;" : "=r"(cta));
    if (hw != W_M1 && hw != W_M2) {
        const int job = hw < W_M1 ? hw : hw - 1;
        if (lane == 0 && job < 2 * NPAGE + 2)
            sts32(sb + OFF_PROBE + job * 4, probe(p.ring + (size_t)max(job / 2 - 1, 0) * PAGE + PROBE + (cta & 31) * 128 + (cta >> 5 & 3) * 16384 + (cta >> 7 << 20) +
                                                  ((job & 1) << 12 ^ (job < 2 ? 0x3000 : 0)), p.zero));
        if (job < 4) bar_arrive(BAR_SIDE, 5 * 32); else bar_arrive(BAR_PROBE, 27 * 32);
        TKX(1)
    }
    if (hw < NS1) {
        stage1(p, sb, hw * 128 + lane, lane, hw == NS1 - 1);
    } else if (hw == W_M1) {
        const uint32_t epoch = ld_rlx32(&g_base);
        if (lane == 0) {
            if (sb & 255u) __trap();
            mbar_init(sb + B_FULL, NS1); mbar_init(sb + B_OPEN, 1); mbar_init(sb + B_FREE, 1);
            for (int i = 0; i < NTAB; i++) mbar_init(sb + B_TAB + i * 8, 1);
            asm volatile("fence.proxy.async.shared::cta;" ::: "memory");
        }
        const uint32_t base = __reduce_or_sync(0xffffffffu, epoch) & 31u;
        if (lane == 0) { sts32(sb + W_BASE, base); sts64(sb + W_NLIST, 0u, 0u); }
        if (lane == 0 && (base & 1u)) { mbar_arrive(sb + B_OPEN); mbar_arrive(sb + B_FREE); }
        for (int i = lane; i < NG + NDUM; i += 32) sts32(sb + OFF_CNT1 + i * 4, i < NG ? H<1>::init(base) + (i & 7) * 16 : DUMMY);
#pragma unroll 1
        for (int i = 0; i < 2; i++) fill<1>(sb + OFF_H1 + H<1>::win(base + i), lane, base + i);
        bar_arrive(BAR_S1, (NS1 + 1) * 32);
        bar_sync(BAR_SIDE, 5 * 32);
        {
            const uint2 la = lds64<OFF_PROBE>(sb), lb = lds64<OFF_PROBE + 8>(sb);
            const uint32_t side = min(la.y, lb.y) < min(la.x, lb.x);
            uint32_t v = 0;
            if (lane < 2) asm volatile("atom.relaxed.gpu.global.add.u32 %0, [%1], %2;" : "=r"(v) : "l"(p.ring + M_CNT + lane * 4096), "r"(side ? 0x10000u : 1u) : "memory");
            if (lane == 0) {
                const uint32_t role = side ? NB - 1 - (v >> 16) : v & 0xffffu;
                const int r0 = (role >= NG ? role - NG : role) * p.R1, nb = min(p.R1, p.E - r0) * 8;
#pragma unroll
                for (int i = 0; i < NTAB; i++) {
                    const int n = max(min(nb - i * TABC, TABC), 0);
                    asm volatile("mbarrier.arrive.expect_tx.shared::cta.b64 _, [%0], %1;" ::"r"(sb + B_TAB + i * 8), "r"(n) : "memory");
                    if (n) asm volatile("cp.async.bulk.shared::cluster.global.mbarrier::complete_tx::bytes [%0], [%1], %2, [%3];"
                                        ::"r"(sb + OFF_M + i * TABC), "l"(p.m + r0 + i * (TABC / 8)), "r"(n), "r"(sb + B_TAB + i * 8) : "memory");
                }
                sts32(sb + W_ROLE, role); sts32(sb + W_SIDE, role < NLO ? 0u : role >= NHI ? 1u : side);
                sts32(sb + W_END, (epoch | 31u) + 1u + (base + p.rounds) % 24u);
            }
            TKX(2)
            bar_sync(BAR_PROBE, 27 * 32);
            const uint2 l = lds64<OFF_PROBE + 8>(sb + min(lane, NPAGE - 1) * 8);
            const uint32_t mine = (__ballot_sync(0xffffffffu, (l.y < l.x) != side) & ~1u) | 0x80000000u;
            if (lane == 0) {
                asm volatile("atom.relaxed.gpu.global.cas.b32 %0, [%1], 0, %2;" : "=r"(v) : "l"(p.ring + M_PAR), "r"(mine) : "memory");
                sts32(sb + W_PAR, v ? v : mine);
            }
        }
        bar_arrive(BAR_PAR, (2 * NC + 2) * 32);
        manager<1>(p, sb, opaque(lane), __reduce_max_sync(0xffffffffu, lds32(sb + W_ROLE)), base);
        asm volatile("cp.async.bulk.wait_group 0;" ::: "memory");
        bar_arrive(BAR_H1, (NS1 + 1) * 32);
        TKX(4)
        {
            const int role = lds32(sb + W_ROLE);
#pragma unroll 1
            for (int i = lane * 16; i < DROW; i += 4 * 512) {
                float4 f[4];
#pragma unroll
                for (int u = 0; u < 4; u++) f[u] = ld_rlx128f(reinterpret_cast<const float4*>(g_dirty + role * DROW + i + u * 512));
#pragma unroll
                for (int u = 0; u < 4; u++) {
                    if (__float_as_uint(f[u].x) | __float_as_uint(f[u].y)) prefetch_l2(g_ovf + role * RPAD + i + u * 512);
                    if (__float_as_uint(f[u].z) | __float_as_uint(f[u].w)) prefetch_l2(g_ovf + role * RPAD + i + u * 512 + 8);
                }
            }
        }
        bar_sync(BAR_DONE, (NE + 1) * 32);
        TKY(0)
        if (lane < 2) { fence_gpu(); st_rlx32(reinterpret_cast<uint32_t*>(p.ring + M_FLAG + lane * 4096) + blockIdx.x, lds32(sb + W_END)); }
        TKY(1)
        wait_flags(p, sb, lane, lds32(sb + W_END));
        TKX(5)
        bar_arrive(BAR_FLAG, (NE + 1) * 32);
        if (blockIdx.x == 0) {
            if (lane == 0) g_base = lds32(sb + W_END);
            if (lane < 3) *reinterpret_cast<uint32_t*>(p.ring + (lane & 2 ? M_PAR : M_CNT + (lane & 1) * 4096)) = 0;
        }
    } else if (hw == W_M2) {
        const uint32_t epoch = ld_rlx32(&g_base);
        uint2 sm[16];
#pragma unroll
        for (int i = 0; i < 8; i++) ld_in4(p.m + 2 * min((i * 8 + (lane >> 2)) * (p.E >> 7) + (lane & 3), (p.E >> 1) - 1), sm[2 * i], sm[2 * i + 1]);
        const float wd = __bfloat162float(lane & 16 ? p.w_up[lane & 15] : p.w_down[lane & 15]);
        if (lane == 0) { mbar_init(sb + B_FULL + 8, NC); mbar_init(sb + B_OPEN + 8, 1); }
        sts128<OFF_HIST>(sb + lane * 16, make_uint4(0u, 0u, 0u, 0u)); sts128<OFF_HIST + 512>(sb + lane * 16, make_uint4(0u, 0u, 0u, 0u));
        __syncwarp();
#pragma unroll
        for (int i = 0; i < 16; i++) atoms_add<OFF_HIST>(sb + (row_max(sm[i].x, sm[i].y) >> 7) * 4, 1u);
        __syncwarp();
        uint32_t best = 0;
#pragma unroll 1
        for (int e = 11 + lane; e <= 230; e += 32) {
            uint32_t c = 0;
#pragma unroll
            for (int i = 0; i < EWIN; i++) c += lds32(sb + OFF_HIST + (e - i) * 4);
            best = max(best, c << 8 | (255 - e));
        }
        const uint32_t e = 255 - (__reduce_max_sync(0xffffffffu, best) & 255u);
        if (lane == 0) { sts32(sb + W_EXP, e); sts32(sb + W_UNIT, (e - 10) << 23); }
        const uint32_t base = __reduce_or_sync(0xffffffffu, epoch) & 31u;
        for (int i = lane; i <= NB + NDUM; i += 32) sts32(sb + OFF_CNT2 + i * 4, i < NB ? H<2>::init(base) + (i & 7) * 16 : DUMMY);
#pragma unroll 1
        for (int i = 0; i < 3; i++) fill<2>(sb + H<2>::win(i), lane, base + i);
        reinterpret_cast<float*>(smem + OFF_WSM)[lane] = wd;
        bar_sync(BAR_PAR, (2 * NC + 2) * 32);
        manager<2>(p, sb, opaque(lane), __reduce_max_sync(0xffffffffu, lds32(sb + W_ROLE)), base);
        TKX(4)
        asm volatile("cp.async.bulk.wait_group 0;" ::: "memory");
    } else {
        const int pw = __reduce_max_sync(0xffffffffu, hw < W_M1 ? hw - NS1 : hw - NS1 - 1), ct = pw * 32 + lane;
        constexpr int CT = 2 * NC * 32;
        bar_sync(BAR_PAR, (2 * NC + 2) * 32);
        TKY(4)
        for (int i = ct; i < R2MAX / 2; i += CT) reinterpret_cast<uint4*>(smem + OFF_ACC)[i] = make_uint4(0x40004000u, 0x40004000u, 0x40004000u, 0x40004000u);
        const int role = __reduce_max_sync(0xffffffffu, lds32(sb + W_ROLE));
        {
            const int e = lds32(sb + W_EXP);
            const uint32_t sc = (uint32_t)(254 - e) * 0x800080u;
            auto conv = [&](uint32_t& x, uint32_t& y) {
                const uint32_t mx = row_max(x, y);
                const int d = e - (int)(mx >> 7);
                x = hmul_bf2(x, sc); y = hmul_bf2(y, sc);
                if (d >= EWIN) y |= 0x40000000u;
                if (d < 0 || (d >= EWIN && e > 127)) { x = 0x40000000u; y = x; }
                if (mx == 0) { x = 0; y = 0; }
            };
#pragma unroll 1
            for (int i = 0; i < NTAB; i++) {
                mbar_wait(sb + B_TAB + i * 8, 0);
                uint4* t = reinterpret_cast<uint4*>(smem + OFF_M + i * TABC) + ct;
#pragma unroll
                for (int u = 0; u < TABC / 16 / CT; u++) if (i * TABC + (ct + u * CT) * 16 < R1MAX * 8) {
                    uint4 v = t[u * CT];
                    conv(v.x, v.y); conv(v.z, v.w);
                    t[u * CT] = v;
                }
            }
        }
        TKX(3)
        const uint32_t base = __reduce_or_sync(0xffffffffu, lds32(sb + W_BASE));
        if (hw < W_M1) {
            stage2(p, sb, pw, opaque(lane), role, U2 & 1 ? base : base + (lane & p.zero));
        } else {
            stage3(p, sb, pw - NC, opaque(lane), role, U3 & 1 ? base : base + (lane & p.zero));
            TKX(4)
            bar_arrive(BAR_ACC, (NE + NC) * 32);
        }
    }
    if (hw < W_M1) {
        bar_arrive(BAR_DONE, (NE + 1) * 32);
        TKX(4)
        finish_rows(p, sb);
    }
}

__global__ void fb_scatter(const uint2* __restrict__ m, const int* __restrict__ idx_in, const int* __restrict__ idx_out,
                           const uint16_t* __restrict__ angle, const __nv_bfloat16* __restrict__ ang_freq, int T, int e0, int e1) {
    const uint32_t fb = *reinterpret_cast<const uint16_t*>(ang_freq);
    for (long long t = blockIdx.x * (long long)blockDim.x + threadIdx.x; t < T; t += (long long)gridDim.x * blockDim.x) {
        int o = idx_out[t];
        if (o < e0 || o >= e1) continue;
        float c = bf16r(cos_bf(hmul_bf2(angle[t], fb) & 0xffffu));
        uint2 v = __ldg(m + idx_in[t]);
        red4(&g_ovf[o - e0], c * bf_lo(v.x), c * bf_hi(v.x), c * bf_lo(v.y), c * bf_hi(v.y));
    }
}
__global__ void fb_final(const Params p, int e0, int e1) {
    int e = e0 + blockIdx.x * blockDim.x + threadIdx.x;
    if (e >= e1) return;
    float4 a4 = g_ovf[e - e0];
    g_ovf[e - e0] = make_float4(0.f, 0.f, 0.f, 0.f);
    float a[4] = {a4.x, a4.y, a4.z, a4.w};
    float d = __bfloat162float(p.dist[e]);
    float g[4] = {0, 0, 0, 0}, h[4] = {0, 0, 0, 0};
    for (int r = 0; r < 8; r++) {
        float df = bf16r(d - __bfloat162float(p.centers[r]));
        float rb = bf16r(expf(bf16r(-10.0f * bf16r(df * df))));
        for (int k = 0; k < 4; k++) {
            g[k] += rb * __bfloat162float(p.w_sbf[r * 4 + k]);
            h[k] += rb * __bfloat162float(p.w_rbf[r * 4 + k]);
        }
    }
    float ag[4];
    for (int k = 0; k < 4; k++) {
        float s = 0.f;
        for (int j = 0; j < 4; j++) s += a[j] * __bfloat162float(p.w_down[j * 4 + k]);
        ag[k] = bf16r(s * g[k]);
    }
    uint2 mv = p.m[e];
    float mm[4] = {bf_lo(mv.x), bf_hi(mv.x), bf_lo(mv.y), bf_hi(mv.y)};
    __nv_bfloat16 o[4];
    for (int k = 0; k < 4; k++) {
        float u = 0.f;
        for (int j = 0; j < 4; j++) u += ag[j] * __bfloat162float(p.w_up[j * 4 + k]);
        o[k] = __float2bfloat16_rn(mm[k] + bf16r(bf16r(u) * bf16r(h[k])));
    }
    p.out[e] = *reinterpret_cast<uint2*>(o);
}

}

static cudaTextureObject_t make_tex(const void* ptr, size_t bytes, int words) {
    cudaResourceDesc rd = {}; cudaTextureDesc td = {};
    rd.resType = cudaResourceTypeLinear; rd.res.linear.devPtr = const_cast<void*>(ptr); rd.res.linear.sizeInBytes = bytes;
    rd.res.linear.desc = cudaCreateChannelDesc(32, words > 1 ? 32 : 0, words > 2 ? 32 : 0, words > 2 ? 32 : 0, cudaChannelFormatKindUnsigned);
    td.readMode = cudaReadModeElementType;
    cudaTextureObject_t t = 0;
    if (cudaCreateTextureObject(&t, &rd, &td, nullptr) != cudaSuccess) { t = 0; (void)cudaGetLastError(); }
    return t;
}

extern "C" void kernel_launch(void* const* d_in, const int* in_sizes, int n_in, void* d_out, int out_size) {
    typedef const __nv_bfloat16* B;
    Params p;
    p.m = (const uint2*)d_in[0]; p.idx_in = (const uint2*)d_in[1]; p.idx_out = (const uint2*)d_in[2]; p.dist = (B)d_in[3];
    p.angle = (const uint32_t*)d_in[4]; p.centers = (B)d_in[5]; p.ang_freq = (B)d_in[6]; p.w_rbf = (B)d_in[7]; p.w_sbf = (B)d_in[8];
    p.w_down = (B)d_in[9]; p.w_up = (B)d_in[10]; p.out = (uint2*)d_out;
    p.E = in_sizes[3]; p.T = in_sizes[1]; p.T2 = p.T >> 1; p.zero = 0;
    p.R1 = p.R2 = p.rounds = p.lastn = p.full = 0; p.i1 = p.i2 = p.k1 = p.k2 = 0.f;
    static int ok = -1;
    static unsigned char* ring = nullptr;
    if (ok < 0) {
        void* ra = nullptr;
        cudaGetSymbolAddress(&ra, g_ring);
        ring = reinterpret_cast<unsigned char*>(((uintptr_t)ra + PAGE - 1) & ~(uintptr_t)(PAGE - 1));
        int dev = 0, sms = 0, occ = 0;
        cudaGetDevice(&dev);
        cudaDeviceGetAttribute(&sms, cudaDevAttrMultiProcessorCount, dev);
        cudaError_t e = cudaFuncSetAttribute(fused_kernel, cudaFuncAttributeMaxDynamicSharedMemorySize, SMEM_BYTES);
        if (e == cudaSuccess) e = cudaOccupancyMaxActiveBlocksPerMultiprocessor(&occ, fused_kernel, NTHR, SMEM_BYTES);
        ok = (e == cudaSuccess && occ >= 1 && sms >= NB) ? 1 : 0;
        (void)cudaGetLastError();
    }
    p.ring = ring;
    static cudaTextureObject_t tx[3];
    if (!tx[0]) { tx[0] = make_tex(p.idx_in, (size_t)(p.T >> 2) * 16, 4); tx[1] = make_tex(p.idx_out, (size_t)(p.T >> 2) * 16, 4); tx[2] = make_tex(p.angle, (size_t)(p.T >> 2) * 8, 2); }
    p.ti = tx[0]; p.to = tx[1]; p.ta = tx[2];
    const bool fused = ok == 1 && p.E <= EMAX && p.E >= 2 * NB && p.E % 2 == 0 && p.T >= 2;
    if (fused) {
        p.R1 = ((p.E + NG - 1) / NG + 1) & ~1; p.R2 = ((p.E + NB - 1) / NB + 1) & ~1;
        p.i1 = nextafterf(1.f / p.R1, 2.f); p.i2 = nextafterf(1.f / p.R2, 2.f); p.k1 = -(float)p.R1; p.k2 = -8.f * p.R2;
        const int per = NB * NPR;
        int full = p.T2 / per, rest = p.T2 - full * per;
        p.full = full;
        p.lastn = (rest + NB - 1) / NB;
        if (p.lastn > NPR / 2) { full++; p.lastn = 0; }
        if (full < D) { full = D; p.lastn = 0; }
        p.rounds = full + 1;
        fused_kernel<<<NB, NTHR, SMEM_BYTES>>>(p);
    } else {
        for (int e0 = 0; e0 < p.E; e0 += EMAX) {
            int e1 = p.E - e0 < EMAX ? p.E : e0 + EMAX;
            fb_scatter<<<1056, 256>>>(p.m, (const int*)d_in[1], (const int*)d_in[2], (const uint16_t*)d_in[4], p.ang_freq, p.T, e0, e1);
            fb_final<<<(e1 - e0 + 255) / 256, 256>>>(p, e0, e1);
        }
    }
}
```

```cpp
#include <cuda_runtime.h>
#include <cuda_bf16.h>
#include <stdint.h>
#include <math.h>

#define RARE(x) __builtin_expect(!!(x), 0)
namespace {

constexpr int NB = 132, NG = 66;
constexpr int R2MAX = 6062, R1MAX = 12124;
constexpr int EMAX = NB * R2MAX;
constexpr int NTHR = 1024;
constexpr int NS1 = 8, NC = 11, J = 6;
constexpr int NPR = 960;
constexpr int D = 3;
constexpr int WIN = 16896;
constexpr int NDUM = 16;
constexpr uint32_t DUMMY = 0xc0000000u;

constexpr int OFF_ACC = WIN, OFF_BAR = OFF_ACC + R2MAX * 8;
constexpr int OFF_H1 = 0x10000 + WIN, OFF_M = OFF_H1 + WIN, OFF_WSM = OFF_M + R1MAX * 8;
constexpr int OFF_CNT1 = OFF_H1 + 0x20000 + WIN, OFF_CNT2 = OFF_CNT1 + (NG + NDUM + 2) * 4;
constexpr int OFF_HIST = OFF_ACC;
constexpr int OFF_PROBE = OFF_WSM + 128;
constexpr int SMEM_BYTES = OFF_CNT2 + (NB + NDUM) * 4 + 16;
static_assert(SMEM_BYTES <= 232448 && OFF_BAR + 64 <= 0x10000 && OFF_PROBE + 160 <= 0x30000, "smem");
static_assert(OFF_BAR % 8 == 0 && OFF_WSM % 16 == 0 && OFF_CNT2 % 16 == 0, "align");
static_assert(NC * J == NG && NC * 32 * 6 * 16 == 2 * WIN, "shape");

template <int HOP> struct H {
    static constexpr int S = HOP == 1 ? 32 : 16, NBIN = HOP == 1 ? NG : NB, CAP = 2 * S, SH = HOP == 1 ? 11 : 12;
    static constexpr int TB = HOP == 1 ? 17 : 28, CNT = HOP == 1 ? OFF_CNT1 : OFF_CNT2, STG = HOP == 1 ? OFF_H1 : 0;
    static constexpr uint32_t INC = (1u << SH) + 8u, PM = (S - 1) * 8, TAG = 7u << TB;
    static __device__ __forceinline__ uint32_t tag(uint32_t R) { return R << TB & TAG; }
    static __device__ __forceinline__ uint32_t init(uint32_t R) { return tag(R) | ((1u << TB) - 0x10000u); }
    static __device__ __forceinline__ uint32_t mark(uint32_t R, uint32_t line) { return ((HOP == 1 ? R >> 1 : R) + line) & 3u; }
    static __device__ __forceinline__ uint32_t win(int r) { return HOP == 1 ? (r & 1) << 17 : (0x310u >> (r % 3 * 4) & 3u) << 16; }
};

constexpr uint32_t PAGE = 1u << 21;
constexpr int NPAGE = NC + 2;
__device__ __align__(256) unsigned char g_ring[(size_t)(NPAGE + 1) * PAGE];
constexpr int MISC = 0xa0000;
constexpr int M_CNT = MISC + 1024, M_PAR = MISC + 1088;
constexpr int M_FLAG = MISC + 2048;
constexpr int PROBE = MISC + 0x40000;
__device__ __forceinline__ uint32_t cred_off(uint32_t role) { return role * 4 + min(role >> 5, 3u) * (16384 - 128); }
struct Ring {
    uint64_t main, mid;
    uint32_t par;
    __device__ __forceinline__ Ring(const unsigned char* ring, uint32_t pars, int k) {
        main = reinterpret_cast<uint64_t>(ring) + ((uint64_t)k << 20);
        par = pars >> (k >> 1) & 1u;
        mid = reinterpret_cast<uint64_t>(ring) + (uint64_t)NC * PAGE + (((k >> 3 << 20) + (k >> 2 & 1) * 0x11000u + (k & 1) * 2048) ^ (k >> 1 & 1) * 0x3000u ^ (pars >> (NC + (k >> 4)) & 1u) << 12);
    }
};
constexpr int NLO = 60, NHI = 72;
__host__ __device__ constexpr uint32_t src_off(int j) { return (j % 3) << 14 | (j / 3) << 18; }
__device__ __forceinline__ uint32_t slot_off(uint32_t s) { return (0xa930u >> s * 4 & 15u) << 16; }
__device__ __forceinline__ uint32_t slot_steps(uint32_t R) { return (uint32_t)(0x30a09030aull >> (2 - R % 3) * 8) & 0xffffffu; }
__device__ __forceinline__ void slot_next(uint32_t& a, uint32_t st) { a ^= st & 0xf0000u; }
__device__ __forceinline__ uint32_t slot_rot(uint32_t st) { return __byte_perm(st, 0u, 0x4102); }
constexpr int RPAD = 6064, DROW = 6144;
__device__ __align__(128) uint8_t g_dirty[NB * DROW];
constexpr int BOX = 32, BOXN = 24, LATE = 8;
__device__ __align__(128) uint2 g_box[NB * NB * BOX];
__device__ uint32_t g_base = 1;
__device__ __align__(128) float4 g_ovf[NB * RPAD];

struct Params {
    const uint2* m; const uint2* idx_in; const uint2* idx_out; const __nv_bfloat16* dist; const uint32_t* angle;
    const __nv_bfloat16* centers; const __nv_bfloat16* ang_freq; const __nv_bfloat16* w_rbf; const __nv_bfloat16* w_sbf;
    const __nv_bfloat16* w_down; const __nv_bfloat16* w_up; uint2* out; unsigned char* ring;
    cudaTextureObject_t ti, to, ta;
    int E, T, T2, R1, R2, rounds, lastn, full; uint32_t zero; float i1, i2, k1, k2;
};

__device__ __forceinline__ float bf16r(float x) { return __bfloat162float(__float2bfloat16_rn(x)); }
__device__ __forceinline__ float bf_lo(uint32_t v) { return __uint_as_float(v << 16); }
__device__ __forceinline__ float bf_hi(uint32_t v) { return __uint_as_float(v & 0xffff0000u); }
__device__ __forceinline__ void red4(float4* a, float x, float y, float z, float w) {
    asm volatile("red.global.add.v4.f32 [%0], {%1,%2,%3,%4};" ::"l"(a), "f"(x), "f"(y), "f"(z), "f"(w) : "memory");
}
__device__ __forceinline__ void bar_sync(int id, int n) { __syncwarp(); asm volatile("bar.sync %0, %1;" ::"r"(id), "r"(n) : "memory"); }
__device__ __forceinline__ void bar_arrive(int id, int n) { __syncwarp(); asm volatile("bar.arrive %0, %1;" ::"r"(id), "r"(n) : "memory"); }
template <int OFF> __device__ __forceinline__ uint32_t atoms_add(uint32_t addr, uint32_t v) {
    uint32_t r; asm volatile("atom.shared.add.u32 %0, [%1+%3], %2;" : "=r"(r) : "r"(addr), "r"(v), "n"(OFF) : "memory"); return r;
}
__device__ __forceinline__ void sts64(uint32_t addr, uint32_t x, uint32_t y) {
    asm volatile("st.shared.v2.u32 [%0], {%1,%2};" ::"r"(addr), "r"(x), "r"(y) : "memory");
}
__device__ __forceinline__ void sts32(uint32_t addr, uint32_t x) { asm volatile("st.shared.u32 [%0], %1;" ::"r"(addr), "r"(x) : "memory"); }
template <int OFF = 0> __device__ __forceinline__ uint2 lds64(uint32_t addr) {
    uint2 v; asm volatile("ld.shared.v2.u32 {%0,%1}, [%2+%3];" : "=r"(v.x), "=r"(v.y) : "r"(addr), "n"(OFF) : "memory"); return v;
}
__device__ __forceinline__ uint32_t lds32(uint32_t addr) {
    uint32_t v; asm volatile("ld.shared.u32 %0, [%1];" : "=r"(v) : "r"(addr) : "memory"); return v;
}
template <int OFF> __device__ __forceinline__ void sts128(uint32_t a, const uint4& v) {
    asm volatile("st.shared.v4.u32 [%0+%5], {%1,%2,%3,%4};" ::"r"(a), "r"(v.x), "r"(v.y), "r"(v.z), "r"(v.w), "n"(OFF) : "memory");
}
__device__ __forceinline__ uint4 lds128(uint32_t a) {
    uint4 v; asm volatile("ld.shared.v4.u32 {%0,%1,%2,%3}, [%4];" : "=r"(v.x), "=r"(v.y), "=r"(v.z), "=r"(v.w) : "r"(a) : "memory"); return v;
}
__device__ __forceinline__ uint32_t ld_rlx32(const uint32_t* p) {
    uint32_t v; asm volatile("ld.relaxed.gpu.global.u32 %0, [%1];" : "=r"(v) : "l"(p) : "memory"); return v;
}
__device__ __forceinline__ uint2 ld_rlx64(const void* p) {
    uint2 v; asm volatile("ld.relaxed.gpu.global.v2.u32 {%0,%1}, [%2];" : "=r"(v.x), "=r"(v.y) : "l"(p) : "memory"); return v;
}
__device__ __forceinline__ float4 ld_rlx128f(const float4* p) {
    float4 v; asm volatile("ld.relaxed.gpu.global.v4.f32 {%0,%1,%2,%3}, [%4];" : "=f"(v.x), "=f"(v.y), "=f"(v.z), "=f"(v.w) : "l"(p) : "memory"); return v;
}
__device__ __forceinline__ float4 take(float4* p, bool q) {
    float4 v;
    asm volatile("{ .reg .b128 a; .reg .b64 x, y; .reg .pred q; mov.b64 x, 0; mov.b128 a, {x, x}; setp.ne.u32 q, %5, 0;\n"
                 "@q atom.relaxed.gpu.global.exch.b128 a, [%4], a; mov.b128 {x, y}, a; mov.b64 {%0,%1}, x; mov.b64 {%2,%3}, y; }"
                 : "=f"(v.x), "=f"(v.y), "=f"(v.z), "=f"(v.w) : "l"(p), "r"((uint32_t)q) : "memory");
    return v;
}
__device__ __forceinline__ void fence_gpu() { asm volatile("fence.acq_rel.gpu;" ::: "memory"); }
__device__ __forceinline__ void st_rlx32(uint32_t* p, uint32_t v) { asm volatile("st.relaxed.gpu.global.u32 [%0], %1;" ::"l"(p), "r"(v) : "memory"); }
__device__ __forceinline__ uint32_t hmul_bf2(uint32_t a, uint32_t b) {
    uint32_t r; asm("mul.rn.bf16x2 %0, %1, %2;" : "=r"(r) : "r"(a), "r"(b)); return r;
}
__device__ __forceinline__ uint32_t hsub_bf2(uint32_t a, uint32_t b) {
    uint32_t r; asm("sub.rn.bf16x2 %0, %1, %2;" : "=r"(r) : "r"(a), "r"(b)); return r;
}
__device__ __forceinline__ uint32_t hadd_bf2(uint32_t a, uint32_t b) {
    uint32_t r; asm("add.rn.bf16x2 %0, %1, %2;" : "=r"(r) : "r"(a), "r"(b)); return r;
}
__device__ __forceinline__ int opaque(int v) { return __shfl_sync(0xffffffffu, v, threadIdx.x); }
constexpr int SPIN_LIMIT = 1 << 22;

__constant__ uint32_t c_inv2pi[8] = {0u, 0x28be60dbu, 0x9391054au, 0x7f09d5f4u, 0x7d4d3770u, 0x36d8a566u, 0x4f10e410u, 0x7f9458eau};
constexpr uint32_t BIGX = 0x4280u;
__device__ __forceinline__ float cos_big(uint32_t xb) {
    uint32_t e = (xb >> 7) & 0xffu, M = (xb & 0x7fu) | 0x80u;
    uint32_t pp = e - 102u;
    uint32_t wi = pp >> 5;
    uint32_t t0 = c_inv2pi[wi], t1 = c_inv2pi[wi + 1], t2 = c_inv2pi[wi + 2];
    uint32_t f = M * __funnelshift_l(t1, t0, pp) + __umulhi(M, __funnelshift_l(t2, t1, pp));
    float c = __cosf((float)(int)f * 1.4629180792671596e-9f);
    return e == 255u ? __uint_as_float(0x7fc00000u) : c;
}
__device__ __forceinline__ float cos_bf(uint32_t xb) {
    return (xb & 0x7fffu) > BIGX ? cos_big(xb) : __cosf(__uint_as_float(xb << 16));
}
__device__ __forceinline__ uint32_t pack_bf2(float lo, float hi) {
    uint32_t r; asm("cvt.rn.bf16x2.f32 %0, %1, %2;" : "=r"(r) : "f"(hi), "f"(lo)); return r;
}
template <int N> __device__ __forceinline__ uint32_t pick(int k, const uint32_t (&a)[N]) {
    uint32_t v = a[0];
#pragma unroll
    for (int i = 1; i < N; i++) if (k == i) v = a[i];
    return v;
}
template <int N> __device__ __forceinline__ uint2 pick(int k, const uint2 (&a)[N]) {
    uint2 v = a[0];
#pragma unroll
    for (int i = 1; i < N; i++) if (k == i) v = a[i];
    return v;
}
__device__ __forceinline__ uint32_t imul(uint32_t a, float s) { uint32_t r; asm("mul.rz.f32 %0, %1, %2;" : "=r"(r) : "r"(a), "f"(s)); return r; }
__device__ __forceinline__ uint32_t ifma(uint32_t a, float s, uint32_t c) { uint32_t r; asm("fma.rn.f32 %0, %1, %2, %3;" : "=r"(r) : "r"(a), "f"(s), "r"(c)); return r; }
__device__ __forceinline__ void side_add(uint32_t bin, uint32_t row, float a, float b, float c, float d) {
    red4(&g_ovf[bin * RPAD + row], a, b, c, d);
    g_dirty[bin * DROW + row] = 1;
}
__device__ __forceinline__ void slow_triplet(const Params& p, uint32_t ii, uint32_t oo, float c) {
    const uint2 v = __ldg(p.m + ii);
    const uint32_t bo = imul(oo, p.i2);
    side_add(bo, oo - bo * p.R2, c * bf_lo(v.x), c * bf_hi(v.x), c * bf_lo(v.y), c * bf_hi(v.y));
}
__device__ __forceinline__ void slow_rec1(const Params& p, uint32_t x, uint32_t y, uint32_t bin) {
    const uint2 v = __ldg(p.m + bin * p.R1 + (y & 0xffffu));
    const float c = bf_hi(y);
    side_add(x & 0xffu, __byte_perm(x, 0u, 0x4413) >> 3, c * bf_lo(v.x), c * bf_hi(v.x), c * bf_lo(v.y), c * bf_hi(v.y));
}
__device__ __forceinline__ uint32_t aux_of(uint32_t w0, uint32_t w1, uint32_t k = 0) {
    uint32_t u; asm("lop3.b32 %0, %1, %2, 0xf000f000, 0xe4;" : "=r"(u) : "r"(w0), "r"((w1 >> 4) + k));
    return __byte_perm(u, 0u, 0x4413);
}
__device__ __forceinline__ void slow_rec2(const Params& p, uint32_t w0, uint32_t w1, uint32_t bin, float unit) {
    side_add(bin, aux_of(w0, w1) >> 3, (float)((int)(w0 & 0xfffu) - 2048) * unit, (float)((int)(w0 >> 16 & 0xfffu) - 2048) * unit,
             (float)((int)(w1 & 0xfffu) - 2048) * unit, (float)((int)(w1 >> 16 & 0xfffu) - 2048) * unit);
}
template <uint32_t M> __device__ __forceinline__ uint32_t and_or(uint32_t a, uint32_t c) {
    uint32_t r; asm("lop3.b32 %0, %1, %2, %3, 0xea;" : "=r"(r) : "r"(a), "n"(M), "r"(c)); return r;
}
template <uint32_t M> __device__ __forceinline__ uint32_t xor_and(uint32_t a, uint32_t c) {
    uint32_t r; asm("lop3.b32 %0, %1, %2, %3, 0x48;" : "=r"(r) : "r"(a), "n"(M), "r"(c)); return r;
}
__device__ __forceinline__ uint32_t mux(uint32_t a, uint32_t b, uint32_t m) {
    uint32_t r; asm("lop3.b32 %0, %1, %2, %3, 0xd8;" : "=r"(r) : "r"(a), "r"(b), "r"(m)); return r;
}
__device__ __forceinline__ uint32_t and_xor(uint32_t a, uint32_t m, uint32_t c) {
    uint32_t r; asm("lop3.b32 %0, %1, %2, %3, 0x6a;" : "=r"(r) : "r"(a), "r"(m), "r"(c)); return r;
}
__device__ __forceinline__ uint2 ld_in(const uint2* a) {
    uint2 v; asm volatile("ld.global.nc.L1::no_allocate.v2.u32 {%0,%1}, [%2];" : "=r"(v.x), "=r"(v.y) : "l"(a)); return v;
}
__device__ __forceinline__ uint32_t ld_in(const uint32_t* a) {
    uint32_t v; asm volatile("ld.global.nc.L1::no_allocate.u32 %0, [%1];" : "=r"(v) : "l"(a)); return v;
}
__device__ __forceinline__ void ld_in4(const uint2* p, uint2& a, uint2& b) {
    asm volatile("ld.global.nc.L1::no_allocate.v4.u32 {%0,%1,%2,%3}, [%4];" : "=r"(a.x), "=r"(a.y), "=r"(b.x), "=r"(b.y) : "l"(p));
}
__device__ __forceinline__ void tex4(cudaTextureObject_t t, int i, uint2& a, uint2& b) {
    asm volatile("tex.1d.v4.u32.s32 {%0,%1,%2,%3}, [%4, {%5}];" : "=r"(a.x), "=r"(a.y), "=r"(b.x), "=r"(b.y) : "l"(t), "r"(i));
}
__device__ __forceinline__ void tex2(cudaTextureObject_t t, int i, uint32_t& a, uint32_t& b) {
    asm volatile("{ .reg .b32 z, w; tex.1d.v4.u32.s32 {%0,%1,z,w}, [%2, {%3}]; }" : "=r"(a), "=r"(b) : "l"(t), "r"(i) : "memory");
}
template <int OFF> __device__ __forceinline__ void put_rec(uint32_t ret, uint32_t lim, uint32_t addr, uint32_t x, uint32_t y) {
    asm volatile("{ .reg .pred q; setp.lt.u32 q, %0, %1; @q st.shared.v2.u32 [%2+%5], {%3,%4}; }" ::"r"(ret), "r"(lim), "r"(addr), "r"(x), "r"(y), "n"(OFF) : "memory");
}
__device__ __forceinline__ uint32_t mbar_try(uint32_t mb, uint32_t parity) {
    uint32_t ok;
    asm volatile("{ .reg .pred q; mbarrier.try_wait.parity.shared::cta.b64 q, [%1], %2; selp.u32 %0, 1, 0, q; }" : "=r"(ok) : "r"(mb), "r"(parity) : "memory");
    return ok;
}
__device__ __forceinline__ void mbar_wait(uint32_t mb, uint32_t parity) {
    if (!mbar_try(mb, parity)) {
        int it = 0;
        while (!mbar_try(mb, parity)) if (++it > SPIN_LIMIT) __trap();
    }
}
__device__ __forceinline__ void mbar_init(uint32_t mb, uint32_t n) { asm volatile("mbarrier.init.shared::cta.b64 [%0], %1;" ::"r"(mb), "r"(n) : "memory"); }
__device__ __forceinline__ void mbar_arrive(uint32_t mb) { asm volatile("mbarrier.arrive.shared::cta.b64 _, [%0];" ::"r"(mb) : "memory"); }
constexpr int B_FULL = OFF_BAR, B_OPEN = OFF_BAR + 16, B_FREE = OFF_BAR + 32;
constexpr int W_END = OFF_BAR + 40, W_SIDE = OFF_BAR + 44, W_PAR = OFF_BAR + 48, W_ROLE = OFF_BAR + 52, W_EXP = OFF_BAR + 56, W_UNIT = OFF_BAR + 60, W_NLIST = OFF_PROBE + 112, W_WRAP = OFF_PROBE + 116, W_BASE = OFF_PROBE + 120, B_TAB = OFF_PROBE + 128;
enum { BAR_S1 = 1, BAR_SIDE, BAR_PROBE, BAR_PAR, BAR_TABLE, BAR_DONE, BAR_TFREE, BAR_ACC, BAR_FLAG, BAR_H1 };
constexpr int W_M1 = NS1 + NC, W_M2 = 31;

extern __shared__ __align__(1024) unsigned char smem[];
#define RTS(c, i)
#define TK_DECL
#define TK(i)
#define TK_CNT(i)
#define TK_OUT
#define TK_ARG
#define TK_PASS
#define TKS(i) TK(i)
#define TKX(i)
#define TKY(i) {}
#define TKZ(i, d)

__device__ __forceinline__ void prefetch_l2(const void* a) { asm volatile("prefetch.global.L2 [%0];" ::"l"(a)); }
__device__ __forceinline__ void wait_flags(const Params& p, uint32_t sb, int lane, uint32_t need) {
    const unsigned char* f = p.ring + M_FLAG + (lds32(sb + W_SIDE) << 12);
    int it = 0;
    while (true) {
        uint32_t a[5];
        asm volatile("ld.acquire.gpu.global.v4.u32 {%0,%1,%2,%3}, [%4];" : "=r"(a[0]), "=r"(a[1]), "=r"(a[2]), "=r"(a[3]) : "l"(f + lane * 16) : "memory");
        asm volatile("ld.acquire.gpu.global.u32 %0, [%1];" : "=r"(a[4]) : "l"(f + 512 + (lane & 3) * 4) : "memory");
        const uint32_t d = (a[0] ^ need) | (a[1] ^ need) | (a[2] ^ need) | (a[3] ^ need) | (a[4] ^ need);
        if (__all_sync(0xffffffffu, d == 0)) break;
        __nanosleep(50);
        if (++it > SPIN_LIMIT) __trap();
    }
}
__device__ __forceinline__ float exp_fast(float x) { float r; asm("ex2.approx.ftz.f32 %0, %1;" : "=f"(r) : "f"(x * 1.4426950408889634f)); return r; }
constexpr uint32_t BIAS = 0x3d803d80u, ZERO = 0x7d80u;
__device__ __forceinline__ float2 acc_fix(uint32_t old, uint32_t q) {
    const uint32_t u = old + BIAS, n = u + q - 0x08000800u;
    return make_float2((float)((int)(u & 0xffffu) + (int)(q & 0xffffu) - 2048 - (int)(n & 0xffffu)), (float)((int)(u >> 16) + (int)(q >> 16) - 2048 - (int)(n >> 16)));
}
constexpr int NE = NS1 + NC, NPAIR = (R2MAX / 2 + NE * 32 - 1) / (NE * 32), NTILE = 15, NG0 = NS1 * 8 * NTILE;
constexpr int OFF_G = OFF_M, GH = R2MAX * 8, OFF_LIST = OFF_G;
static_assert(2 * R2MAX <= R1MAX && NG0 * 16 <= WIN && NG0 + NE * 8 * NTILE >= R2MAX / 2 && NPAIR * NE * 64 <= DROW, "gates");
__device__ __forceinline__ int gate_g(int k) { return (k < NG0 ? OFF_H1 : OFF_G) + k * 16; }
__device__ __forceinline__ int gate_h(int k) { return (k < NG0 ? OFF_H1 + 0x20000 : OFF_G + GH) + k * 16; }
__device__ __forceinline__ uint2 out_row(int row, const float4& o, const float4& add, const uint2& mv) {
    const float* w = reinterpret_cast<const float*>(smem + OFF_WSM);
    const float unit = *reinterpret_cast<const float*>(smem + W_UNIT), K = 8388608.f + ZERO;
    const uint2 ac = reinterpret_cast<const uint2*>(smem + OFF_ACC)[row];
    const uint32_t* g = reinterpret_cast<const uint32_t*>(smem + gate_g(row >> 1)) + (row & 1), *h = reinterpret_cast<const uint32_t*>(smem + gate_h(row >> 1)) + (row & 1);
    const uint32_t c0 = ac.x + BIAS, c1 = ac.y + BIAS;
    const float a[4] = {fmaf(__uint_as_float(__byte_perm(c0, 0x4b00u, 0x5410)) - K, unit, o.x), fmaf(__uint_as_float(__byte_perm(c0, 0x4b00u, 0x5432)) - K, unit, o.y),
                        fmaf(__uint_as_float(__byte_perm(c1, 0x4b00u, 0x5410)) - K, unit, o.z), fmaf(__uint_as_float(__byte_perm(c1, 0x4b00u, 0x5432)) - K, unit, o.w)};
    float sd[4], uu[4];
#pragma unroll
    for (int k = 0; k < 4; k++) sd[k] = fmaf(a[3], w[12 + k], fmaf(a[2], w[8 + k], fmaf(a[1], w[4 + k], a[0] * w[k])));
    const uint32_t a01 = hmul_bf2(pack_bf2(sd[0] + add.x, sd[1] + add.y), g[0]), a23 = hmul_bf2(pack_bf2(sd[2] + add.z, sd[3] + add.w), g[2]);
#pragma unroll
    for (int k = 0; k < 4; k++) uu[k] = fmaf(bf_hi(a23), w[28 + k], fmaf(bf_lo(a23), w[24 + k], fmaf(bf_hi(a01), w[20 + k], bf_lo(a01) * w[16 + k])));
    return make_uint2(hadd_bf2(mv.x, hmul_bf2(pack_bf2(uu[0], uu[1]), h[0])), hadd_bf2(mv.y, hmul_bf2(pack_bf2(uu[2], uu[3]), h[2])));
}
__device__ __forceinline__ void mma16(float (&c)[4], const uint32_t (&a)[4], uint32_t b0, uint32_t b1) {
    asm volatile("mma.sync.aligned.m16n8k16.row.col.f32.bf16.bf16.f32 {%0,%1,%2,%3}, {%4,%5,%6,%7}, {%8,%9}, {%0,%1,%2,%3};"
                 : "+f"(c[0]), "+f"(c[1]), "+f"(c[2]), "+f"(c[3]) : "r"(a[0]), "r"(a[1]), "r"(a[2]), "r"(a[3]), "r"(b0), "r"(b1));
}
__device__ __forceinline__ void finish_rows(const Params& p, uint32_t sb) {
    int tid;
    asm volatile("mov.u32 %0, %%tid.x;" : "=r"(tid));
    const int role = lds32(sb + W_ROLE), row0 = role * p.R2, np = min(p.R2, p.E - row0) >> 1, lane = tid & 31;
    {
        const uint16_t* wg = reinterpret_cast<const uint16_t*>(lane & 16 ? p.w_rbf : p.w_sbf) + (lane & 3) * 8 + (lane >> 2 & 3);
        const uint16_t* cp = reinterpret_cast<const uint16_t*>(p.centers) + (lane & 3) * 2;
        const uint32_t wb = __ldg(wg) | (uint32_t)__ldg(wg + 4) << 16, cen = __ldg(cp) | (uint32_t)__ldg(cp + 1) << 16;
        if (tid < NS1 * 32) {
            if (tid * 32 < np) prefetch_l2(p.dist + row0 + tid * 64);
            for (int i = tid * 8; i < np; i += NS1 * 32 * 8) prefetch_l2(p.m + row0 + 2 * i);
        }
#pragma unroll 1
        for (int pass = tid >= NS1 * 32; pass < 2; pass++) {
            const int k0 = (pass ? NG0 : 0) + (tid >> 2), dk = pass ? NE * 8 : NS1 * 8;
            uint2 v[NTILE];
#pragma unroll
            for (int i = 0; i < NTILE; i++) v[i].x = ld_in(reinterpret_cast<const uint32_t*>(p.dist) + min((row0 >> 1) + k0 + i * dk, (p.E >> 1) - 1));
#pragma unroll
            for (int i = 0; i < NTILE; i++) {
                uint32_t rb[2];
#pragma unroll
                for (int u = 0; u < 2; u++) {
                    const uint32_t df = hsub_bf2(__byte_perm(v[i].x, 0u, u ? 0x3232 : 0x1010), cen);
                    const uint32_t ar = hmul_bf2(hmul_bf2(df, df), 0xc120c120u);
                    rb[u] = pack_bf2(exp_fast(bf_lo(ar)), exp_fast(bf_hi(ar)));
                }
                float c[4];
                asm volatile("mma.sync.aligned.m16n8k8.row.col.f32.bf16.bf16.f32 {%0,%1,%2,%3}, {%4,%5}, {%6}, {%7,%7,%7,%7};"
                             : "=f"(c[0]), "=f"(c[1]), "=f"(c[2]), "=f"(c[3]) : "r"(rb[0]), "r"(rb[1]), "r"(wb), "f"(0.f));
                v[i] = make_uint2(pack_bf2(c[0], c[1]), pack_bf2(c[2], c[3]));
            }
            if (pass) bar_sync(BAR_TFREE, NE * 32); else bar_sync(BAR_H1, (NS1 + 1) * 32);
            const uint32_t a = sb + (lane & 2 ? gate_h(k0) : gate_g(k0)) + (lane & 1) * 8;
#pragma unroll
            for (int i = 0; i < NTILE; i++) if (k0 + i * dk < R2MAX / 2) sts64(a + i * dk * 16, v[i].x, v[i].y);
            if (pass) TKY(1) else TKY(0)
        }
    }
    uint2 mv[2 * NPAIR];
#pragma unroll
    for (int i = 0; i < NPAIR; i++) ld_in4(p.m + 2 * min((row0 >> 1) + tid + i * NE * 32, (p.E >> 1) - 1), mv[2 * i], mv[2 * i + 1]);
    uint8_t* dirty = g_dirty + role * DROW + tid * 2;
    auto flags = [&]() {
        uint32_t f[NPAIR], m = 0;
#pragma unroll
        for (int i = 0; i < NPAIR; i++) asm volatile("ld.relaxed.gpu.global.u16 %0, [%1];" : "=r"(f[i]) : "l"(dirty + i * NE * 64) : "memory");
#pragma unroll
        for (int i = 0; i < NPAIR; i++) m |= ((f[i] | f[i] >> 7) & 3u) << 2 * i;
        return m;
    };
    auto row_of = [&](int j) { return 2 * tid + (j >> 1) * NE * 64 + (j & 1); };
    bar_sync(BAR_FLAG, (NE + 1) * 32);
    TKY(2)
    uint32_t kept = flags(), left = 0, bad = 0, at = 0;
    TKZ(3, kept)
    if (kept) {
        at = atoms_add<W_NLIST>(sb, __popc(kept));
        if (at + __popc(kept) > NG0) { left = kept; kept = 0; }
        at = sb + OFF_LIST + at * 16;
        uint32_t to = at;
#pragma unroll 1
        for (uint32_t m = kept; m; m &= m - 1) {
            float4 o[2];
            o[0] = take(&g_ovf[role * RPAD + row_of(__ffs(m) - 1)], true);
            m &= m - 1;
            o[1] = take(&g_ovf[role * RPAD + row_of(__ffs(m) - 1)], m);
            const float4* w = reinterpret_cast<const float4*>(smem + OFF_WSM);
#pragma unroll
            for (int u = 0; u < 2; u++) if (!u || m) {
                sts128<0>(to, make_uint4(__float_as_uint(fmaf(o[u].w, w[3].x, fmaf(o[u].z, w[2].x, fmaf(o[u].y, w[1].x, o[u].x * w[0].x)))),
                                         __float_as_uint(fmaf(o[u].w, w[3].y, fmaf(o[u].z, w[2].y, fmaf(o[u].y, w[1].y, o[u].x * w[0].y)))),
                                         __float_as_uint(fmaf(o[u].w, w[3].z, fmaf(o[u].z, w[2].z, fmaf(o[u].y, w[1].z, o[u].x * w[0].z)))),
                                         __float_as_uint(fmaf(o[u].w, w[3].w, fmaf(o[u].z, w[2].w, fmaf(o[u].y, w[1].w, o[u].x * w[0].w))))));
                to += 16;
            }
        }
    }
    uint32_t wb[8];
#pragma unroll
    for (int i = 0; i < 8; i++) {
        const uint32_t a = sb + OFF_WSM + ((i & 4) * 4 + (i & 1) * 8 + (i & 2) + (lane >> 2 & 1)) * 4;
        wb[i] = (lane & 3) == lane >> 3 ? __byte_perm(lds32(a), lds32(a + 16), 0x7632) : 0u;
    }
    const uint32_t k0 = (lds32(sb + W_UNIT) >> 16) * 0x10001u + 0x03800380u;
    TKX(5)
    bar_sync(BAR_ACC, (NE + NC) * 32);
    TKX(6)
    uint32_t from = at;
#pragma unroll
    for (int i = 0; i < NPAIR; i++) {
        const int k = tid + i * NE * 32;
        const uint4 ac = lds128(sb + OFF_ACC + k * 16), g = lds128(sb + gate_g(k)), h = lds128(sb + gate_h(k));
        const uint32_t u[4] = {ac.x + BIAS, ac.z + BIAS, ac.y + BIAS, ac.w + BIAS};
        uint32_t a[4];
        float c[4] = {0.f, 0.f, 0.f, 0.f}, d[4] = {0.f, 0.f, 0.f, 0.f};
#pragma unroll
        for (int j = 0; j < 2; j++)
            asm volatile("{ .reg .pred q; setp.ne.u32 q, %5, 0; @q ld.shared.v2.f32 {%0,%1}, [%4]; @q ld.shared.v2.f32 {%2,%3}, [%4+8]; @q add.u32 %4, %4, 16; }"
                         : "+f"(c[2 * j]), "+f"(c[2 * j + 1]), "+f"(d[2 * j]), "+f"(d[2 * j + 1]), "+r"(from) : "r"(kept & 1u << (2 * i + j)) : "memory");
#pragma unroll
        for (int j = 0; j < 4; j++) a[j] = hsub_bf2(and_or<0x007f007fu>(u[j] >> 9, k0 + 0x04800480u), k0 + 0x04c004c0u);
        mma16(c, a, wb[0], wb[1]); mma16(d, a, wb[2], wb[3]);
#pragma unroll
        for (int j = 0; j < 4; j++) a[j] = and_or<0x007f007fu>(u[j] >> 2, k0 + 0x01000100u);
        mma16(c, a, wb[0], wb[1]); mma16(d, a, wb[2], wb[3]);
#pragma unroll
        for (int j = 0; j < 4; j++) a[j] = and_or<0x00030003u>(u[j], k0);
        mma16(c, a, wb[0], wb[1]); mma16(d, a, wb[2], wb[3]);
        a[0] = hmul_bf2(pack_bf2(c[0], c[1]), g.x); a[1] = hmul_bf2(pack_bf2(c[2], c[3]), g.y);
        a[2] = hmul_bf2(pack_bf2(d[0], d[1]), g.z); a[3] = hmul_bf2(pack_bf2(d[2], d[3]), g.w);
#pragma unroll
        for (int j = 0; j < 4; j++) c[j] = d[j] = 0.f;
        mma16(c, a, wb[4], wb[5]); mma16(d, a, wb[6], wb[7]);
        if (k < np) {
            reinterpret_cast<uint4*>(p.out + row0)[k] = make_uint4(hadd_bf2(mv[2 * i].x, hmul_bf2(pack_bf2(c[0], c[1]), h.x)), hadd_bf2(mv[2 * i].y, hmul_bf2(pack_bf2(d[0], d[1]), h.z)),
                                                                   hadd_bf2(mv[2 * i + 1].x, hmul_bf2(pack_bf2(c[2], c[3]), h.y)), hadd_bf2(mv[2 * i + 1].y, hmul_bf2(pack_bf2(d[2], d[3]), h.w)));
            if (c[0] != c[0] || c[2] != c[2]) bad |= 3u << 2 * i;
        }
    }
    if (lds32(sb + W_WRAP)) left = flags();
#pragma unroll 1
    for (uint32_t m = left | bad; m; m &= m - 1) {
        const int j = __ffs(m) - 1, row = row_of(j);
        uint4 v = make_uint4(0u, 0u, 0u, 0u);
        if (kept >> j & 1u) v = lds128(at + __popc(kept & ((1u << j) - 1u)) * 16);
        p.out[row0 + row] = out_row(row, take(&g_ovf[role * RPAD + row], left >> j & 1u),
                                    make_float4(__uint_as_float(v.x), __uint_as_float(v.y), __uint_as_float(v.z), __uint_as_float(v.w)), p.m[row0 + row]);
    }
#pragma unroll 1
    for (uint32_t m = left | kept; m; m &= m - 1) g_dirty[role * DROW + row_of(__ffs(m) - 1)] = 0;
}

template <int HOP> __device__ __forceinline__ uint2 null_rec(int lane, uint32_t R) {
    if (HOP == 1) return make_uint2(0x800000u | H<1>::tag(R), (OFF_CNT1 - OFF_M) / 8);
    return make_uint2(0x08000800u | lane << 28, 0x0fff0000u | H<2>::tag(R));
}
template <int HOP> __device__ __forceinline__ void fill(uint32_t win, int lane, uint32_t R) {
    const uint2 v = null_rec<HOP>(lane, R);
#pragma unroll 11
    for (int i = 0; i < WIN / 512; i++) sts128<0>(win + lane * 16 + i * 512, make_uint4(v.x, v.y, v.x, v.y));
}
template <int HOP> __device__ __forceinline__ void reset(uint32_t win, int lane, uint32_t R) {
    const uint2 v = null_rec<HOP>(lane, R);
    const uint32_t a = win + lane * 32 + H<HOP>::mark(R, lane >> 2) * 8;
#pragma unroll
    for (int i = 0; i < 16; i++) sts64(a + i * 1024, v.x, v.y);
    if (lane < 16) sts64(a + 16384, v.x, v.y);
}
__device__ __forceinline__ bool elect() {
    uint32_t q; asm volatile("{ .reg .pred q; elect.sync _|q, 0xffffffff; selp.u32 %0, 1, 0, q; }" : "=r"(q)); return q;
}
__device__ __forceinline__ const unsigned char* mk_ptr(uint32_t lo, uint32_t hi) { return reinterpret_cast<const unsigned char*>((uint64_t)hi << 32 | lo); }
__device__ __forceinline__ void bulk_store(uint32_t lo, uint32_t hi, uint32_t src, uint32_t n) {
    asm volatile("cp.async.bulk.global.shared::cta.bulk_group [%0], [%1], %2;" ::"l"(mk_ptr(lo, hi)), "r"(src), "r"(n) : "memory");
}
template <int HOP>
__device__ __forceinline__ void manager(const Params& p, uint32_t sb, int lane, int role, uint32_t base) {
    typedef H<HOP> h;
    constexpr int V = h::NBIN / 32, PB = h::S * 8;
    const int RT = p.rounds, lo = HOP == 1 && role >= NG ? NG : 0, hi = lo + h::NBIN;
    const int w = (role - lo) / (HOP * J), j = (role - lo - w * HOP * J) / HOP;
    const Ring rg(p.ring, __reduce_or_sync(0xffffffffu, lds32(sb + W_PAR)), 2 * w + HOP - 1);
    const uint32_t side = lds32(sb + W_SIDE), dhi = rg.main >> 32, mhi = rg.mid >> 32;
    const uint32_t c0 = HOP == 2 ? role & 1 : 0, up = (HOP == 1 && lo) ^ rg.par ^ c0;
    uint32_t dA = ((uint32_t)rg.main + src_off(j) + (c0 << 16) + (up ? 4096 : 12288)) ^ slot_off(base % 3);
    uint32_t dM = ((uint32_t)rg.mid + src_off(j) + c0 * 1024) ^ slot_off(base % 3);
    const int a0 = max(64, lo), b1 = min(68, hi);
    int n0 = (min(NHI, hi) - a0) * PB, a1 = (max(NLO, lo) - lo) * PB;
    const unsigned char* cr = reinterpret_cast<const unsigned char*>(rg.main) + MISC + ((side ^ rg.par) << 12);
    const unsigned char* cr0 = cr + cred_off(lo + lane * V), *cr1 = cr + cred_off(lo + 32 * V + min(lane, V - 1));
    const uint32_t ca0 = sb + h::CNT + lane * V * 4, ca1 = sb + h::CNT + (32 * V + min(lane, V + NDUM)) * 4;
    const uint32_t rot0 = (lane * V & 7) * 16, rot1 = lane * 16;
    uint32_t st = slot_steps(base);
    uint32_t init = h::init(base), prim = sb + h::STG + (HOP == 1 ? h::win(base) : 0u);
    uint32_t cs[5] = {0, 0, 0, 0, 0};
    auto sample = [&]() {
        if (V == 2) asm volatile("ld.relaxed.gpu.global.v2.u32 {%0,%1}, [%2];" : "=r"(cs[0]), "=r"(cs[1]) : "l"(cr0) : "memory");
        else asm volatile("ld.relaxed.gpu.global.v4.u32 {%0,%1,%2,%3}, [%4];" : "=r"(cs[0]), "=r"(cs[1]), "=r"(cs[2]), "=r"(cs[3]) : "l"(cr0) : "memory");
        cs[V] = ld_rlx32(reinterpret_cast<const uint32_t*>(cr1));
    };
    uint32_t low[5] = {rot0, rot0 + 16, rot0 + 32, rot0 + 48, rot1};
    TK_DECL
#pragma unroll 1
    for (int r = 0;; r++) {
        const uint32_t R = base + r, ninit = h::init(R + 1), done = prim;
        TK(5)
        mbar_wait(sb + B_FULL + (HOP - 1) * 8, r & 1);
        TK(0)
        uint32_t c[5];
        if (V == 2) asm volatile("ld.shared.v2.u32 {%0,%1}, [%2];" : "=r"(c[0]), "=r"(c[1]) : "r"(ca0) : "memory");
        else asm volatile("ld.shared.v4.u32 {%0,%1,%2,%3}, [%4];" : "=r"(c[0]), "=r"(c[1]), "=r"(c[2]), "=r"(c[3]) : "r"(ca0) : "memory");
        c[V] = lds32(ca1);
        uint32_t nc[5];
#pragma unroll
        for (int k = 0; k <= V; k++) {
            const uint32_t rot = k < V ? rot0 + k * 16 : rot1, z = ninit + (HOP == 1 ? rot : low[k]);
            if (HOP == 2) low[k] = min((max((int)(c[k] - low[k] - init - h::CAP * h::INC), 0) >> h::SH) * 128u + low[k], rot + BOXN * 128u);
            nc[k] = min(max(c[k] + (ninit - init - h::S * h::INC), z), (HOP == 1 ? z : ninit + low[k]) + (h::CAP - h::S) * h::INC);
        }
        if (V == 2) sts64(ca0, nc[0], nc[1]); else sts128<0>(ca0, make_uint4(nc[0], nc[1], nc[2], nc[3]));
        sts32(ca1, lane < V ? nc[V] : lane < V + NDUM ? DUMMY : r);
        __syncwarp();
        if (lane == 0) mbar_arrive(sb + B_OPEN + (HOP - 1) * 8);
        TK(1)
        TK(2)
        asm volatile("fence.proxy.async.shared::cta;" ::: "memory");
        TK(6)
        if (r >= D) {
            int it = 0;
            while (true) {
                uint32_t bad = 0;
#pragma unroll
                for (int k = 0; k <= V; k++) bad |= cs[k] - (R - D + 1);
                if (!__any_sync(0xffffffffu, bad >> 20)) break;
                if (++it > SPIN_LIMIT) __trap();
                if (it > 1) __nanosleep(100);
                sample();
            }
        }
        TK(3)
        if (elect()) {
            const uint32_t dB = (HOP == 1 ? dA ^ 0x10000u : dA) + (up ? 8192 : -8192), sm = prim + (lo ? 2 * PB : 0);
            bulk_store(dA, dhi, sm, 8192);
            bulk_store(dB, dhi, HOP == 1 ? sm + 8192 : prim + 68 * PB, 8192);
            if (n0 > 0) bulk_store(dM + (a0 - 64) * PB, mhi, prim + (a0 - lo) * PB, n0);
            if (a1 < (b1 - lo) * PB) bulk_store((dM ^ 4096u) + (uint32_t)((lo - NLO) * PB + a1), mhi, prim + a1, (b1 - lo) * PB - a1);
            asm volatile("cp.async.bulk.commit_group;" ::: "memory");
            if (r != RT - 1) asm volatile("cp.async.bulk.wait_group.read 0;" ::: "memory");
        }
        __syncwarp();
        TK(4)
        prim = HOP == 1 ? prim ^ 0x20000u : prim >= sb + 0x30000u ? sb : prim + (prim - sb) + 0x10000u;
        if (r == RT - 1) break;
        reset<HOP>(done, lane, R + HOP + 1);
        if (HOP == 1) {
            __syncwarp();
            if (lane == 0) mbar_arrive(sb + B_FREE);
        }
        if (RARE(r == D - 1 || r == RT - D - 1)) {
            uint32_t n = NHI, m = NLO;
            if (r < RT - D - 1) {
                int it = 0;
                while (true) {
                    n = ld_rlx32(reinterpret_cast<const uint32_t*>(p.ring + M_CNT + (side << 12)));
                    if ((n & 0xffffu) + (n >> 16) == NB) break;
                    if (++it > SPIN_LIMIT) __trap();
                }
                m = n = min(max(__reduce_or_sync(0xffffffffu, n) & 0xffffu, (uint32_t)NLO), (uint32_t)NHI);
            }
            n0 = (min((int)n, hi) - a0) * PB;
            a1 = (max((int)m, lo) - lo) * PB;
        }
        if (HOP == 2 && RARE(r == RT - LATE)) fence_gpu();
        sample();
        slot_next(dA, st); slot_next(dM, st);
        st = slot_rot(st);
        init = ninit;
    }
    TK_OUT
}

#define POLL_NS 200
#define POLL_NS3 400
template <int HOP> struct Reader {
    uint32_t lo, hi, st, line;
    uint32_t* cred;
    __device__ __forceinline__ void init(const Params& p, uint32_t sb, int w, int lane, int role, uint32_t base) {
        constexpr int PB = H<HOP>::S * 8;
        const int first = HOP == 1 ? (role >= NG ? NG : 0) + w * J : w * 2 * J;
        const Ring rg(p.ring, lds32(sb + W_PAR), 2 * w + HOP - 1);
        const uint32_t side = lds32(sb + W_SIDE);
        const bool mid = side ? role < 68 : role >= 64;
        const uint32_t i = role - (side ? (mid ? NLO : 68) : (mid ? 64 : 0));
        const uint32_t c = HOP == 1 ? i >> 5 : lane >> 3 & 1, in = (HOP == 1 ? (i & 31) * PB + (lane & 15) * 16 : i * PB + (lane & 7) * 16) + (lane >> 4) * src_off(3);
        lo = (in + (mid ? ((uint32_t)rg.mid ^ side << 12) + c * 1024 : (uint32_t)rg.main + (c << 16) + (side ^ rg.par ^ c ? 4096 : 12288))) ^ slot_off(base % 3);
        hi = __reduce_or_sync(0xffffffffu, (uint32_t)((mid ? rg.mid : rg.main) >> 32));
        st = slot_steps(base);
        line = opaque((HOP == 1 ? 2 * (role % NG) + (lane >> 3 & 1) : role) + (lane & 1) * 2);
        const bool both = first >= NLO && first < NHI;
        cred = lane < 1 + both ? reinterpret_cast<uint32_t*>(rg.main + MISC + (((both ? lane : first >= NG) ^ rg.par) << 12) + cred_off(role)) : nullptr;
    }
    template <int K> __device__ __forceinline__ void load1(uint2 (&v)[J]) const {
        asm volatile("ld.relaxed.gpu.global.v4.u32 {%0,%1,%2,%3}, [%4+%5];" : "=r"(v[2 * K].x), "=r"(v[2 * K].y), "=r"(v[2 * K + 1].x), "=r"(v[2 * K + 1].y)
                     : "l"(mk_ptr(lo, hi)), "n"(src_off(K)) : "memory");
    }
    static __device__ __forceinline__ uint32_t word(const uint2& v) { return HOP == 1 ? v.x : v.y; }
    template <int K> __device__ __forceinline__ void again(uint2 (&v)[J], uint32_t want, uint32_t m0, uint32_t m1, uint32_t grp) const {
        if (__ballot_sync(0xffffffffu, ((word(v[2 * K]) ^ want) & m0) | ((word(v[2 * K + 1]) ^ want) & m1)) & grp) load1<K>(v);
    }
    __device__ __forceinline__ void load(uint2 (&rec)[J]) const { load1<0>(rec); load1<1>(rec); load1<2>(rec); }
    __device__ __forceinline__ void check(uint2 (&rec)[J], uint32_t R, uint32_t ns, int lane TK_ARG) {
        const uint32_t want = H<HOP>::tag(R), mk = H<HOP>::mark(R, line);
        const uint32_t m0 = mk == 0 ? H<HOP>::TAG : 0u, m1 = mk == 1 ? H<HOP>::TAG : 0u;
        int it = 0;
        while (true) {
            uint32_t b0 = 0, b1 = 0;
#pragma unroll
            for (int j = 0; j < J; j += 2) { b0 |= word(rec[j]) ^ want; b1 |= word(rec[j + 1]) ^ want; }
            if (!__any_sync(0xffffffffu, (b0 & m0) | (b1 & m1))) break;
            if (++it > SPIN_LIMIT) __trap();
            __nanosleep(ns);
            TK_CNT(7)
            const uint32_t grp = 0xffu << (lane & 24u);
            again<0>(rec, want, m0, m1, grp); again<1>(rec, want, m0, m1, grp); again<2>(rec, want, m0, m1, grp);
        }
        if (cred) st_rlx32(cred, R + 1);
        __syncwarp();
        slot_next(lo, st);
        st = slot_rot(st);
    }
    __device__ __forceinline__ void finish() const { if (cred) st_rlx32(cred, 0u); }
};

constexpr int NPROBE = 4;
__device__ __forceinline__ uint32_t probe(unsigned char* a, uint32_t zero) {
    *reinterpret_cast<uint4*>(a) = make_uint4(0u, 0u, 0u, 0u);
    *reinterpret_cast<uint4*>(a + 16) = make_uint4(0u, 0u, 0u, 0u);
    uint32_t best = ~0u, v = threadIdx.x, prev = 0;
#pragma unroll
    for (int t = 0; t <= NPROBE + 1; t++) {
        uint32_t now;
        if (t <= NPROBE) asm volatile("atom.relaxed.gpu.global.add.u32 %0, [%1], 1;" : "=r"(v) : "l"(a + (v & zero)) : "memory");
        else asm volatile("red.relaxed.gpu.global.add.u32 [%0], 1;" ::"l"(a + (v & zero)) : "memory");
        asm volatile("mov.u32 %0, %%clock;" : "=r"(now) :: "memory");
        if (t > 1) best = min(best, now - prev);
        prev = now;
    }
    return best;
}
template <bool B> struct BoolC { static constexpr bool value = B; };

__device__ __forceinline__ void stage1(const Params& p, uint32_t sb, const int pos0, int lane, const bool half) {
    typedef H<1> h;
    constexpr int NP = 4;
    static_assert(NPR == NS1 * NP * 32 - NP * 16, "tiles");
    const int RT = p.rounds;
    uint32_t ff = *reinterpret_cast<const uint16_t*>(p.ang_freq) * 0x10001u;
    auto pair_of = [&](int r, int pos) {
        const int q = r < RT - 1 ? (r * NB + blockIdx.x) * NPR + pos : (RT - 1) * NB * NPR + blockIdx.x * p.lastn + pos;
        return pos < (r < RT - 1 ? NPR : r == RT - 1 ? p.lastn : 0) && q < p.T2 ? q : -1;
    };
    uint2 vi[NP], vo[NP]; uint32_t va[NP];
    auto load_edge = [&](int r) {
#pragma unroll
        for (int u = 0; u < NP; u++) {
            const int q = max(pair_of(r, pos0 + u * 32), 0);
            vi[u] = ld_in(p.idx_in + q); vo[u] = ld_in(p.idx_out + q); va[u] = ld_in(p.angle + q);
        }
    };
    load_edge(0);
    if (blockIdx.x == 0 && pos0 == 0 && (p.T & 1)) {
        const int t = p.T - 1;
        slow_triplet(p, reinterpret_cast<const uint32_t*>(p.idx_in)[t], reinterpret_cast<const uint32_t*>(p.idx_out)[t],
                     bf16r(cos_bf(hmul_bf2(reinterpret_cast<const uint16_t*>(p.angle)[t], ff) & 0xffffu)));
    }
    ff = __reduce_or_sync(0xffffffffu, ff);
    bar_sync(BAR_S1, (NS1 + 1) * 32);
    uint32_t R = __reduce_or_sync(0xffffffffu, lds32(sb + W_BASE));
    TK_DECL
    auto step = [&](const int r, const int qn, auto edge) {
        constexpr bool EDGE = decltype(edge)::value;
        uint32_t cc[NP], big = 0;
#pragma unroll
        for (int u = 0; u < NP; u++) {
            va[u] = hmul_bf2(va[u], ff);
            cc[u] = pack_bf2(__cosf(bf_lo(va[u])), __cosf(bf_hi(va[u])));
            big |= hmul_bf2(va[u], 0x3d003d00u);
        }
        if (RARE(big & 0x40004000u)) {
#pragma unroll 1
            for (int u = 0; u < NP; u++) {
                const uint32_t a = pick(u, va);
                float c0 = cos_bf(a & 0xffffu), c1 = cos_bf(a >> 16);
                if ((c0 != c0 || c1 != c1) && (EDGE ? pair_of(r, pos0 + u * 32) >= 0 : !half || u < 2)) {
                    const uint2 i2 = pick(u, vi), o2 = pick(u, vo);
                    if (c0 != c0) slow_triplet(p, i2.x, o2.x, c0);
                    if (c1 != c1) slow_triplet(p, i2.y, o2.y, c1);
                }
                const uint32_t v = pack_bf2(c0 != c0 ? 0.f : c0, c1 != c1 ? 0.f : c1);
#pragma unroll
                for (int k = 0; k < NP; k++) if (k == u) cc[k] = v;
            }
        }
        uint32_t bin[2 * NP], x[2 * NP], y[2 * NP];
        uint32_t dep = 0;
        auto loads = [&]() {
            const int q = qn + (dep & p.zero);
#pragma unroll
            for (int u = 0; u < NP; u += 2) {
                const int k = !u ? q : q + (half ? 0x40000000 : 32);
                tex2(p.ta, k, va[u], va[u + 1]); tex4(p.to, k, vo[u], vo[u + 1]); tex4(p.ti, k, vi[u], vi[u + 1]);
            }
        };
#pragma unroll
        for (int j = 0; j < 2 * NP; j++) {
            const uint32_t ii = j & 1 ? vi[j >> 1].y : vi[j >> 1].x, oo = j & 1 ? vo[j >> 1].y : vo[j >> 1].x;
            bin[j] = imul(ii, p.i1);
            y[j] = __byte_perm(ifma(bin[j], p.k1, ii), cc[j >> 1], j & 1 ? 0x7610 : 0x5410);
            const uint32_t bo = imul(oo, p.i2);
            x[j] = __byte_perm(ifma(bo, p.k2, imul(oo, 8.f)), bo, 0x0514);
            dep |= x[j] | y[j];
            if (EDGE && pair_of(r, pos0 + (j >> 1) * 32) < 0) bin[j] = NG + (lane & (NDUM - 1));
        }
        if (EDGE) load_edge(r + 1);
        else loads();
        const uint32_t init = h::init(R), lim = init + ((EDGE && r == RT - 1 ? h::S : h::CAP) << h::SH);
        TKS(0)
        mbar_wait(sb + B_OPEN, ~R & 1);
        TKS(1)
        bool freed = false;
        uint32_t over = 0;
#pragma unroll
        for (int g = 0; g < 2 * NP; g += NP) if (!g || EDGE || !half) {
            constexpr int G = NP;
            uint32_t ret[G];
            int mx = 0;
#pragma unroll
            for (int j = 0; j < G; j++) ret[j] = atoms_add<h::CNT>(sb + imul(bin[g + j], 4.f), h::INC);
#pragma unroll
            for (int j = 0; j < G; j++) mx = j ? max(mx, (int)ret[j]) : (int)ret[j];
            if (!freed && __any_sync(0xffffffffu, mx >= (int)(init + 0x10000u))) { TKS(2) mbar_wait(sb + B_FREE, ~R & 1); freed = true; TKS(3) }
            TKS(2)
#pragma unroll
            for (int j = 0; j < G; j++) {
                x[g + j] = and_or<h::TAG>(ret[j], x[g + j]);
                put_rec<h::STG>(ret[j], lim, sb + and_or<0x20000u | h::PM>(ret[j], imul(bin[g + j], 256.f)), x[g + j], y[g + j]);
            }
            if (RARE(mx >= (int)lim)) {
#pragma unroll
                for (int j = 0; j < G; j++) if ((int)ret[j] >= (int)lim) over |= 1u << (g + j);
            }
        }
        __syncwarp();
        if (elect()) mbar_arrive(sb + B_FULL);
        R++;
        TKS(4)
#pragma unroll 1
        while (RARE(over)) {
            TK_CNT(7)
            const int j = __ffs(over) - 1;
            over &= over - 1;
            slow_rec1(p, pick(j, x), pick(j, y), pick(j, bin));
        }
        __syncwarp();
    };
#pragma unroll 1
    for (int q = opaque(((NB + blockIdx.x) * NPR + pos0 + lane) >> 1), r = 1; r < p.full; r++, q += NB * NPR / 2) step(r - 1, q, BoolC<false>());
#pragma unroll 1
    for (int r = max(p.full - 1, 0); r < RT; r++) step(r, 0, BoolC<true>());
    TK_OUT
}

__device__ __forceinline__ void stage2(const Params& p, uint32_t sb, int w, int lane, int role, uint32_t base) {
    typedef H<2> h;
    const int RT = p.rounds;
    Reader<1> rd;
    rd.init(p, sb, w, lane, role, base);
    uint2 rec[J];
    rd.load(rec);
    bar_sync(BAR_TABLE, 2 * NC * 32);
    uint32_t kb = sb + 0x10000u, am = 0x10000u | h::PM;
    const float unit = __uint_as_float(__reduce_or_sync(0xffffffffu, lds32(sb + W_UNIT)));
    TK_DECL
#pragma unroll 1
    for (int r = 0; r < RT; r++) {
        rd.check(rec, base + r, POLL_NS, lane TK_PASS);
        const uint32_t want = H<1>::tag(base + r);
        TKS(0)
        uint2 mv[J];
#pragma unroll
        for (int j = 0; j < J; j++) {
            mv[j] = make_uint2(0u, 0u);
            const uint32_t a = sb + imul(rec[j].y & 0xffffu, 8.f);
            if (!xor_and<0x8e0000u>(rec[j].x, want)) mv[j] = lds64<OFF_M>(a);
        }
        uint32_t fl = 0;
#pragma unroll
        for (int j = 0; j < J; j++) fl |= mv[j].y;
        if (RARE(fl & 0x40000000u)) {
#pragma unroll 1
            for (int j = 0; j < J; j++) {
                const uint2 v = pick(j, mv), w = pick(j, rec);
                if ((v.y & 0x40000000u) && !((w.x ^ want) & 0x8e0000u)) {
                    if (v.x & 0x40000000u) slow_rec1(p, w.x, w.y, lds32(sb + W_ROLE) % NG);
                    else {
                        const float c = bf_hi(w.y), s = __uint_as_float(lds32(sb + W_UNIT)) * 1024.f;
                        side_add(w.x & 0xffu, __byte_perm(w.x, 0u, 0x4413) >> 3, c * (bf_lo(v.x) * s), c * (bf_hi(v.x) * s),
                                 c * (bf_lo(v.y) * s), c * (bf_hi(v.y & 0xbfffffffu) * s));
                    }
                }
            }
#pragma unroll
            for (int j = 0; j < J; j++) if (mv[j].y & 0x40000000u) rec[j].x = 0x800000u;
        }
        uint32_t w0[J], w1[J], bin[J], ret[J];
#pragma unroll
        for (int j = 0; j < J; j++) {
            const float c = bf_hi(rec[j].y), MG = 8194.0f;
            const uint32_t x = rec[j].x;
            const float v[4] = {bf_lo(mv[j].x), bf_hi(mv[j].x), bf_lo(mv[j].y), bf_hi(mv[j].y)};
            w0[j] = and_or<0xf000f000u>(x, __byte_perm(__float_as_uint(fmaf(c, v[0], MG)), __float_as_uint(fmaf(c, v[1], MG)), 0x5410));
            w1[j] = and_or<0xf000f000u>(x << 4, __byte_perm(__float_as_uint(fmaf(c, v[2], MG)), __float_as_uint(fmaf(c, v[3], MG)), 0x5410));
            bin[j] = min(xor_and<0x8e00ffu>(x, want), NB + (lane & (NDUM - 1)));
        }
        const uint32_t lim = h::init(base + r) + (r == RT - 1 ? 0x10000u : 0x20000u);
        rd.load(rec);
        TKS(1)
        mbar_wait(sb + B_OPEN + 8, (r - 1) & 1);
        TKS(2)
#pragma unroll
        for (int j = 0; j < J; j++) ret[j] = atoms_add<h::CNT>(sb + imul(bin[j], 4.f), h::INC);
        uint32_t mx = 0;
#pragma unroll
        for (int j = 0; j < J; j++) {
            w1[j] = and_or<h::TAG>(ret[j], w1[j]);
            put_rec<0>(ret[j], lim, and_xor(ret[j], am, bin[j] * 128 + kb), w0[j], w1[j]);
            mx = __viaddmax_u32(ret[j], 0u - DUMMY, mx);
        }
        __syncwarp();
        if (lane == 0) mbar_arrive(sb + B_FULL + 8);
        TKS(3)
        if (RARE(mx >= lim - DUMMY)) {
            uint32_t over = 0;
#pragma unroll
            for (int j = 0; j < J; j++) if (ret[j] - DUMMY >= lim - DUMMY) over |= 1u << j;
#pragma unroll 1
            do {
                const int j = __ffs(over) - 1;
                over &= over - 1;
                const uint32_t b = pick(j, bin), v = pick(j, ret) - lim, e = v >> h::SH, at = ((v - e * h::INC - (b & 7u) * 16u - h::CAP * 8) >> 7) + e;
                if (max(at, e) < BOXN && r < RT - LATE) g_box[(b * NB + role) * BOX + at] = make_uint2(pick(j, w0), pick(j, w1) | h::TAG);
                else slow_rec2(p, pick(j, w0), pick(j, w1), b, unit);
            } while (over);
        }
        __syncwarp();
        am = am >= 0x30000u ? 0x10000u | h::PM : am + 0x10000u;
        kb ^= am & 0x30000u;
        TKS(4)
    }
    rd.finish();
    TK_OUT
}

__device__ __forceinline__ void add_recs(uint32_t sb, int lane, const uint2 (&rec)[J], uint32_t want) {
    const uint32_t t = 0u - (lane & 1u), k = (t & 1u << 26) - (want >> 4);
    uint32_t o0[J], o1[J], g = 0;
#pragma unroll
    for (int j = 0; j < J; j++) {
        o0[j] = 0; o1[j] = 0;
        if (xor_and<0x7fffffffu>(rec[j].y, want) < 0x0ffc0000u) {
            const uint32_t a = aux_of(rec[j].x, rec[j].y, k);
            const uint32_t v0 = (rec[j].x & 0x0fff0fffu) - 0x08000800u, v1 = (rec[j].y & 0x0fff0fffu) - 0x08000800u;
            o0[j] = atoms_add<OFF_ACC>(sb + a, mux(v0, v1, t));
            o1[j] = atoms_add<OFF_ACC>(sb + (a ^ 4u), mux(v1, v0, t));
        }
    }
#pragma unroll
    for (int j = 0; j < J; j++) g |= o0[j] | o1[j];
    if (RARE(__any_sync(0xffffffffu, g & 0x80008000u))) {
#pragma unroll 1
        for (int j = 0; j < J; j++) {
            const uint2 w = pick(j, rec);
            const uint32_t aux = aux_of(w.x, w.y), p0 = pick(j, o0), p1 = pick(j, o1);
            const float2 a = acc_fix(t ? p1 : p0, w.x & 0x0fff0fffu), b = acc_fix(t ? p0 : p1, w.y & 0x0fff0fffu);
            const float unit = __uint_as_float(lds32(sb + W_UNIT));
            if (xor_and<0x7fffffffu>(w.y, want) < 0x0ffc0000u && (a.x != 0.f || a.y != 0.f || b.x != 0.f || b.y != 0.f)) {
                side_add(lds32(sb + W_ROLE), aux >> 3, a.x * unit, a.y * unit, b.x * unit, b.y * unit);
                sts32(sb + W_WRAP, 1u);
            }
            __syncwarp();
        }
    }
}
__device__ __forceinline__ void stage3(const Params& p, uint32_t sb, int w, int lane, int role, uint32_t base) {
    const int RT = p.rounds;
    Reader<2> rd;
    rd.init(p, sb, w, lane, role, base);
    uint2 rec[J];
    bar_sync(BAR_TABLE, 2 * NC * 32);
    TK_DECL
#pragma unroll 1
    for (int r = 0; r < RT; r++) {
        rd.load(rec);
        rd.check(rec, base + r, r < RT - 2 ? POLL_NS3 : 100, lane TK_PASS);
        RTS((r & 127) == 40 && w == 0, 1 + (r >> 7))
        TK(0)
        add_recs(sb, lane, rec, H<2>::tag(base + r));
        TK(1)
        if (RARE((uint32_t)(r - (RT - LATE + 1)) < 2u)) {
            static_assert(BOX == 32, "box");
            float4* box = reinterpret_cast<float4*>(g_box) + (lds32(sb + W_ROLE) * NB + (w * 2 + r - (RT - LATE + 1)) * J) * (BOX / 2) + lane;
            TKY(0)
#pragma unroll
            for (int j = 0; j < J / 2; j++) {
                const float4 v = ld_rlx128f(box + j * 32);
                rec[2 * j] = make_uint2(__float_as_uint(v.x), __float_as_uint(v.y)); rec[2 * j + 1] = make_uint2(__float_as_uint(v.z), __float_as_uint(v.w));
            }
#pragma unroll
            for (int j = 0; j < J / 2; j++) if (rec[2 * j].x) box[j * 32] = make_float4(0.f, 0.f, 0.f, 0.f);
            add_recs(sb, lane, rec, H<2>::TAG);
            TKY(1)
        }
    }
    rd.finish();
    TK_OUT
}

__device__ __forceinline__ uint32_t row_max(uint32_t x, uint32_t y) {
    const uint32_t mx = __vmaxu2(x & 0x7fff7fffu, y & 0x7fff7fffu);
    return max(mx & 0xffffu, mx >> 16);
}
constexpr int NTAB = 3, TABC = 3 * 2 * NC * 32 * 16;
static_assert(NTAB * TABC >= R1MAX * 8, "table");
constexpr int EWIN = 5;

__global__ void __launch_bounds__(NTHR, 1) fused_kernel(const Params p) {
    const int tid = threadIdx.x, lane = tid & 31;
    const int hw = __reduce_max_sync(0xffffffffu, tid >> 5);
    const uint32_t sb = __reduce_or_sync(0xffffffffu, (uint32_t)__cvta_generic_to_shared(smem));
    TKX(0)
    RTS(tid == 0, 0)
    uint32_t cta;
    asm volatile("mov.u32 %0, %%ctaid.x;" : "=r"(cta));
    if (hw != W_M1 && hw != W_M2) {
        const int job = hw < W_M1 ? hw : hw - 1;
        if (lane == 0 && job < 2 * NPAGE + 2)
            sts32(sb + OFF_PROBE + job * 4, probe(p.ring + (size_t)max(job / 2 - 1, 0) * PAGE + PROBE + (cta & 31) * 128 + (cta >> 5 & 3) * 16384 + (cta >> 7 << 20) +
                                                  ((job & 1) << 12 ^ (job < 2 ? 0x3000 : 0)), p.zero));
        if (job < 4) bar_arrive(BAR_SIDE, 5 * 32); else bar_arrive(BAR_PROBE, 27 * 32);
        TKX(1)
    }
    if (hw < NS1) {
        stage1(p, sb, hw * 128 + lane, lane, hw == NS1 - 1);
    } else if (hw == W_M1) {
        const uint32_t epoch = ld_rlx32(&g_base);
        if (lane == 0) {
            if (sb & 255u) __trap();
            mbar_init(sb + B_FULL, NS1); mbar_init(sb + B_OPEN, 1); mbar_init(sb + B_FREE, 1);
            for (int i = 0; i < NTAB; i++) mbar_init(sb + B_TAB + i * 8, 1);
            asm volatile("fence.proxy.async.shared::cta;" ::: "memory");
        }
        const uint32_t base = __reduce_or_sync(0xffffffffu, epoch) & 31u;
        if (lane == 0) { sts32(sb + W_BASE, base); sts64(sb + W_NLIST, 0u, 0u); }
        if (lane == 0 && (base & 1u)) { mbar_arrive(sb + B_OPEN); mbar_arrive(sb + B_FREE); }
        for (int i = lane; i < NG + NDUM; i += 32) sts32(sb + OFF_CNT1 + i * 4, i < NG ? H<1>::init(base) + (i & 7) * 16 : DUMMY);
#pragma unroll 1
        for (int i = 0; i < 2; i++) fill<1>(sb + OFF_H1 + H<1>::win(base + i), lane, base + i);
        bar_arrive(BAR_S1, (NS1 + 1) * 32);
        bar_sync(BAR_SIDE, 5 * 32);
        {
            const uint2 la = lds64<OFF_PROBE>(sb), lb = lds64<OFF_PROBE + 8>(sb);
            const uint32_t side = min(la.y, lb.y) < min(la.x, lb.x);
            uint32_t v = 0;
            if (lane < 2) asm volatile("atom.relaxed.gpu.global.add.u32 %0, [%1], %2;" : "=r"(v) : "l"(p.ring + M_CNT + lane * 4096), "r"(side ? 0x10000u : 1u) : "memory");
            if (lane == 0) {
                const uint32_t role = side ? NB - 1 - (v >> 16) : v & 0xffffu;
                const int r0 = (role >= NG ? role - NG : role) * p.R1, nb = min(p.R1, p.E - r0) * 8;
#pragma unroll
                for (int i = 0; i < NTAB; i++) {
                    const int n = max(min(nb - i * TABC, TABC), 0);
                    asm volatile("mbarrier.arrive.expect_tx.shared::cta.b64 _, [%0], %1;" ::"r"(sb + B_TAB + i * 8), "r"(n) : "memory");
                    if (n) asm volatile("cp.async.bulk.shared::cluster.global.mbarrier::complete_tx::bytes [%0], [%1], %2, [%3];"
                                        ::"r"(sb + OFF_M + i * TABC), "l"(p.m + r0 + i * (TABC / 8)), "r"(n), "r"(sb + B_TAB + i * 8) : "memory");
                }
                sts32(sb + W_ROLE, role); sts32(sb + W_SIDE, role < NLO ? 0u : role >= NHI ? 1u : side);
                sts32(sb + W_END, (epoch | 31u) + 1u + (base + p.rounds) % 24u);
            }
            TKX(2)
            bar_sync(BAR_PROBE, 27 * 32);
            const uint2 l = lds64<OFF_PROBE + 8>(sb + min(lane, NPAGE - 1) * 8);
            const uint32_t mine = (__ballot_sync(0xffffffffu, (l.y < l.x) != side) & ~1u) | 0x80000000u;
            if (lane == 0) {
                asm volatile("atom.relaxed.gpu.global.cas.b32 %0, [%1], 0, %2;" : "=r"(v) : "l"(p.ring + M_PAR), "r"(mine) : "memory");
                sts32(sb + W_PAR, v ? v : mine);
            }
        }
        bar_arrive(BAR_PAR, (2 * NC + 2) * 32);
        manager<1>(p, sb, opaque(lane), __reduce_max_sync(0xffffffffu, lds32(sb + W_ROLE)), base);
        asm volatile("cp.async.bulk.wait_group 0;" ::: "memory");
        bar_arrive(BAR_H1, (NS1 + 1) * 32);
        TKX(4)
        {
            const int role = lds32(sb + W_ROLE);
#pragma unroll 1
            for (int i = lane * 16; i < DROW; i += 4 * 512) {
                float4 f[4];
#pragma unroll
                for (int u = 0; u < 4; u++) f[u] = ld_rlx128f(reinterpret_cast<const float4*>(g_dirty + role * DROW + i + u * 512));
#pragma unroll
                for (int u = 0; u < 4; u++) {
                    if (__float_as_uint(f[u].x) | __float_as_uint(f[u].y)) prefetch_l2(g_ovf + role * RPAD + i + u * 512);
                    if (__float_as_uint(f[u].z) | __float_as_uint(f[u].w)) prefetch_l2(g_ovf + role * RPAD + i + u * 512 + 8);
                }
            }
        }
        bar_sync(BAR_DONE, (NE + 1) * 32);
        TKY(0)
        if (lane < 2) { fence_gpu(); st_rlx32(reinterpret_cast<uint32_t*>(p.ring + M_FLAG + lane * 4096) + blockIdx.x, lds32(sb + W_END)); }
        TKY(1)
        wait_flags(p, sb, lane, lds32(sb + W_END));
        TKX(5)
        bar_arrive(BAR_FLAG, (NE + 1) * 32);
        if (blockIdx.x == 0) {
            if (lane == 0) g_base = lds32(sb + W_END);
            if (lane < 3) *reinterpret_cast<uint32_t*>(p.ring + (lane & 2 ? M_PAR : M_CNT + (lane & 1) * 4096)) = 0;
        }
    } else if (hw == W_M2) {
        const uint32_t epoch = ld_rlx32(&g_base);
        uint2 sm[16];
#pragma unroll
        for (int i = 0; i < 8; i++) ld_in4(p.m + 2 * min((i * 8 + (lane >> 2)) * (p.E >> 7) + (lane & 3), (p.E >> 1) - 1), sm[2 * i], sm[2 * i + 1]);
        const float wd = __bfloat162float(lane & 16 ? p.w_up[lane & 15] : p.w_down[lane & 15]);
        if (lane == 0) { mbar_init(sb + B_FULL + 8, NC); mbar_init(sb + B_OPEN + 8, 1); }
        sts128<OFF_HIST>(sb + lane * 16, make_uint4(0u, 0u, 0u, 0u)); sts128<OFF_HIST + 512>(sb + lane * 16, make_uint4(0u, 0u, 0u, 0u));
        __syncwarp();
#pragma unroll
        for (int i = 0; i < 16; i++) atoms_add<OFF_HIST>(sb + (row_max(sm[i].x, sm[i].y) >> 7) * 4, 1u);
        __syncwarp();
        uint32_t best = 0;
#pragma unroll 1
        for (int e = 11 + lane; e <= 230; e += 32) {
            uint32_t c = 0;
#pragma unroll
            for (int i = 0; i < EWIN; i++) c += lds32(sb + OFF_HIST + (e - i) * 4);
            best = max(best, c << 8 | (255 - e));
        }
        const uint32_t e = 255 - (__reduce_max_sync(0xffffffffu, best) & 255u);
        if (lane == 0) { sts32(sb + W_EXP, e); sts32(sb + W_UNIT, (e - 10) << 23); }
        const uint32_t base = __reduce_or_sync(0xffffffffu, epoch) & 31u;
        for (int i = lane; i <= NB + NDUM; i += 32) sts32(sb + OFF_CNT2 + i * 4, i < NB ? H<2>::init(base) + (i & 7) * 16 : DUMMY);
#pragma unroll 1
        for (int i = 0; i < 3; i++) fill<2>(sb + H<2>::win(i), lane, base + i);
        reinterpret_cast<float*>(smem + OFF_WSM)[lane] = wd;
        bar_sync(BAR_PAR, (2 * NC + 2) * 32);
        manager<2>(p, sb, opaque(lane), __reduce_max_sync(0xffffffffu, lds32(sb + W_ROLE)), base);
        TKX(4)
        asm volatile("cp.async.bulk.wait_group 0;" ::: "memory");
    } else {
        const int pw = __reduce_max_sync(0xffffffffu, hw < W_M1 ? hw - NS1 : hw - NS1 - 1), ct = pw * 32 + lane;
        constexpr int CT = 2 * NC * 32;
        bar_sync(BAR_PAR, (2 * NC + 2) * 32);
        TKY(4)
        for (int i = ct; i < R2MAX / 2; i += CT) reinterpret_cast<uint4*>(smem + OFF_ACC)[i] = make_uint4(0x40004000u, 0x40004000u, 0x40004000u, 0x40004000u);
        const int role = __reduce_max_sync(0xffffffffu, lds32(sb + W_ROLE));
        {
            const int e = lds32(sb + W_EXP);
            const uint32_t sc = (uint32_t)(254 - e) * 0x800080u;
            auto conv = [&](uint32_t& x, uint32_t& y) {
                const uint32_t mx = row_max(x, y);
                const int d = e - (int)(mx >> 7);
                x = hmul_bf2(x, sc); y = hmul_bf2(y, sc);
                if (d >= EWIN) y |= 0x40000000u;
                if (d < 0 || (d >= EWIN && e > 127)) { x = 0x40000000u; y = x; }
                if (mx == 0) { x = 0; y = 0; }
            };
#pragma unroll 1
            for (int i = 0; i < NTAB; i++) {
                mbar_wait(sb + B_TAB + i * 8, 0);
                uint4* t = reinterpret_cast<uint4*>(smem + OFF_M + i * TABC) + ct;
#pragma unroll
                for (int u = 0; u < TABC / 16 / CT; u++) if (i * TABC + (ct + u * CT) * 16 < R1MAX * 8) {
                    uint4 v = t[u * CT];
                    conv(v.x, v.y); conv(v.z, v.w);
                    t[u * CT] = v;
                }
            }
        }
        TKX(3)
        const uint32_t base = __reduce_or_sync(0xffffffffu, lds32(sb + W_BASE));
        if (hw < W_M1) {
            stage2(p, sb, pw, opaque(lane), role, base);
        } else {
            stage3(p, sb, pw - NC, opaque(lane), role, base);
            TKX(4)
            bar_arrive(BAR_ACC, (NE + NC) * 32);
        }
    }
    if (hw < W_M1) {
        bar_arrive(BAR_DONE, (NE + 1) * 32);
        TKX(4)
        finish_rows(p, sb);
    }
}

__global__ void fb_scatter(const uint2* __restrict__ m, const int* __restrict__ idx_in, const int* __restrict__ idx_out,
                           const uint16_t* __restrict__ angle, const __nv_bfloat16* __restrict__ ang_freq, int T, int e0, int e1) {
    const uint32_t fb = *reinterpret_cast<const uint16_t*>(ang_freq);
    for (long long t = blockIdx.x * (long long)blockDim.x + threadIdx.x; t < T; t += (long long)gridDim.x * blockDim.x) {
        int o = idx_out[t];
        if (o < e0 || o >= e1) continue;
        float c = bf16r(cos_bf(hmul_bf2(angle[t], fb) & 0xffffu));
        uint2 v = __ldg(m + idx_in[t]);
        red4(&g_ovf[o - e0], c * bf_lo(v.x), c * bf_hi(v.x), c * bf_lo(v.y), c * bf_hi(v.y));
    }
}
__global__ void fb_final(const Params p, int e0, int e1) {
    int e = e0 + blockIdx.x * blockDim.x + threadIdx.x;
    if (e >= e1) return;
    float4 a4 = g_ovf[e - e0];
    g_ovf[e - e0] = make_float4(0.f, 0.f, 0.f, 0.f);
    float a[4] = {a4.x, a4.y, a4.z, a4.w};
    float d = __bfloat162float(p.dist[e]);
    float g[4] = {0, 0, 0, 0}, h[4] = {0, 0, 0, 0};
    for (int r = 0; r < 8; r++) {
        float df = bf16r(d - __bfloat162float(p.centers[r]));
        float rb = bf16r(expf(bf16r(-10.0f * bf16r(df * df))));
        for (int k = 0; k < 4; k++) {
            g[k] += rb * __bfloat162float(p.w_sbf[r * 4 + k]);
            h[k] += rb * __bfloat162float(p.w_rbf[r * 4 + k]);
        }
    }
    float ag[4];
    for (int k = 0; k < 4; k++) {
        float s = 0.f;
        for (int j = 0; j < 4; j++) s += a[j] * __bfloat162float(p.w_down[j * 4 + k]);
        ag[k] = bf16r(s * g[k]);
    }
    uint2 mv = p.m[e];
    float mm[4] = {bf_lo(mv.x), bf_hi(mv.x), bf_lo(mv.y), bf_hi(mv.y)};
    __nv_bfloat16 o[4];
    for (int k = 0; k < 4; k++) {
        float u = 0.f;
        for (int j = 0; j < 4; j++) u += ag[j] * __bfloat162float(p.w_up[j * 4 + k]);
        o[k] = __float2bfloat16_rn(mm[k] + bf16r(bf16r(u) * bf16r(h[k])));
    }
    p.out[e] = *reinterpret_cast<uint2*>(o);
}

}

static cudaTextureObject_t make_tex(const void* ptr, size_t bytes, int words) {
    cudaResourceDesc rd = {}; cudaTextureDesc td = {};
    rd.resType = cudaResourceTypeLinear; rd.res.linear.devPtr = const_cast<void*>(ptr); rd.res.linear.sizeInBytes = bytes;
    rd.res.linear.desc = cudaCreateChannelDesc(32, words > 1 ? 32 : 0, words > 2 ? 32 : 0, words > 2 ? 32 : 0, cudaChannelFormatKindUnsigned);
    td.readMode = cudaReadModeElementType;
    cudaTextureObject_t t = 0;
    if (cudaCreateTextureObject(&t, &rd, &td, nullptr) != cudaSuccess) { t = 0; (void)cudaGetLastError(); }
    return t;
}

extern "C" void kernel_launch(void* const* d_in, const int* in_sizes, int n_in, void* d_out, int out_size) {
    typedef const __nv_bfloat16* B;
    Params p;
    p.m = (const uint2*)d_in[0]; p.idx_in = (const uint2*)d_in[1]; p.idx_out = (const uint2*)d_in[2]; p.dist = (B)d_in[3];
    p.angle = (const uint32_t*)d_in[4]; p.centers = (B)d_in[5]; p.ang_freq = (B)d_in[6]; p.w_rbf = (B)d_in[7]; p.w_sbf = (B)d_in[8];
    p.w_down = (B)d_in[9]; p.w_up = (B)d_in[10]; p.out = (uint2*)d_out;
    p.E = in_sizes[3]; p.T = in_sizes[1]; p.T2 = p.T >> 1; p.zero = 0;
    p.R1 = p.R2 = p.rounds = p.lastn = p.full = 0; p.i1 = p.i2 = p.k1 = p.k2 = 0.f;
    static int ok = -1;
    static unsigned char* ring = nullptr;
    if (ok < 0) {
        void* ra = nullptr;
        cudaGetSymbolAddress(&ra, g_ring);
        ring = reinterpret_cast<unsigned char*>(((uintptr_t)ra + PAGE - 1) & ~(uintptr_t)(PAGE - 1));
        int dev = 0, sms = 0, occ = 0;
        cudaGetDevice(&dev);
        cudaDeviceGetAttribute(&sms, cudaDevAttrMultiProcessorCount, dev);
        cudaError_t e = cudaFuncSetAttribute(fused_kernel, cudaFuncAttributeMaxDynamicSharedMemorySize, SMEM_BYTES);
        if (e == cudaSuccess) e = cudaOccupancyMaxActiveBlocksPerMultiprocessor(&occ, fused_kernel, NTHR, SMEM_BYTES);
        ok = (e == cudaSuccess && occ >= 1 && sms >= NB) ? 1 : 0;
        (void)cudaGetLastError();
    }
    p.ring = ring;
    static cudaTextureObject_t tx[3];
    static const void* of[3];
    static int of_t = -1;
    if (of[0] != d_in[1] || of[1] != d_in[2] || of[2] != d_in[4] || of_t != p.T) {
        tx[0] = make_tex(p.idx_in, (size_t)(p.T >> 2) * 16, 4); tx[1] = make_tex(p.idx_out, (size_t)(p.T >> 2) * 16, 4); tx[2] = make_tex(p.angle, (size_t)(p.T >> 2) * 8, 2);
        of[0] = d_in[1]; of[1] = d_in[2]; of[2] = d_in[4]; of_t = p.T;
    }
    p.ti = tx[0]; p.to = tx[1]; p.ta = tx[2];
    const bool fused = ok == 1 && p.E <= EMAX && p.E >= 2 * NB && p.E % 2 == 0 && p.T >= 2;
    if (fused) {
        p.R1 = ((p.E + NG - 1) / NG + 1) & ~1; p.R2 = ((p.E + NB - 1) / NB + 1) & ~1;
        p.i1 = nextafterf(1.f / p.R1, 2.f); p.i2 = nextafterf(1.f / p.R2, 2.f); p.k1 = -(float)p.R1; p.k2 = -8.f * p.R2;
        const int per = NB * NPR;
        int full = p.T2 / per, rest = p.T2 - full * per;
        p.full = p.ti && p.to && p.ta ? full : 0;
        p.lastn = (rest + NB - 1) / NB;
        if (p.lastn > NPR / 2) { full++; p.lastn = 0; }
        if (full < D) { full = D; p.lastn = 0; }
        p.rounds = full + 1;
        fused_kernel<<<NB, NTHR, SMEM_BYTES>>>(p);
    } else {
        for (int e0 = 0; e0 < p.E; e0 += EMAX) {
            int e1 = p.E - e0 < EMAX ? p.E : e0 + EMAX;
            fb_scatter<<<1056, 256>>>(p.m, (const int*)d_in[1], (const int*)d_in[2], (const uint16_t*)d_in[4], p.ang_freq, p.T, e0, e1);
            fb_final<<<(e1 - e0 + 255) / 256, 256>>>(p, e0, e1);
        }
    }
}
```

```cpp
#include <cuda_runtime.h>
#include <cuda_bf16.h>
#include <stdint.h>
#include <math.h>

#define LATEE 0
#define AHEAD 3
#define RSPLIT (D - 1)
#define TEX0 1
#define KDRY 4
#define SMP1 0
#define SMP2 1
#define RARE(x) __builtin_expect(!!(x), 0)
namespace {

constexpr int NB = 132, NG = 66;
constexpr int R2MAX = 6062, R1MAX = 12128;
constexpr int EMAX = NB * R2MAX;
constexpr int NTHR = 1024;
constexpr int NS1 = 8, NC = 11, J = 6;
constexpr int NPR = 960;
constexpr int D = 3;
constexpr int WIN = 16896;
constexpr int NDUM = 16;
constexpr uint32_t DUMMY = 0xc0000000u;

constexpr int OFF_ACC = WIN, OFF_BAR = OFF_ACC + R2MAX * 8;
constexpr int OFF_H1 = 0x10000 + WIN, OFF_M = OFF_H1 + WIN, OFF_PROBE = OFF_M + R1MAX * 8;
constexpr int OFF_CNT1 = OFF_H1 + 0x20000 + WIN, OFF_CNT2 = OFF_CNT1 + (NG + NDUM + 2) * 4;
constexpr int OFF_HIST = OFF_ACC;
constexpr int OFF_WSM = OFF_CNT2 + (NB + NDUM) * 4 + 16;
constexpr int SMEM_BYTES = OFF_WSM + 128;
static_assert(SMEM_BYTES <= 232448 && OFF_BAR + 64 <= 0x10000 && OFF_PROBE + 256 <= 0x30000, "smem");
static_assert(OFF_BAR % 8 == 0 && OFF_WSM % 16 == 0 && OFF_CNT2 % 16 == 0, "align");
static_assert(NC * J == NG && NC * 32 * 6 * 16 == 2 * WIN, "shape");

template <int HOP> struct H {
    static constexpr int S = HOP == 1 ? 32 : 16, NBIN = HOP == 1 ? NG : NB, CAP = 2 * S, SH = HOP == 1 ? 11 : 12;
    static constexpr int TB = HOP == 1 ? 17 : 28, CNT = HOP == 1 ? OFF_CNT1 : OFF_CNT2, STG = HOP == 1 ? OFF_H1 : 0;
    static constexpr uint32_t INC = (1u << SH) + 8u, PM = (S - 1) * 8, TAG = 7u << TB;
    static __device__ __forceinline__ uint32_t tag(uint32_t R) { return R << TB & TAG; }
    static __device__ __forceinline__ uint32_t init(uint32_t R) { return tag(R) | ((1u << TB) - 0x10000u); }
    static __device__ __forceinline__ uint32_t mark(uint32_t R, uint32_t line) { return ((HOP == 1 ? R >> 1 : R) + line) & 3u; }
    static __device__ __forceinline__ uint32_t win(int r) { return HOP == 1 ? (r & 1) << 17 : (0x310u >> (r % 3 * 4) & 3u) << 16; }
};

constexpr uint32_t PAGE = 1u << 21;
constexpr int NPAGE = NC + 2;
__device__ __align__(256) unsigned char g_ring[(size_t)(NPAGE + 1) * PAGE];
constexpr int MISC = 0xa0000;
constexpr int M_CNT = MISC + 1024, M_PAR = M_CNT + 4;
constexpr int M_BASE = M_CNT + 8;
constexpr int M_FLAG = MISC + 2048;
constexpr int PROBE = MISC + 0x40000;
__device__ __forceinline__ uint32_t cred_off(uint32_t role) { return role * 4 + min(role >> 5, 3u) * (16384 - 128); }
struct Ring {
    uint64_t main, mid;
    uint32_t par;
    __device__ __forceinline__ Ring(const unsigned char* ring, uint32_t pars, int k) {
        main = reinterpret_cast<uint64_t>(ring) + ((uint64_t)k << 20);
        par = pars >> (k >> 1) & 1u;
        mid = reinterpret_cast<uint64_t>(ring) + (uint64_t)NC * PAGE + (((k >> 3 << 20) + (k >> 2 & 1) * 0x11000u + (k & 1) * 2048) ^ (k >> 1 & 1) * 0x3000u ^ (pars >> (NC + (k >> 4)) & 1u) << 12);
    }
};
constexpr int NLO = 60, NHI = 72;
__host__ __device__ constexpr uint32_t src_off(int j) { return (j % 3) << 14 | (j / 3) << 18; }
__device__ __forceinline__ uint32_t slot_off(uint32_t s) { return (0xa930u >> s * 4 & 15u) << 16; }
__device__ __forceinline__ uint32_t slot_steps(uint32_t R) { return (uint32_t)(0x30a09030aull >> (2 - R % 3) * 8) & 0xffffffu; }
__device__ __forceinline__ void slot_next(uint32_t& a, uint32_t st) { a ^= st & 0xf0000u; }
__device__ __forceinline__ uint32_t slot_rot(uint32_t st) { return __byte_perm(st, 0u, 0x4102); }
constexpr int RPAD = 6064, DROW = 6144;
__device__ __align__(128) uint8_t g_dirty[NB * DROW];
constexpr int BOX = 32, BOXN = 24, LATE = 8;
__device__ __align__(128) uint2 g_box[NB * NB * BOX];
__device__ __align__(128) float4 g_ovf[NB * RPAD];

struct Params {
    const uint2* m; const uint2* idx_in; const uint2* idx_out; const __nv_bfloat16* dist; const uint32_t* angle;
    const __nv_bfloat16* centers; const __nv_bfloat16* ang_freq; const __nv_bfloat16* w_rbf; const __nv_bfloat16* w_sbf;
    const __nv_bfloat16* w_down; const __nv_bfloat16* w_up; uint2* out; unsigned char* ring;
    cudaTextureObject_t ti, to, ta;
    int E, T, T2, R1, R2, rounds, lastn, full; uint32_t zero; float i1, i2, k1, k2;
};

__device__ __forceinline__ float bf16r(float x) { return __bfloat162float(__float2bfloat16_rn(x)); }
__device__ __forceinline__ float bf_lo(uint32_t v) { return __uint_as_float(v << 16); }
__device__ __forceinline__ float bf_hi(uint32_t v) { return __uint_as_float(v & 0xffff0000u); }
__device__ __forceinline__ void red4(float4* a, float x, float y, float z, float w) {
    asm volatile("red.global.add.v4.f32 [%0], {%1,%2,%3,%4};" ::"l"(a), "f"(x), "f"(y), "f"(z), "f"(w) : "memory");
}
__device__ __forceinline__ void bar_sync(int id, int n) { __syncwarp(); asm volatile("bar.sync %0, %1;" ::"r"(id), "r"(n) : "memory"); }
__device__ __forceinline__ void bar_arrive(int id, int n) { __syncwarp(); asm volatile("bar.arrive %0, %1;" ::"r"(id), "r"(n) : "memory"); }
template <int OFF> __device__ __forceinline__ uint32_t atoms_add(uint32_t addr, uint32_t v) {
    uint32_t r; asm volatile("atom.shared.add.u32 %0, [%1+%3], %2;" : "=r"(r) : "r"(addr), "r"(v), "n"(OFF) : "memory"); return r;
}
__device__ __forceinline__ void sts64(uint32_t addr, uint32_t x, uint32_t y) {
    asm volatile("st.shared.v2.u32 [%0], {%1,%2};" ::"r"(addr), "r"(x), "r"(y) : "memory");
}
__device__ __forceinline__ void sts32(uint32_t addr, uint32_t x) { asm volatile("st.shared.u32 [%0], %1;" ::"r"(addr), "r"(x) : "memory"); }
template <int OFF = 0> __device__ __forceinline__ uint2 lds64(uint32_t addr) {
    uint2 v; asm volatile("ld.shared.v2.u32 {%0,%1}, [%2+%3];" : "=r"(v.x), "=r"(v.y) : "r"(addr), "n"(OFF) : "memory"); return v;
}
__device__ __forceinline__ uint32_t lds32(uint32_t addr) {
    uint32_t v; asm volatile("ld.shared.u32 %0, [%1];" : "=r"(v) : "r"(addr) : "memory"); return v;
}
template <int OFF> __device__ __forceinline__ void sts128(uint32_t a, const uint4& v) {
    asm volatile("st.shared.v4.u32 [%0+%5], {%1,%2,%3,%4};" ::"r"(a), "r"(v.x), "r"(v.y), "r"(v.z), "r"(v.w), "n"(OFF) : "memory");
}
__device__ __forceinline__ uint4 lds128(uint32_t a) {
    uint4 v; asm volatile("ld.shared.v4.u32 {%0,%1,%2,%3}, [%4];" : "=r"(v.x), "=r"(v.y), "=r"(v.z), "=r"(v.w) : "r"(a) : "memory"); return v;
}
__device__ __forceinline__ uint32_t ld_rlx32(const uint32_t* p) {
    uint32_t v; asm volatile("ld.relaxed.gpu.global.u32 %0, [%1];" : "=r"(v) : "l"(p) : "memory"); return v;
}
__device__ __forceinline__ uint2 ld_rlx64(const void* p) {
    uint2 v; asm volatile("ld.relaxed.gpu.global.v2.u32 {%0,%1}, [%2];" : "=r"(v.x), "=r"(v.y) : "l"(p) : "memory"); return v;
}
__device__ __forceinline__ float4 ld_rlx128f(const float4* p) {
    float4 v; asm volatile("ld.relaxed.gpu.global.v4.f32 {%0,%1,%2,%3}, [%4];" : "=f"(v.x), "=f"(v.y), "=f"(v.z), "=f"(v.w) : "l"(p) : "memory"); return v;
}
__device__ __forceinline__ float4 take(float4* p, bool q) {
    float4 v;
    asm volatile("{ .reg .b128 a; .reg .b64 x, y; .reg .pred q; mov.b64 x, 0; mov.b128 a, {x, x}; setp.ne.u32 q, %5, 0;\n"
                 "@q atom.relaxed.gpu.global.exch.b128 a, [%4], a; mov.b128 {x, y}, a; mov.b64 {%0,%1}, x; mov.b64 {%2,%3}, y; }"
                 : "=f"(v.x), "=f"(v.y), "=f"(v.z), "=f"(v.w) : "l"(p), "r"((uint32_t)q) : "memory");
    return v;
}
__device__ __forceinline__ void fence_gpu() { asm volatile("fence.acq_rel.gpu;" ::: "memory"); }
__device__ __forceinline__ void st_rlx32(uint32_t* p, uint32_t v) { asm volatile("st.relaxed.gpu.global.u32 [%0], %1;" ::"l"(p), "r"(v) : "memory"); }
__device__ __forceinline__ uint32_t hmul_bf2(uint32_t a, uint32_t b) {
    uint32_t r; asm("mul.rn.bf16x2 %0, %1, %2;" : "=r"(r) : "r"(a), "r"(b)); return r;
}
__device__ __forceinline__ uint32_t hsub_bf2(uint32_t a, uint32_t b) {
    uint32_t r; asm("sub.rn.bf16x2 %0, %1, %2;" : "=r"(r) : "r"(a), "r"(b)); return r;
}
__device__ __forceinline__ uint32_t hadd_bf2(uint32_t a, uint32_t b) {
    uint32_t r; asm("add.rn.bf16x2 %0, %1, %2;" : "=r"(r) : "r"(a), "r"(b)); return r;
}
__device__ __forceinline__ int opaque(int v) { return __shfl_sync(0xffffffffu, v, threadIdx.x); }
constexpr int SPIN_LIMIT = 1 << 22;

__constant__ uint32_t c_inv2pi[8] = {0u, 0x28be60dbu, 0x9391054au, 0x7f09d5f4u, 0x7d4d3770u, 0x36d8a566u, 0x4f10e410u, 0x7f9458eau};
constexpr uint32_t BIGX = 0x4280u;
__device__ __forceinline__ float cos_big(uint32_t xb) {
    uint32_t e = (xb >> 7) & 0xffu, M = (xb & 0x7fu) | 0x80u;
    uint32_t pp = e - 102u;
    uint32_t wi = pp >> 5;
    uint32_t t0 = c_inv2pi[wi], t1 = c_inv2pi[wi + 1], t2 = c_inv2pi[wi + 2];
    uint32_t f = M * __funnelshift_l(t1, t0, pp) + __umulhi(M, __funnelshift_l(t2, t1, pp));
    float c = __cosf((float)(int)f * 1.4629180792671596e-9f);
    return e == 255u ? __uint_as_float(0x7fc00000u) : c;
}
__device__ __forceinline__ float cos_bf(uint32_t xb) {
    return (xb & 0x7fffu) > BIGX ? cos_big(xb) : __cosf(__uint_as_float(xb << 16));
}
__device__ __forceinline__ uint32_t pack_bf2(float lo, float hi) {
    uint32_t r; asm("cvt.rn.bf16x2.f32 %0, %1, %2;" : "=r"(r) : "f"(hi), "f"(lo)); return r;
}
template <int N> __device__ __forceinline__ uint32_t pick(int k, const uint32_t (&a)[N]) {
    uint32_t v = a[0];
#pragma unroll
    for (int i = 1; i < N; i++) if (k == i) v = a[i];
    return v;
}
template <int N> __device__ __forceinline__ uint2 pick(int k, const uint2 (&a)[N]) {
    uint2 v = a[0];
#pragma unroll
    for (int i = 1; i < N; i++) if (k == i) v = a[i];
    return v;
}
__device__ __forceinline__ uint32_t imul(uint32_t a, float s) { uint32_t r; asm("mul.rz.f32 %0, %1, %2;" : "=r"(r) : "r"(a), "f"(s)); return r; }
__device__ __forceinline__ uint32_t ifma(uint32_t a, float s, uint32_t c) { uint32_t r; asm("fma.rn.f32 %0, %1, %2, %3;" : "=r"(r) : "r"(a), "f"(s), "r"(c)); return r; }
__device__ __forceinline__ void side_add(uint32_t bin, uint32_t row, float a, float b, float c, float d) {
    red4(&g_ovf[bin * RPAD + row], a, b, c, d);
    g_dirty[bin * DROW + row] = 1;
}
__device__ __forceinline__ void slow_triplet(const Params& p, uint32_t ii, uint32_t oo, float c) {
    const uint2 v = __ldg(p.m + ii);
    const uint32_t bo = imul(oo, p.i2);
    side_add(bo, oo - bo * p.R2, c * bf_lo(v.x), c * bf_hi(v.x), c * bf_lo(v.y), c * bf_hi(v.y));
}
__device__ __forceinline__ void slow_rec1(const Params& p, uint32_t x, uint32_t y, uint32_t bin) {
    const uint2 v = __ldg(p.m + bin * p.R1 + (y & 0xffffu));
    const float c = bf_hi(y);
    side_add(x & 0xffu, __byte_perm(x, 0u, 0x4413) >> 3, c * bf_lo(v.x), c * bf_hi(v.x), c * bf_lo(v.y), c * bf_hi(v.y));
}
__device__ __forceinline__ uint32_t aux_of(uint32_t w0, uint32_t w1, uint32_t k = 0) {
    uint32_t u; asm("lop3.b32 %0, %1, %2, 0xf000f000, 0xe4;" : "=r"(u) : "r"(w0), "r"((w1 >> 4) + k));
    return __byte_perm(u, 0u, 0x4413);
}
__device__ __forceinline__ void slow_rec2(const Params& p, uint32_t w0, uint32_t w1, uint32_t bin, float unit) {
    side_add(bin, aux_of(w0, w1) >> 3, (float)((int)(w0 & 0xfffu) - 2048) * unit, (float)((int)(w0 >> 16 & 0xfffu) - 2048) * unit,
             (float)((int)(w1 & 0xfffu) - 2048) * unit, (float)((int)(w1 >> 16 & 0xfffu) - 2048) * unit);
}
template <uint32_t M> __device__ __forceinline__ uint32_t and_or(uint32_t a, uint32_t c) {
    uint32_t r; asm("lop3.b32 %0, %1, %2, %3, 0xea;" : "=r"(r) : "r"(a), "n"(M), "r"(c)); return r;
}
template <uint32_t M> __device__ __forceinline__ uint32_t xor_and(uint32_t a, uint32_t c) {
    uint32_t r; asm("lop3.b32 %0, %1, %2, %3, 0x48;" : "=r"(r) : "r"(a), "n"(M), "r"(c)); return r;
}
__device__ __forceinline__ uint32_t mux(uint32_t a, uint32_t b, uint32_t m) {
    uint32_t r; asm("lop3.b32 %0, %1, %2, %3, 0xd8;" : "=r"(r) : "r"(a), "r"(b), "r"(m)); return r;
}
__device__ __forceinline__ uint32_t and_xor(uint32_t a, uint32_t m, uint32_t c) {
    uint32_t r; asm("lop3.b32 %0, %1, %2, %3, 0x6a;" : "=r"(r) : "r"(a), "r"(m), "r"(c)); return r;
}
__device__ __forceinline__ uint2 ld_in(const uint2* a) {
    uint2 v; asm volatile("ld.global.nc.L1::no_allocate.v2.u32 {%0,%1}, [%2];" : "=r"(v.x), "=r"(v.y) : "l"(a)); return v;
}
__device__ __forceinline__ uint32_t ld_in(const uint32_t* a) {
    uint32_t v; asm volatile("ld.global.nc.L1::no_allocate.u32 %0, [%1];" : "=r"(v) : "l"(a)); return v;
}
__device__ __forceinline__ void ld_in4(const uint2* p, uint2& a, uint2& b) {
    asm volatile("ld.global.nc.L1::no_allocate.v4.u32 {%0,%1,%2,%3}, [%4];" : "=r"(a.x), "=r"(a.y), "=r"(b.x), "=r"(b.y) : "l"(p));
}
__device__ __forceinline__ void tex4(cudaTextureObject_t t, int i, uint2& a, uint2& b) {
    asm volatile("tex.1d.v4.u32.s32 {%0,%1,%2,%3}, [%4, {%5}];" : "=r"(a.x), "=r"(a.y), "=r"(b.x), "=r"(b.y) : "l"(t), "r"(i));
}
__device__ __forceinline__ void tex2(cudaTextureObject_t t, int i, uint32_t& a, uint32_t& b) {
    asm volatile("{ .reg .b32 z, w; tex.1d.v4.u32.s32 {%0,%1,z,w}, [%2, {%3}]; }" : "=r"(a), "=r"(b) : "l"(t), "r"(i) : "memory");
}
template <int OFF> __device__ __forceinline__ void put_rec(uint32_t ret, uint32_t lim, uint32_t addr, uint32_t x, uint32_t y) {
    asm volatile("{ .reg .pred q; setp.lt.u32 q, %0, %1; @q st.shared.v2.u32 [%2+%5], {%3,%4}; }" ::"r"(ret), "r"(lim), "r"(addr), "r"(x), "r"(y), "n"(OFF) : "memory");
}
__device__ __forceinline__ uint32_t mbar_try(uint32_t mb, uint32_t parity) {
    uint32_t ok;
    asm volatile("{ .reg .pred q; mbarrier.try_wait.parity.shared::cta.b64 q, [%1], %2; selp.u32 %0, 1, 0, q; }" : "=r"(ok) : "r"(mb), "r"(parity) : "memory");
    return ok;
}
__device__ __forceinline__ void mbar_wait(uint32_t mb, uint32_t parity) {
    if (!mbar_try(mb, parity)) {
        int it = 0;
        while (!mbar_try(mb, parity)) if (++it > SPIN_LIMIT) __trap();
    }
}
__device__ __forceinline__ void mbar_init(uint32_t mb, uint32_t n) { asm volatile("mbarrier.init.shared::cta.b64 [%0], %1;" ::"r"(mb), "r"(n) : "memory"); }
__device__ __forceinline__ void mbar_arrive(uint32_t mb) { asm volatile("mbarrier.arrive.shared::cta.b64 _, [%0];" ::"r"(mb) : "memory"); }
constexpr int B_FULL = OFF_BAR, B_OPEN = OFF_BAR + 16, B_FREE = OFF_BAR + 32;
constexpr int W_END = OFF_BAR + 40, W_SIDE = OFF_BAR + 44, W_PAR = OFF_BAR + 48, W_ROLE = OFF_BAR + 52, W_EXP = OFF_BAR + 56, W_UNIT = OFF_BAR + 60, W_NLIST = OFF_PROBE + 112, W_WRAP = OFF_PROBE + 116, W_BASE = OFF_PROBE + 120, B_TAB = OFF_PROBE + 128;
enum { BAR_S1 = 1, BAR_SIDE, BAR_PROBE, BAR_PAR, BAR_TABLE, BAR_DONE, BAR_TFREE, BAR_ACC, BAR_FLAG, BAR_H1, BAR_BASE };
constexpr int W_M1 = NS1 + NC, W_M2 = 31;

extern __shared__ __align__(1024) unsigned char smem[];
#define RTS(c, i)
#define TK_DECL
#define TK(i)
#define TK_CNT(i)
#define TK_OUT
#define TK_ARG
#define TK_PASS
#define TKS(i) TK(i)
#define TKX(i)
#define TKY(i) {}
#define TKZ(i, d)

__device__ __forceinline__ void prefetch_l2(const void* a) { asm volatile("prefetch.global.L2 [%0];" ::"l"(a)); }
__device__ __forceinline__ void wait_flags(const Params& p, uint32_t sb, int lane, uint32_t need) {
    const unsigned char* f = p.ring + M_FLAG + (lds32(sb + W_SIDE) << 12);
    int it = 0;
    while (true) {
        uint32_t a[5];
        asm volatile("ld.acquire.gpu.global.v4.u32 {%0,%1,%2,%3}, [%4];" : "=r"(a[0]), "=r"(a[1]), "=r"(a[2]), "=r"(a[3]) : "l"(f + lane * 16) : "memory");
        asm volatile("ld.acquire.gpu.global.u32 %0, [%1];" : "=r"(a[4]) : "l"(f + 512 + (lane & 3) * 4) : "memory");
        const uint32_t d = (a[0] ^ need) | (a[1] ^ need) | (a[2] ^ need) | (a[3] ^ need) | (a[4] ^ need);
        if (__all_sync(0xffffffffu, d == 0)) break;
        __nanosleep(50);
        if (++it > SPIN_LIMIT) __trap();
    }
}
__device__ __forceinline__ float exp_fast(float x) { float r; asm("ex2.approx.ftz.f32 %0, %1;" : "=f"(r) : "f"(x * 1.4426950408889634f)); return r; }
constexpr uint32_t BIAS = 0x3d803d80u, ZERO = 0x7d80u;
__device__ __forceinline__ float2 acc_fix(uint32_t old, uint32_t q) {
    const uint32_t u = old + BIAS, n = u + q - 0x08000800u;
    return make_float2((float)((int)(u & 0xffffu) + (int)(q & 0xffffu) - 2048 - (int)(n & 0xffffu)), (float)((int)(u >> 16) + (int)(q >> 16) - 2048 - (int)(n >> 16)));
}
constexpr int NE = NS1 + NC, NPAIR = (R2MAX / 2 + NE * 32 - 1) / (NE * 32), NTILE = 15, NG0 = NS1 * 8 * NTILE;
constexpr int OFF_G = OFF_M, GH = R2MAX * 8, OFF_LIST = OFF_G;
static_assert(2 * R2MAX <= R1MAX && NG0 * 16 <= WIN && NG0 + NE * 8 * NTILE >= R2MAX / 2 && NPAIR * NE * 64 <= DROW, "gates");
__device__ __forceinline__ int gate_g(int k) { return (k < NG0 ? OFF_H1 : OFF_G) + k * 16; }
__device__ __forceinline__ int gate_h(int k) { return (k < NG0 ? OFF_H1 + 0x20000 : OFF_G + GH) + k * 16; }
__device__ __forceinline__ uint2 out_row(int row, const float4& o, const float4& add, const uint2& mv) {
    const float* w = reinterpret_cast<const float*>(smem + OFF_WSM);
    const float unit = *reinterpret_cast<const float*>(smem + W_UNIT), K = 8388608.f + ZERO;
    const uint2 ac = reinterpret_cast<const uint2*>(smem + OFF_ACC)[row];
    const uint32_t* g = reinterpret_cast<const uint32_t*>(smem + gate_g(row >> 1)) + (row & 1), *h = reinterpret_cast<const uint32_t*>(smem + gate_h(row >> 1)) + (row & 1);
    const uint32_t c0 = ac.x + BIAS, c1 = ac.y + BIAS;
    const float a[4] = {fmaf(__uint_as_float(__byte_perm(c0, 0x4b00u, 0x5410)) - K, unit, o.x), fmaf(__uint_as_float(__byte_perm(c0, 0x4b00u, 0x5432)) - K, unit, o.y),
                        fmaf(__uint_as_float(__byte_perm(c1, 0x4b00u, 0x5410)) - K, unit, o.z), fmaf(__uint_as_float(__byte_perm(c1, 0x4b00u, 0x5432)) - K, unit, o.w)};
    float sd[4], uu[4];
#pragma unroll
    for (int k = 0; k < 4; k++) sd[k] = fmaf(a[3], w[12 + k], fmaf(a[2], w[8 + k], fmaf(a[1], w[4 + k], a[0] * w[k])));
    const uint32_t a01 = hmul_bf2(pack_bf2(sd[0] + add.x, sd[1] + add.y), g[0]), a23 = hmul_bf2(pack_bf2(sd[2] + add.z, sd[3] + add.w), g[2]);
#pragma unroll
    for (int k = 0; k < 4; k++) uu[k] = fmaf(bf_hi(a23), w[28 + k], fmaf(bf_lo(a23), w[24 + k], fmaf(bf_hi(a01), w[20 + k], bf_lo(a01) * w[16 + k])));
    return make_uint2(hadd_bf2(mv.x, hmul_bf2(pack_bf2(uu[0], uu[1]), h[0])), hadd_bf2(mv.y, hmul_bf2(pack_bf2(uu[2], uu[3]), h[2])));
}
__device__ __forceinline__ void mma16(float (&c)[4], const uint32_t (&a)[4], uint32_t b0, uint32_t b1) {
    asm volatile("mma.sync.aligned.m16n8k16.row.col.f32.bf16.bf16.f32 {%0,%1,%2,%3}, {%4,%5,%6,%7}, {%8,%9}, {%0,%1,%2,%3};"
                 : "+f"(c[0]), "+f"(c[1]), "+f"(c[2]), "+f"(c[3]) : "r"(a[0]), "r"(a[1]), "r"(a[2]), "r"(a[3]), "r"(b0), "r"(b1));
}
__device__ __forceinline__ void finish_rows(const Params& p, uint32_t sb) {
    int tid;
    asm volatile("mov.u32 %0, %%tid.x;" : "=r"(tid));
    const int role = lds32(sb + W_ROLE), row0 = role * p.R2, np = min(p.R2, p.E - row0) >> 1, lane = tid & 31;
    {
        const uint16_t* wg = reinterpret_cast<const uint16_t*>(lane & 16 ? p.w_rbf : p.w_sbf) + (lane & 3) * 8 + (lane >> 2 & 3);
        const uint16_t* cp = reinterpret_cast<const uint16_t*>(p.centers) + (lane & 3) * 2;
        const uint32_t wb = __ldg(wg) | (uint32_t)__ldg(wg + 4) << 16, cen = __ldg(cp) | (uint32_t)__ldg(cp + 1) << 16;
        if (tid < NS1 * 32) {
            if (tid * 32 < np) prefetch_l2(p.dist + row0 + tid * 64);
            for (int i = tid * 8; i < np; i += NS1 * 32 * 8) prefetch_l2(p.m + row0 + 2 * i);
        }
#pragma unroll 1
        for (int pass = tid >= NS1 * 32; pass < 2; pass++) {
            const int k0 = (pass ? NG0 : 0) + (tid >> 2), dk = pass ? NE * 8 : NS1 * 8;
            uint2 v[NTILE];
#pragma unroll
            for (int i = 0; i < NTILE; i++) v[i].x = ld_in(reinterpret_cast<const uint32_t*>(p.dist) + min((row0 >> 1) + k0 + i * dk, (p.E >> 1) - 1));
#pragma unroll
            for (int i = 0; i < NTILE; i++) {
                uint32_t rb[2];
#pragma unroll
                for (int u = 0; u < 2; u++) {
                    const uint32_t df = hsub_bf2(__byte_perm(v[i].x, 0u, u ? 0x3232 : 0x1010), cen);
                    const uint32_t ar = hmul_bf2(hmul_bf2(df, df), 0xc120c120u);
                    rb[u] = pack_bf2(exp_fast(bf_lo(ar)), exp_fast(bf_hi(ar)));
                }
                float c[4];
                asm volatile("mma.sync.aligned.m16n8k8.row.col.f32.bf16.bf16.f32 {%0,%1,%2,%3}, {%4,%5}, {%6}, {%7,%7,%7,%7};"
                             : "=f"(c[0]), "=f"(c[1]), "=f"(c[2]), "=f"(c[3]) : "r"(rb[0]), "r"(rb[1]), "r"(wb), "f"(0.f));
                v[i] = make_uint2(pack_bf2(c[0], c[1]), pack_bf2(c[2], c[3]));
            }
            if (pass) bar_sync(BAR_TFREE, NE * 32); else bar_sync(BAR_H1, (NS1 + 1) * 32);
            const uint32_t a = sb + (lane & 2 ? gate_h(k0) : gate_g(k0)) + (lane & 1) * 8;
#pragma unroll
            for (int i = 0; i < NTILE; i++) if (k0 + i * dk < R2MAX / 2) sts64(a + i * dk * 16, v[i].x, v[i].y);
            if (pass) TKY(1) else TKY(0)
        }
    }
    uint2 mv[2 * NPAIR];
#pragma unroll
    for (int i = 0; i < NPAIR; i++) ld_in4(p.m + 2 * min((row0 >> 1) + tid + i * NE * 32, (p.E >> 1) - 1), mv[2 * i], mv[2 * i + 1]);
    uint8_t* dirty = g_dirty + role * DROW + tid * 2;
    auto flags = [&]() {
        uint32_t f[NPAIR], m = 0;
#pragma unroll
        for (int i = 0; i < NPAIR; i++) asm volatile("ld.relaxed.gpu.global.u16 %0, [%1];" : "=r"(f[i]) : "l"(dirty + i * NE * 64) : "memory");
#pragma unroll
        for (int i = 0; i < NPAIR; i++) m |= ((f[i] | f[i] >> 7) & 3u) << 2 * i;
        return m;
    };
    auto row_of = [&](int j) { return 2 * tid + (j >> 1) * NE * 64 + (j & 1); };
    bar_sync(BAR_FLAG, (NE + 1) * 32);
    TKY(2)
    uint32_t kept = flags(), left = 0, bad = 0, at = 0;
    TKZ(3, kept)
    if (kept) {
        at = atoms_add<W_NLIST>(sb, __popc(kept));
        if (at + __popc(kept) > NG0) { left = kept; kept = 0; }
        at = sb + OFF_LIST + at * 16;
        uint32_t to = at;
#pragma unroll 1
        for (uint32_t m = kept; m; m &= m - 1) {
            float4 o[2];
            o[0] = take(&g_ovf[role * RPAD + row_of(__ffs(m) - 1)], true);
            m &= m - 1;
            o[1] = take(&g_ovf[role * RPAD + row_of(__ffs(m) - 1)], m);
            const float4* w = reinterpret_cast<const float4*>(smem + OFF_WSM);
#pragma unroll
            for (int u = 0; u < 2; u++) if (!u || m) {
                sts128<0>(to, make_uint4(__float_as_uint(fmaf(o[u].w, w[3].x, fmaf(o[u].z, w[2].x, fmaf(o[u].y, w[1].x, o[u].x * w[0].x)))),
                                         __float_as_uint(fmaf(o[u].w, w[3].y, fmaf(o[u].z, w[2].y, fmaf(o[u].y, w[1].y, o[u].x * w[0].y)))),
                                         __float_as_uint(fmaf(o[u].w, w[3].z, fmaf(o[u].z, w[2].z, fmaf(o[u].y, w[1].z, o[u].x * w[0].z)))),
                                         __float_as_uint(fmaf(o[u].w, w[3].w, fmaf(o[u].z, w[2].w, fmaf(o[u].y, w[1].w, o[u].x * w[0].w))))));
                to += 16;
            }
        }
    }
    uint32_t wb[8];
#pragma unroll
    for (int i = 0; i < 8; i++) {
        const uint32_t a = sb + OFF_WSM + ((i & 4) * 4 + (i & 1) * 8 + (i & 2) + (lane >> 2 & 1)) * 4;
        wb[i] = (lane & 3) == lane >> 3 ? __byte_perm(lds32(a), lds32(a + 16), 0x7632) : 0u;
    }
    const uint32_t k0 = (lds32(sb + W_UNIT) >> 16) * 0x10001u + 0x03800380u;
    TKX(5)
    bar_sync(BAR_ACC, (NE + NC) * 32);
    TKX(6)
    uint32_t from = at;
#pragma unroll
    for (int i = 0; i < NPAIR; i++) {
        const int k = tid + i * NE * 32;
        const uint4 ac = lds128(sb + OFF_ACC + k * 16), g = lds128(sb + gate_g(k)), h = lds128(sb + gate_h(k));
        const uint32_t u[4] = {ac.x + BIAS, ac.z + BIAS, ac.y + BIAS, ac.w + BIAS};
        uint32_t a[4];
        float c[4] = {0.f, 0.f, 0.f, 0.f}, d[4] = {0.f, 0.f, 0.f, 0.f};
#pragma unroll
        for (int j = 0; j < 2; j++)
            asm volatile("{ .reg .pred q; setp.ne.u32 q, %5, 0; @q ld.shared.v2.f32 {%0,%1}, [%4]; @q ld.shared.v2.f32 {%2,%3}, [%4+8]; @q add.u32 %4, %4, 16; }"
                         : "+f"(c[2 * j]), "+f"(c[2 * j + 1]), "+f"(d[2 * j]), "+f"(d[2 * j + 1]), "+r"(from) : "r"(kept & 1u << (2 * i + j)) : "memory");
#pragma unroll
        for (int j = 0; j < 4; j++) a[j] = hsub_bf2(and_or<0x007f007fu>(u[j] >> 9, k0 + 0x04800480u), k0 + 0x04c004c0u);
        mma16(c, a, wb[0], wb[1]); mma16(d, a, wb[2], wb[3]);
#pragma unroll
        for (int j = 0; j < 4; j++) a[j] = and_or<0x007f007fu>(u[j] >> 2, k0 + 0x01000100u);
        mma16(c, a, wb[0], wb[1]); mma16(d, a, wb[2], wb[3]);
#pragma unroll
        for (int j = 0; j < 4; j++) a[j] = and_or<0x00030003u>(u[j], k0);
        mma16(c, a, wb[0], wb[1]); mma16(d, a, wb[2], wb[3]);
        a[0] = hmul_bf2(pack_bf2(c[0], c[1]), g.x); a[1] = hmul_bf2(pack_bf2(c[2], c[3]), g.y);
        a[2] = hmul_bf2(pack_bf2(d[0], d[1]), g.z); a[3] = hmul_bf2(pack_bf2(d[2], d[3]), g.w);
#pragma unroll
        for (int j = 0; j < 4; j++) c[j] = d[j] = 0.f;
        mma16(c, a, wb[4], wb[5]); mma16(d, a, wb[6], wb[7]);
        if (k < np) {
            reinterpret_cast<uint4*>(p.out + row0)[k] = make_uint4(hadd_bf2(mv[2 * i].x, hmul_bf2(pack_bf2(c[0], c[1]), h.x)), hadd_bf2(mv[2 * i].y, hmul_bf2(pack_bf2(d[0], d[1]), h.z)),
                                                                   hadd_bf2(mv[2 * i + 1].x, hmul_bf2(pack_bf2(c[2], c[3]), h.y)), hadd_bf2(mv[2 * i + 1].y, hmul_bf2(pack_bf2(d[2], d[3]), h.w)));
            if (c[0] != c[0] || c[2] != c[2]) bad |= 3u << 2 * i;
        }
    }
    if (lds32(sb + W_WRAP)) left = flags();
#pragma unroll 1
    for (uint32_t m = left | bad; m; m &= m - 1) {
        const int j = __ffs(m) - 1, row = row_of(j);
        uint4 v = make_uint4(0u, 0u, 0u, 0u);
        if (kept >> j & 1u) v = lds128(at + __popc(kept & ((1u << j) - 1u)) * 16);
        p.out[row0 + row] = out_row(row, take(&g_ovf[role * RPAD + row], left >> j & 1u),
                                    make_float4(__uint_as_float(v.x), __uint_as_float(v.y), __uint_as_float(v.z), __uint_as_float(v.w)), p.m[row0 + row]);
    }
#pragma unroll 1
    for (uint32_t m = left | kept; m; m &= m - 1) g_dirty[role * DROW + row_of(__ffs(m) - 1)] = 0;
}

template <int HOP> __device__ __forceinline__ uint2 null_rec(int lane, uint32_t R) {
    if (HOP == 1) return make_uint2(0x800000u | H<1>::tag(R), (OFF_CNT1 - OFF_M) / 8);
    return make_uint2(0x08000800u | lane << 28, 0x0fff0000u | H<2>::tag(R));
}
template <int HOP> __device__ __forceinline__ void fill(uint32_t win, int ct, uint32_t R) {
    const uint2 v = null_rec<HOP>(ct, R);
#pragma unroll
    for (int i = 0; i < WIN / (NC * 512); i++) sts128<0>(win + ct * 16 + i * NC * 512, make_uint4(v.x, v.y, v.x, v.y));
}
template <int HOP> __device__ __forceinline__ void reset(uint32_t win, int lane, uint32_t R) {
    const uint2 v = null_rec<HOP>(lane, R);
    const uint32_t a = win + lane * 32 + H<HOP>::mark(R, lane >> 2) * 8;
#pragma unroll
    for (int i = 0; i < 16; i++) sts64(a + i * 1024, v.x, v.y);
    if (lane < 16) sts64(a + 16384, v.x, v.y);
}
__device__ __forceinline__ bool elect() {
    uint32_t q; asm volatile("{ .reg .pred q; elect.sync _|q, 0xffffffff; selp.u32 %0, 1, 0, q; }" : "=r"(q)); return q;
}
__device__ __forceinline__ const unsigned char* mk_ptr(uint32_t lo, uint32_t hi) { return reinterpret_cast<const unsigned char*>((uint64_t)hi << 32 | lo); }
__device__ __forceinline__ void bulk_store(uint32_t lo, uint32_t hi, uint32_t src, uint32_t n) {
    asm volatile("cp.async.bulk.global.shared::cta.bulk_group [%0], [%1], %2;" ::"l"(mk_ptr(lo, hi)), "r"(src), "r"(n) : "memory");
}
template <int HOP>
__device__ __forceinline__ void manager(const Params& p, uint32_t sb, int lane, int role, uint32_t base) {
    typedef H<HOP> h;
    constexpr int SMP = HOP == 1 ? SMP1 : SMP2;
    constexpr int V = h::NBIN / 32, PB = h::S * 8;
    const int RT = p.rounds + HOP - 1, lo = HOP == 1 && role >= NG ? NG : 0, hi = lo + h::NBIN;
    const int w = (role - lo) / (HOP * J), j = (role - lo - w * HOP * J) / HOP;
    const Ring rg(p.ring, __reduce_or_sync(0xffffffffu, lds32(sb + W_PAR)), 2 * w + HOP - 1);
    const uint32_t side = lds32(sb + W_SIDE), dhi = rg.main >> 32, mhi = rg.mid >> 32;
    const uint32_t c0 = HOP == 2 ? role & 1 : 0, up = (HOP == 1 && lo) ^ rg.par ^ c0;
    uint32_t dA = ((uint32_t)rg.main + src_off(j) + (c0 << 16) + (up ? 4096 : 12288)) ^ slot_off(base % 3);
    uint32_t dM = ((uint32_t)rg.mid + src_off(j) + c0 * 1024) ^ slot_off(base % 3);
    const int a0 = max(64, lo), b1 = min(68, hi);
    int n0 = (min(NHI, hi) - a0) * PB, a1 = (max(NLO, lo) - lo) * PB;
    const unsigned char* cr = reinterpret_cast<const unsigned char*>(rg.main) + MISC + ((side ^ rg.par) << 12);
    const unsigned char* cr0 = cr + cred_off(lo + lane * V), *cr1 = cr + cred_off(lo + 32 * V + min(lane, V - 1));
    const uint32_t ca0 = sb + h::CNT + lane * V * 4, ca1 = sb + h::CNT + (32 * V + min(lane, V + NDUM)) * 4;
    const uint32_t rot0 = (lane * V & 7) * 16, rot1 = lane * 16;
    uint32_t st = slot_steps(base);
    uint32_t init = h::init(base), prim = sb + h::STG + (HOP == 1 ? h::win(base) : 0u);
    uint32_t cs[5] = {0, 0, 0, 0, 0};
    auto sample = [&]() {
        if (V == 2) asm volatile("ld.relaxed.gpu.global.v2.u32 {%0,%1}, [%2];" : "=r"(cs[0]), "=r"(cs[1]) : "l"(cr0) : "memory");
        else asm volatile("ld.relaxed.gpu.global.v4.u32 {%0,%1,%2,%3}, [%4];" : "=r"(cs[0]), "=r"(cs[1]), "=r"(cs[2]), "=r"(cs[3]) : "l"(cr0) : "memory");
        cs[V] = ld_rlx32(reinterpret_cast<const uint32_t*>(cr1));
    };
    uint32_t low[5] = {rot0, rot0 + 16, rot0 + 32, rot0 + 48, rot1};
    TK_DECL
#pragma unroll 1
    for (int r = 0;; r++) {
        const uint32_t R = base + r, ninit = h::init(R + 1), done = prim;
        TK(5)
        mbar_wait(sb + B_FULL + (HOP - 1) * 8, r & 1);
        TK(0)
        if (SMP == 1) sample();
        uint32_t c[5];
        if (V == 2) asm volatile("ld.shared.v2.u32 {%0,%1}, [%2];" : "=r"(c[0]), "=r"(c[1]) : "r"(ca0) : "memory");
        else asm volatile("ld.shared.v4.u32 {%0,%1,%2,%3}, [%4];" : "=r"(c[0]), "=r"(c[1]), "=r"(c[2]), "=r"(c[3]) : "r"(ca0) : "memory");
        c[V] = lds32(ca1);
        uint32_t nc[5];
#pragma unroll
        for (int k = 0; k <= V; k++) {
            const uint32_t rot = k < V ? rot0 + k * 16 : rot1, z = ninit + (HOP == 1 ? rot : low[k]);
            if (HOP == 2) low[k] = min((max((int)(c[k] - low[k] - init - h::CAP * h::INC), 0) >> h::SH) * 128u + low[k], rot + BOXN * 128u);
            nc[k] = min(max(c[k] + (ninit - init - h::S * h::INC), z), (HOP == 1 ? z : ninit + low[k]) + (h::CAP - h::S) * h::INC);
        }
        if (V == 2) sts64(ca0, nc[0], nc[1]); else sts128<0>(ca0, make_uint4(nc[0], nc[1], nc[2], nc[3]));
        sts32(ca1, lane < V ? nc[V] : lane < V + NDUM ? DUMMY : r);
        __syncwarp();
        if (lane == 0) mbar_arrive(sb + B_OPEN + (HOP - 1) * 8);
        TK(1)
        TK(2)
        asm volatile("fence.proxy.async.shared::cta;" ::: "memory");
        TK(6)
        if (r >= D) {
            int it = 0;
            while (true) {
                uint32_t bad = 0;
#pragma unroll
                for (int k = 0; k <= V; k++) bad |= cs[k] - (R - D + 1);
                if (!__any_sync(0xffffffffu, bad >> 20)) break;
                if (++it > SPIN_LIMIT) __trap();
                if (it > 1) __nanosleep(100);
                sample();
            }
        }
        TK(3)
        if (SMP == 2) sample();
        if (elect()) {
            const uint32_t dB = (HOP == 1 ? dA ^ 0x10000u : dA) + (up ? 8192 : -8192), sm = prim + (lo ? 2 * PB : 0);
            bulk_store(dA, dhi, sm, 8192);
            bulk_store(dB, dhi, HOP == 1 ? sm + 8192 : prim + 68 * PB, 8192);
            if (n0 > 0) bulk_store(dM + (a0 - 64) * PB, mhi, prim + (a0 - lo) * PB, n0);
            if (a1 < (b1 - lo) * PB) bulk_store((dM ^ 4096u) + (uint32_t)((lo - NLO) * PB + a1), mhi, prim + a1, (b1 - lo) * PB - a1);
            asm volatile("cp.async.bulk.commit_group;" ::: "memory");
            if (r != RT - 1) asm volatile("cp.async.bulk.wait_group.read 0;" ::: "memory");
        }
        __syncwarp();
        TK(4)
        prim = HOP == 1 ? prim ^ 0x20000u : prim >= sb + 0x30000u ? sb : prim + (prim - sb) + 0x10000u;
        if (r == RT - 1) break;
        if (SMP == 3) sample();
        reset<HOP>(done, lane, R + HOP + 1);
        if (HOP == 1) {
            __syncwarp();
            if (lane == 0) mbar_arrive(sb + B_FREE);
        }
        if (RARE(r == RSPLIT || r == RT - D - 1)) {
            uint32_t n = NHI, m = NLO;
            if (r < RT - D - 1) {
                int it = 0;
                while (true) {
                    n = ld_rlx32(reinterpret_cast<const uint32_t*>(p.ring + M_CNT + (side << 12)));
                    if ((n & 0xffffu) + (n >> 16) == NB) break;
                    if (++it > SPIN_LIMIT) __trap();
                }
                m = n = min(max(__reduce_or_sync(0xffffffffu, n) & 0xffffu, (uint32_t)NLO), (uint32_t)NHI);
            }
            n0 = (min((int)n, hi) - a0) * PB;
            a1 = (max((int)m, lo) - lo) * PB;
        }
        if (HOP == 2 && RARE(r == RT - LATE)) fence_gpu();
        if (SMP == 0) sample();
        slot_next(dA, st); slot_next(dM, st);
        st = slot_rot(st);
        init = ninit;
    }
    TK_OUT
}

#define POLL_NS 200
#define POLL_NS3 400
template <int HOP> struct Reader {
    uint32_t lo, hi, st, line;
    uint32_t* cred;
    __device__ __forceinline__ void init(const Params& p, uint32_t sb, int w, int lane, int role, uint32_t base) {
        constexpr int PB = H<HOP>::S * 8;
        const int first = HOP == 1 ? (role >= NG ? NG : 0) + w * J : w * 2 * J;
        const Ring rg(p.ring, lds32(sb + W_PAR), 2 * w + HOP - 1);
        const uint32_t side = lds32(sb + W_SIDE);
        const bool mid = side ? role < 68 : role >= 64;
        const uint32_t i = role - (side ? (mid ? NLO : 68) : (mid ? 64 : 0));
        const uint32_t c = HOP == 1 ? i >> 5 : lane >> 3 & 1, in = (HOP == 1 ? (i & 31) * PB + (lane & 15) * 16 : i * PB + (lane & 7) * 16) + (lane >> 4) * src_off(3);
        lo = (in + (mid ? ((uint32_t)rg.mid ^ side << 12) + c * 1024 : (uint32_t)rg.main + (c << 16) + (side ^ rg.par ^ c ? 4096 : 12288))) ^ slot_off(base % 3);
        hi = __reduce_or_sync(0xffffffffu, (uint32_t)((mid ? rg.mid : rg.main) >> 32));
        st = slot_steps(base);
        line = opaque((HOP == 1 ? 2 * (role % NG) + (lane >> 3 & 1) : role) + (lane & 1) * 2);
        const bool both = first >= NLO && first < NHI;
        cred = lane < 1 + both ? reinterpret_cast<uint32_t*>(rg.main + MISC + (((both ? lane : first >= NG) ^ rg.par) << 12) + cred_off(role)) : nullptr;
    }
    template <int K> __device__ __forceinline__ void load1(uint2 (&v)[J]) const {
        asm volatile("ld.relaxed.gpu.global.v4.u32 {%0,%1,%2,%3}, [%4+%5];" : "=r"(v[2 * K].x), "=r"(v[2 * K].y), "=r"(v[2 * K + 1].x), "=r"(v[2 * K + 1].y)
                     : "l"(mk_ptr(lo, hi)), "n"(src_off(K)) : "memory");
    }
    static __device__ __forceinline__ uint32_t word(const uint2& v) { return HOP == 1 ? v.x : v.y; }
    template <int K> __device__ __forceinline__ void again(uint2 (&v)[J], uint32_t want, uint32_t m0, uint32_t m1, uint32_t grp) const {
        if (__ballot_sync(0xffffffffu, ((word(v[2 * K]) ^ want) & m0) | ((word(v[2 * K + 1]) ^ want) & m1)) & grp) load1<K>(v);
    }
    __device__ __forceinline__ void load(uint2 (&rec)[J]) const { load1<0>(rec); load1<1>(rec); load1<2>(rec); }
    __device__ __forceinline__ void check(uint2 (&rec)[J], uint32_t R, uint32_t ns, int lane TK_ARG) {
        const uint32_t want = H<HOP>::tag(R), mk = H<HOP>::mark(R, line);
        const uint32_t m0 = mk == 0 ? H<HOP>::TAG : 0u, m1 = mk == 1 ? H<HOP>::TAG : 0u;
        int it = 0;
        while (true) {
            uint32_t b0 = 0, b1 = 0;
#pragma unroll
            for (int j = 0; j < J; j += 2) { b0 |= word(rec[j]) ^ want; b1 |= word(rec[j + 1]) ^ want; }
            if (!__any_sync(0xffffffffu, (b0 & m0) | (b1 & m1))) break;
            if (++it > SPIN_LIMIT) __trap();
            __nanosleep(ns);
            TK_CNT(7)
            const uint32_t grp = 0xffu << (lane & 24u);
            again<0>(rec, want, m0, m1, grp); again<1>(rec, want, m0, m1, grp); again<2>(rec, want, m0, m1, grp);
        }
        if (cred) st_rlx32(cred, R + 1);
        __syncwarp();
        slot_next(lo, st);
        st = slot_rot(st);
    }
    __device__ __forceinline__ void finish() const { if (cred) st_rlx32(cred, 0u); }
};

#define NPROBE 2
__device__ __forceinline__ uint32_t probe(unsigned char* a, uint32_t zero) {
    *reinterpret_cast<uint4*>(a) = make_uint4(0u, 0u, 0u, 0u);
    *reinterpret_cast<uint4*>(a + 16) = make_uint4(0u, 0u, 0u, 0u);
    uint32_t best = ~0u, v = threadIdx.x, prev = 0;
#pragma unroll
    for (int t = 0; t <= NPROBE + 1; t++) {
        uint32_t now;
        if (t <= NPROBE) asm volatile("atom.relaxed.gpu.global.add.u32 %0, [%1], 1;" : "=r"(v) : "l"(a + (v & zero)) : "memory");
        else asm volatile("red.relaxed.gpu.global.add.u32 [%0], 1;" ::"l"(a + (v & zero)) : "memory");
        asm volatile("mov.u32 %0, %%clock;" : "=r"(now) :: "memory");
        if (t > 1) best = min(best, now - prev);
        prev = now;
    }
    return best;
}
template <bool B> struct BoolC { static constexpr bool value = B; };

__device__ __forceinline__ void stage1(const Params& p, uint32_t sb, const int pos0, int lane, const bool half) {
    typedef H<1> h;
    constexpr int NP = 4;
    static_assert(NPR == NS1 * NP * 32 - NP * 16, "tiles");
    const int RT = p.rounds;
    uint32_t ff = *reinterpret_cast<const uint16_t*>(p.ang_freq) * 0x10001u;
    auto pair_of = [&](int r, int pos) {
        const int q = r < RT - 1 ? (r * NB + blockIdx.x) * NPR + pos : (RT - 1) * NB * NPR + blockIdx.x * p.lastn + pos;
        return pos < (r < RT - 1 ? NPR : r == RT - 1 ? p.lastn : 0) && q < p.T2 ? q : -1;
    };
    uint2 vi[NP], vo[NP]; uint32_t va[NP];
    auto load_edge = [&](int r) {
#pragma unroll
        for (int u = 0; u < NP; u++) {
            const int q = max(pair_of(r, pos0 + u * 32), 0);
            vi[u] = ld_in(p.idx_in + q); vo[u] = ld_in(p.idx_out + q); va[u] = ld_in(p.angle + q);
        }
    };
    if (TEX0 && p.full) {
#pragma unroll
        for (int u = 0; u < NP; u += 2) {
            const int k = ((blockIdx.x * NPR + pos0 + lane) >> 1) + (!u ? 0 : half ? 0x40000000 : 32);
            tex2(p.ta, k, va[u], va[u + 1]); tex4(p.to, k, vo[u], vo[u + 1]); tex4(p.ti, k, vi[u], vi[u + 1]);
        }
    } else load_edge(0);
    if (blockIdx.x == 0 && pos0 == 0 && (p.T & 1)) {
        const int t = p.T - 1;
        slow_triplet(p, reinterpret_cast<const uint32_t*>(p.idx_in)[t], reinterpret_cast<const uint32_t*>(p.idx_out)[t],
                     bf16r(cos_bf(hmul_bf2(reinterpret_cast<const uint16_t*>(p.angle)[t], ff) & 0xffffu)));
    }
    ff = __reduce_or_sync(0xffffffffu, ff);
    bar_sync(BAR_S1, (NS1 + NC) * 32);
    uint32_t R = __reduce_or_sync(0xffffffffu, lds32(sb + W_BASE) & 31u);
    TK_DECL
    auto step = [&](const int r, const int qn, auto edge) {
        constexpr bool EDGE = decltype(edge)::value;
        uint32_t cc[NP], big = 0;
#pragma unroll
        for (int u = 0; u < NP; u++) {
            va[u] = hmul_bf2(va[u], ff);
            cc[u] = pack_bf2(__cosf(bf_lo(va[u])), __cosf(bf_hi(va[u])));
            big |= hmul_bf2(va[u], 0x3d003d00u);
        }
        if (RARE(big & 0x40004000u)) {
#pragma unroll 1
            for (int u = 0; u < NP; u++) {
                const uint32_t a = pick(u, va);
                float c0 = cos_bf(a & 0xffffu), c1 = cos_bf(a >> 16);
                if ((c0 != c0 || c1 != c1) && (EDGE ? pair_of(r, pos0 + u * 32) >= 0 : !half || u < 2)) {
                    const uint2 i2 = pick(u, vi), o2 = pick(u, vo);
                    if (c0 != c0) slow_triplet(p, i2.x, o2.x, c0);
                    if (c1 != c1) slow_triplet(p, i2.y, o2.y, c1);
                }
                const uint32_t v = pack_bf2(c0 != c0 ? 0.f : c0, c1 != c1 ? 0.f : c1);
#pragma unroll
                for (int k = 0; k < NP; k++) if (k == u) cc[k] = v;
            }
        }
        uint32_t bin[2 * NP], x[2 * NP], y[2 * NP];
        uint32_t dep = 0;
        auto loads = [&]() {
            const int q = qn + (dep & p.zero);
#pragma unroll
            for (int u = 0; u < NP; u += 2) {
                const int k = !u ? q : q + (half ? 0x40000000 : 32);
                tex2(p.ta, k, va[u], va[u + 1]); tex4(p.to, k, vo[u], vo[u + 1]); tex4(p.ti, k, vi[u], vi[u + 1]);
            }
        };
#pragma unroll
        for (int j = 0; j < 2 * NP; j++) {
            const uint32_t ii = j & 1 ? vi[j >> 1].y : vi[j >> 1].x, oo = j & 1 ? vo[j >> 1].y : vo[j >> 1].x;
            bin[j] = imul(ii, p.i1);
            y[j] = __byte_perm(ifma(bin[j], p.k1, ii), cc[j >> 1], j & 1 ? 0x7610 : 0x5410);
            const uint32_t bo = imul(oo, p.i2);
            x[j] = __byte_perm(ifma(bo, p.k2, imul(oo, 8.f)), bo, 0x0514);
            dep |= x[j] | y[j];
            if (EDGE && pair_of(r, pos0 + (j >> 1) * 32) < 0) bin[j] = NG + (lane & (NDUM - 1));
        }
        if (!EDGE) loads();
        else if (!LATEE) load_edge(r + 1);
        const uint32_t init = h::init(R), lim = init + ((EDGE && r == RT - 1 ? h::S : h::CAP) << h::SH);
        TKS(0)
        mbar_wait(sb + B_OPEN, ~R & 1);
        TKS(1)
        bool freed = false;
        uint32_t over = 0;
#pragma unroll
        for (int g = 0; g < 2 * NP; g += NP) if (!g || EDGE || !half) {
            constexpr int G = NP;
            uint32_t ret[G];
            int mx = 0;
#pragma unroll
            for (int j = 0; j < G; j++) ret[j] = atoms_add<h::CNT>(sb + imul(bin[g + j], 4.f), h::INC);
#pragma unroll
            for (int j = 0; j < G; j++) mx = j ? max(mx, (int)ret[j]) : (int)ret[j];
            if (!freed && __any_sync(0xffffffffu, mx >= (int)(init + 0x10000u))) { TKS(2) mbar_wait(sb + B_FREE, ~R & 1); freed = true; TKS(3) }
            TKS(2)
#pragma unroll
            for (int j = 0; j < G; j++) {
                x[g + j] = and_or<h::TAG>(ret[j], x[g + j]);
                put_rec<h::STG>(ret[j], lim, sb + and_or<0x20000u | h::PM>(ret[j], imul(bin[g + j], 256.f)), x[g + j], y[g + j]);
            }
            if (RARE(mx >= (int)lim)) {
#pragma unroll
                for (int j = 0; j < G; j++) if ((int)ret[j] >= (int)lim) over |= 1u << (g + j);
            }
        }
        __syncwarp();
        if (elect()) mbar_arrive(sb + B_FULL);
        R++;
        TKS(4)
#pragma unroll 1
        while (RARE(over)) {
            TK_CNT(7)
            const int j = __ffs(over) - 1;
            over &= over - 1;
            slow_rec1(p, pick(j, x), pick(j, y), pick(j, bin));
        }
        __syncwarp();
        if (LATEE && EDGE && r < RT - 1) load_edge(r + 1);
    };
#pragma unroll 1
    for (int q = opaque(((NB + blockIdx.x) * NPR + pos0 + lane) >> 1), r = 1; r < p.full; r++, q += NB * NPR / 2) step(r - 1, q, BoolC<false>());
#pragma unroll 1
    for (int r = max(p.full - 1, 0); r < RT; r++) step(r, 0, BoolC<true>());
    TK_OUT
}

__device__ __forceinline__ void stage2(const Params& p, uint32_t sb, int w, int lane, int role, uint32_t base1, uint32_t base) {
    typedef H<2> h;
    const int RT = p.rounds + 1;
    Reader<1> rd;
    rd.init(p, sb, w, lane, role, base1 + 3);
    uint2 rec[J];
#pragma unroll
    for (int j = 0; j < J; j++) rec[j] = null_rec<1>(lane, base1);
    uint32_t kb = sb + 0x10000u, am = 0x10000u | h::PM;
    const float unit = __uint_as_float(__reduce_or_sync(0xffffffffu, lds32(sb + W_UNIT)));
    TK_DECL
#pragma unroll 1
    for (int r = 0; r < RT; r++) {
        rd.check(rec, base1 + r, POLL_NS, lane TK_PASS);
        if (RARE(r == 1)) bar_sync(BAR_TABLE, 2 * NC * 32);
        const uint32_t want = H<1>::tag(base1 + r);
        TKS(0)
        uint2 mv[J];
#pragma unroll
        for (int j = 0; j < J; j++) {
            mv[j] = make_uint2(0u, 0u);
            const uint32_t a = sb + imul(rec[j].y & 0xffffu, 8.f);
            if (!xor_and<0x8e0000u>(rec[j].x, want)) mv[j] = lds64<OFF_M>(a);
        }
        uint32_t fl = 0;
#pragma unroll
        for (int j = 0; j < J; j++) fl |= mv[j].y;
        if (RARE(fl & 0x40000000u)) {
#pragma unroll 1
            for (int j = 0; j < J; j++) {
                const uint2 v = pick(j, mv), w = pick(j, rec);
                if ((v.y & 0x40000000u) && !((w.x ^ want) & 0x8e0000u)) {
                    if (v.x & 0x40000000u) slow_rec1(p, w.x, w.y, lds32(sb + W_ROLE) % NG);
                    else {
                        const float c = bf_hi(w.y), s = __uint_as_float(lds32(sb + W_UNIT)) * 1024.f;
                        side_add(w.x & 0xffu, __byte_perm(w.x, 0u, 0x4413) >> 3, c * (bf_lo(v.x) * s), c * (bf_hi(v.x) * s),
                                 c * (bf_lo(v.y) * s), c * (bf_hi(v.y & 0xbfffffffu) * s));
                    }
                }
            }
#pragma unroll
            for (int j = 0; j < J; j++) if (mv[j].y & 0x40000000u) rec[j].x = 0x800000u;
        }
        uint32_t w0[J], w1[J], bin[J], ret[J];
#pragma unroll
        for (int j = 0; j < J; j++) {
            const float c = bf_hi(rec[j].y), MG = 8194.0f;
            const uint32_t x = rec[j].x;
            const float v[4] = {bf_lo(mv[j].x), bf_hi(mv[j].x), bf_lo(mv[j].y), bf_hi(mv[j].y)};
            w0[j] = and_or<0xf000f000u>(x, __byte_perm(__float_as_uint(fmaf(c, v[0], MG)), __float_as_uint(fmaf(c, v[1], MG)), 0x5410));
            w1[j] = and_or<0xf000f000u>(x << 4, __byte_perm(__float_as_uint(fmaf(c, v[2], MG)), __float_as_uint(fmaf(c, v[3], MG)), 0x5410));
            bin[j] = min(xor_and<0x8e00ffu>(x, want), NB + (lane & (NDUM - 1)));
        }
        const uint32_t lim = h::init(base + r) + (r == RT - 1 ? 0x10000u : 0x20000u);
        rd.load(rec);
        TKS(1)
        mbar_wait(sb + B_OPEN + 8, (r - 1) & 1);
        TKS(2)
#pragma unroll
        for (int j = 0; j < J; j++) ret[j] = atoms_add<h::CNT>(sb + imul(bin[j], 4.f), h::INC);
        uint32_t mx = 0;
#pragma unroll
        for (int j = 0; j < J; j++) {
            w1[j] = and_or<h::TAG>(ret[j], w1[j]);
            put_rec<0>(ret[j], lim, and_xor(ret[j], am, bin[j] * 128 + kb), w0[j], w1[j]);
            mx = __viaddmax_u32(ret[j], 0u - DUMMY, mx);
        }
        __syncwarp();
        if (lane == 0) mbar_arrive(sb + B_FULL + 8);
        TKS(3)
        if (RARE(mx >= lim - DUMMY)) {
            uint32_t over = 0;
#pragma unroll
            for (int j = 0; j < J; j++) if (ret[j] - DUMMY >= lim - DUMMY) over |= 1u << j;
#pragma unroll 1
            do {
                const int j = __ffs(over) - 1;
                over &= over - 1;
                const uint32_t b = pick(j, bin), v = pick(j, ret) - lim, e = v >> h::SH, at = ((v - e * h::INC - (b & 7u) * 16u - h::CAP * 8) >> 7) + e;
                if (max(at, e) < BOXN && r < RT - LATE) g_box[(b * NB + role) * BOX + at] = make_uint2(pick(j, w0), pick(j, w1) | h::TAG);
                else slow_rec2(p, pick(j, w0), pick(j, w1), b, unit);
            } while (over);
        }
        __syncwarp();
        am = am >= 0x30000u ? 0x10000u | h::PM : am + 0x10000u;
        kb ^= am & 0x30000u;
        TKS(4)
    }
    rd.finish();
    TK_OUT
}

__device__ __forceinline__ void add_recs(uint32_t sb, int lane, const uint2 (&rec)[J], uint32_t want) {
    const uint32_t t = 0u - (lane & 1u), k = (t & 1u << 26) - (want >> 4);
    uint32_t o0[J], o1[J], g = 0;
#pragma unroll
    for (int j = 0; j < J; j++) {
        o0[j] = 0; o1[j] = 0;
        if (xor_and<0x7fffffffu>(rec[j].y, want) < 0x0ffc0000u) {
            const uint32_t a = aux_of(rec[j].x, rec[j].y, k);
            const uint32_t v0 = (rec[j].x & 0x0fff0fffu) - 0x08000800u, v1 = (rec[j].y & 0x0fff0fffu) - 0x08000800u;
            o0[j] = atoms_add<OFF_ACC>(sb + a, mux(v0, v1, t));
            o1[j] = atoms_add<OFF_ACC>(sb + (a ^ 4u), mux(v1, v0, t));
        }
    }
#pragma unroll
    for (int j = 0; j < J; j++) g |= o0[j] | o1[j];
    if (RARE(__any_sync(0xffffffffu, g & 0x80008000u))) {
#pragma unroll 1
        for (int j = 0; j < J; j++) {
            const uint2 w = pick(j, rec);
            const uint32_t aux = aux_of(w.x, w.y), p0 = pick(j, o0), p1 = pick(j, o1);
            const float2 a = acc_fix(t ? p1 : p0, w.x & 0x0fff0fffu), b = acc_fix(t ? p0 : p1, w.y & 0x0fff0fffu);
            const float unit = __uint_as_float(lds32(sb + W_UNIT));
            if (xor_and<0x7fffffffu>(w.y, want) < 0x0ffc0000u && (a.x != 0.f || a.y != 0.f || b.x != 0.f || b.y != 0.f)) {
                side_add(lds32(sb + W_ROLE), aux >> 3, a.x * unit, a.y * unit, b.x * unit, b.y * unit);
                sts32(sb + W_WRAP, 1u);
            }
            __syncwarp();
        }
    }
}
__device__ __forceinline__ void stage3(const Params& p, uint32_t sb, int w, int lane, int role, uint32_t base) {
    const int RT = p.rounds + 1;
    Reader<2> rd;
    rd.init(p, sb, w, lane, role, base);
    uint2 rec[J];
    TK_DECL
#pragma unroll 1
    for (int r = 0; r < RT; r++) {
        rd.load(rec);
        rd.check(rec, base + r, r < RT - 2 ? POLL_NS3 : 100, lane TK_PASS);
        RTS((r & 127) == 41 && w == 0, 1 + (r >> 7))
        TK(0)
        add_recs(sb, lane, rec, H<2>::tag(base + r));
        TK(1)
        if (RARE((uint32_t)(r - (RT - LATE + 1)) < 2u)) {
            static_assert(BOX == 32, "box");
            float4* box = reinterpret_cast<float4*>(g_box) + (lds32(sb + W_ROLE) * NB + (w * 2 + r - (RT - LATE + 1)) * J) * (BOX / 2) + lane;
            TKY(0)
#pragma unroll
            for (int j = 0; j < J / 2; j++) {
                const float4 v = ld_rlx128f(box + j * 32);
                rec[2 * j] = make_uint2(__float_as_uint(v.x), __float_as_uint(v.y)); rec[2 * j + 1] = make_uint2(__float_as_uint(v.z), __float_as_uint(v.w));
            }
#pragma unroll
            for (int j = 0; j < J / 2; j++) if (rec[2 * j].x) box[j * 32] = make_float4(0.f, 0.f, 0.f, 0.f);
            add_recs(sb, lane, rec, H<2>::TAG);
            TKY(1)
        }
    }
    rd.finish();
    TK_OUT
}

__device__ __forceinline__ uint32_t row_max(uint32_t x, uint32_t y) {
    const uint32_t mx = __vmaxu2(x & 0x7fff7fffu, y & 0x7fff7fffu);
    return max(mx & 0xffffu, mx >> 16);
}
__device__ __forceinline__ uint32_t amax2(uint32_t a, uint32_t b) {
    uint32_t r; asm("max.NaN.xorsign.abs.bf16x2 %0, %1, %2;" : "=r"(r) : "r"(a), "r"(b)); return r;
}
constexpr int NTAB = 9, TABC = 2 * NC * 32 * 16;
__device__ __forceinline__ void load_piece(const Params& p, uint32_t sb, int role, int i) {
    const int r0 = (role >= NG ? role - NG : role) * p.R1, n = max(min(min(p.R1, p.E - r0) * 8 - i * TABC, TABC), 0);
    asm volatile("mbarrier.arrive.expect_tx.shared::cta.b64 _, [%0], %1;" ::"r"(sb + B_TAB + i * 8), "r"(n) : "memory");
    if (n) asm volatile("cp.async.bulk.shared::cluster.global.mbarrier::complete_tx::bytes [%0], [%1], %2, [%3];"
                        ::"r"(sb + OFF_M + i * TABC), "l"(p.m + r0 + i * (TABC / 8)), "r"(n), "r"(sb + B_TAB + i * 8) : "memory");
}
static_assert(NTAB * TABC >= R1MAX * 8 && NTAB * TABC - TABC / 2 <= R1MAX * 8, "table");
constexpr int EWIN = 5;

__global__ void __launch_bounds__(NTHR, 1) fused_kernel(const Params p) {
    const int tid = threadIdx.x, lane = tid & 31;
    const int hw = __reduce_max_sync(0xffffffffu, tid >> 5);
    const uint32_t sb = __reduce_or_sync(0xffffffffu, (uint32_t)__cvta_generic_to_shared(smem));
    TKX(0)
    RTS(tid == 0, 0)
    uint32_t cta;
    asm volatile("mov.u32 %0, %%ctaid.x;" : "=r"(cta));
    if (hw != W_M1 && hw != W_M2) {
        const int job = hw < W_M1 ? hw : hw - 1;
        if (lane == 0 && job < 2 * NPAGE + 2)
            sts32(sb + OFF_PROBE + job * 4, probe(p.ring + (size_t)max(job / 2 - 1, 0) * PAGE + PROBE + (cta & 31) * 128 + (cta >> 5 & 3) * 16384 + (cta >> 7 << 20) +
                                                  ((job & 1) << 12 ^ (job < 2 ? 0x3000 : 0)), p.zero));
        if (job < 4) bar_arrive(BAR_SIDE, 5 * 32); else bar_arrive(BAR_PROBE, 27 * 32);
        TKX(1)
    }
    if (hw < NS1) {
        stage1(p, sb, hw * 128 + lane, lane, hw == NS1 - 1);
    } else if (hw == W_M1) {
        const uint32_t epoch = ld_rlx32(reinterpret_cast<const uint32_t*>(p.ring + M_BASE)) ^ 33u;
        if (lane == 0) {
            if (sb & 255u) __trap();
            mbar_init(sb + B_FULL, NS1); mbar_init(sb + B_OPEN, 1); mbar_init(sb + B_FREE, 1);
            for (int i = 0; i < NTAB; i++) mbar_init(sb + B_TAB + i * 8, 1);
            asm volatile("fence.proxy.async.shared::cta;" ::: "memory");
        }
        const uint32_t base = __reduce_or_sync(0xffffffffu, epoch) & 31u;
        if (lane == 0) { sts32(sb + W_BASE, epoch); sts64(sb + W_NLIST, 0u, 0u); }
        if (lane == 0 && (base & 1u)) { mbar_arrive(sb + B_OPEN); mbar_arrive(sb + B_FREE); }
        bar_arrive(BAR_BASE, (NC + 1) * 32);
        TKY(5)
        bar_sync(BAR_SIDE, 5 * 32);
        TKY(6)
        {
            const uint2 la = lds64<OFF_PROBE>(sb), lb = lds64<OFF_PROBE + 8>(sb);
            const uint32_t side = min(la.y, lb.y) < min(la.x, lb.x);
            uint32_t v = 0;
            if (lane == 0) {
                asm volatile("atom.relaxed.gpu.global.add.u32 %0, [%1], %2;" : "=r"(v) : "l"(p.ring + M_CNT), "r"(side ? 0x10000u : 1u) : "memory");
                asm volatile("red.relaxed.gpu.global.add.u32 [%0], %1;" ::"l"(p.ring + M_CNT + 4096), "r"(side ? 0x10000u : 1u) : "memory");
            }
            bar_sync(BAR_PROBE, 27 * 32);
            const uint2 l = lds64<OFF_PROBE + 8>(sb + min(lane, NPAGE - 1) * 8);
            const uint32_t mine = (__ballot_sync(0xffffffffu, (l.y < l.x) != side) & ~1u) | 0x80000000u;
            if (lane == 0) {
                uint32_t par;
                asm volatile("atom.relaxed.gpu.global.cas.b32 %0, [%1], 0, %2;" : "=r"(par) : "l"(p.ring + M_PAR), "r"(mine) : "memory");
                const uint32_t role = side ? NB - 1 - (v >> 16) : v & 0xffffu;
#pragma unroll 1
                for (int i = 0; i < AHEAD; i++) load_piece(p, sb, role, i);
                sts32(sb + W_ROLE, role); sts32(sb + W_SIDE, role < NLO ? 0u : role >= NHI ? 1u : side);
                sts32(sb + W_END, (epoch | 1023u) + 1u + (base + p.rounds) % 24u + ((epoch >> 5 & 31u) + p.rounds + 1) % 24u * 32u);
                sts32(sb + W_PAR, par ? par : mine);
            }
            TKX(2)
        }
        bar_arrive(BAR_PAR, (2 * NC + 2) * 32);
        manager<1>(p, sb, opaque(lane), __reduce_max_sync(0xffffffffu, lds32(sb + W_ROLE)), base);
        asm volatile("cp.async.bulk.wait_group 0;" ::: "memory");
        bar_arrive(BAR_H1, (NS1 + 1) * 32);
        TKX(4)
        {
            const int role = lds32(sb + W_ROLE);
#pragma unroll 1
            for (int i = lane * 16; i < DROW; i += 4 * 512) {
                float4 f[4];
#pragma unroll
                for (int u = 0; u < 4; u++) f[u] = ld_rlx128f(reinterpret_cast<const float4*>(g_dirty + role * DROW + i + u * 512));
#pragma unroll
                for (int u = 0; u < 4; u++) {
                    if (__float_as_uint(f[u].x) | __float_as_uint(f[u].y)) prefetch_l2(g_ovf + role * RPAD + i + u * 512);
                    if (__float_as_uint(f[u].z) | __float_as_uint(f[u].w)) prefetch_l2(g_ovf + role * RPAD + i + u * 512 + 8);
                }
            }
        }
        bar_sync(BAR_DONE, (NE + 1) * 32);
        TKY(0)
        if (lane < 2) { fence_gpu(); st_rlx32(reinterpret_cast<uint32_t*>(p.ring + M_FLAG + lane * 4096) + blockIdx.x, lds32(sb + W_END)); }
        TKY(1)
        wait_flags(p, sb, lane, lds32(sb + W_END));
        TKX(5)
        bar_arrive(BAR_FLAG, (NE + 1) * 32);
        if (blockIdx.x == 0) {
            if (lane == 0) *reinterpret_cast<uint32_t*>(p.ring + M_BASE) = lds32(sb + W_END) ^ 33u;
            if (lane < 3) *reinterpret_cast<uint32_t*>(p.ring + (lane & 2 ? M_PAR : M_CNT + (lane & 1) * 4096)) = 0;
        }
    } else if (hw == W_M2) {
        uint2 sm[16];
#pragma unroll
        for (int i = 0; i < 8; i++) ld_in4(p.m + 2 * min((i * 8 + (lane >> 2)) * (p.E >> 7) + (lane & 3), (p.E >> 1) - 1), sm[2 * i], sm[2 * i + 1]);
        const float wd = __bfloat162float(lane & 16 ? p.w_up[lane & 15] : p.w_down[lane & 15]);
        if (lane == 0) { mbar_init(sb + B_FULL + 8, NC); mbar_init(sb + B_OPEN + 8, 1); }
        sts128<OFF_HIST>(sb + lane * 16, make_uint4(0u, 0u, 0u, 0u)); sts128<OFF_HIST + 512>(sb + lane * 16, make_uint4(0u, 0u, 0u, 0u));
        __syncwarp();
#pragma unroll
        for (int i = 0; i < 16; i++) atoms_add<OFF_HIST>(sb + (row_max(sm[i].x, sm[i].y) >> 7) * 4, 1u);
        __syncwarp();
        uint32_t best = 0;
#pragma unroll 1
        for (int e = 11 + lane; e <= 230; e += 32) {
            uint32_t c = 0;
#pragma unroll
            for (int i = 0; i < EWIN; i++) c += lds32(sb + OFF_HIST + (e - i) * 4);
            best = max(best, c << 8 | (255 - e));
        }
        const uint32_t e = 255 - (__reduce_max_sync(0xffffffffu, best) & 255u);
        if (lane == 0) { sts32(sb + W_EXP, e); sts32(sb + W_UNIT, (e - 10) << 23); }
        reinterpret_cast<float*>(smem + OFF_WSM)[lane] = wd;
        TKY(5)
        bar_sync(BAR_PAR, (2 * NC + 2) * 32);
        manager<2>(p, sb, opaque(lane), __reduce_max_sync(0xffffffffu, lds32(sb + W_ROLE)), __reduce_or_sync(0xffffffffu, lds32(sb + W_BASE)) >> 5 & 31u);
        TKX(4)
        asm volatile("cp.async.bulk.wait_group 0;" ::: "memory");
    } else {
        const int w = __reduce_max_sync(0xffffffffu, hw < W_M1 ? hw - NS1 : hw - W_M1 - 1), ct = w * 32 + lane;
        if (hw < W_M1) {
            bar_sync(BAR_BASE, (NC + 1) * 32);
            const uint32_t b1 = lds32(sb + W_BASE) & 31u, b2 = lds32(sb + W_BASE) >> 5 & 31u;
            if (ct < NG + NDUM) sts32(sb + OFF_CNT1 + ct * 4, ct < NG ? H<1>::init(b1) + (ct & 7) * 16 : DUMMY);
            if (ct <= NB + NDUM) sts32(sb + OFF_CNT2 + ct * 4, ct < NB ? H<2>::init(b2) + (ct & 7) * 16 : DUMMY);
            fill<1>(sb + OFF_H1 + H<1>::win(b1), ct, b1); fill<1>(sb + OFF_H1 + H<1>::win(b1 + 1), ct, b1 + 1);
            bar_arrive(BAR_S1, (NS1 + NC) * 32);
#pragma unroll
            for (int i = 0; i < 3; i++) fill<2>(sb + H<2>::win(i), ct, b2 + i);
        }
        bar_sync(BAR_PAR, (2 * NC + 2) * 32);
        TKY(4)
        const int role = __reduce_max_sync(0xffffffffu, lds32(sb + W_ROLE));
        const uint32_t epoch = __reduce_or_sync(0xffffffffu, lds32(sb + W_BASE));
        if (hw < W_M1) {
            for (int i = ct; i < R2MAX / 2; i += NC * 32) reinterpret_cast<uint4*>(smem + OFF_ACC)[i] = make_uint4(0x40004000u, 0x40004000u, 0x40004000u, 0x40004000u);
            mbar_wait(sb + B_TAB + KDRY * 8, 0);
            stage2(p, sb, w, opaque(lane), role, (epoch & 31u) - 1u, epoch >> 5 & 31u);
        } else {
            const int e = lds32(sb + W_EXP);
            const uint32_t sc = (uint32_t)(254 - e) * 0x800080u, top = (e << 7 | 0x807fu) * 0x10001u;
            auto conv = [&](uint32_t& x, uint32_t& y) {
                const uint32_t mx = row_max(x, y);
                const int d = e - (int)(mx >> 7);
                x = hmul_bf2(x, sc); y = hmul_bf2(y, sc);
                if (d >= EWIN) y |= 0x40000000u;
                if (d < 0 || (d >= EWIN && e > 127)) { x = 0x40000000u; y = x; }
                if (mx == 0) { x = 0; y = 0; }
            };
#pragma unroll 1
            for (int i = 0; i < NTAB; i++) {
                mbar_wait(sb + B_TAB + i * 8, 0);
                if (ct == 0 && i < NTAB - AHEAD) load_piece(p, sb, role, i + AHEAD);
                const uint32_t t = sb + OFF_M + i * TABC + ct * 16, t1 = t + TABC / 2 < sb + OFF_M + R1MAX * 8 ? t + TABC / 2 : t;
                uint4 v[2] = {lds128(t), lds128(t1)};
                uint32_t ok = ~0u;
#pragma unroll
                for (int u = 0; u < 2; u++) {
                    const uint32_t a = amax2(v[u].x, v[u].y), b = amax2(v[u].z, v[u].w), mx = amax2(__byte_perm(a, b, 0x5410), __byte_perm(a, b, 0x7632)) & 0x7fff7fffu;
                    ok &= (top - mx) ^ (top - EWIN * 0x800080u - mx);
                }
                if (RARE(~ok & 0x80008000u)) {
#pragma unroll 1
                    for (int u = 0; u < 4; u++) {
                        conv(v[0].x, v[0].y);
                        const uint2 f = make_uint2(v[0].x, v[0].y);
                        v[0] = make_uint4(v[0].z, v[0].w, v[1].x, v[1].y); v[1] = make_uint4(v[1].z, v[1].w, f.x, f.y);
                    }
                } else {
#pragma unroll
                    for (int u = 0; u < 2; u++) v[u] = make_uint4(hmul_bf2(v[u].x, sc), hmul_bf2(v[u].y, sc), hmul_bf2(v[u].z, sc), hmul_bf2(v[u].w, sc));
                }
                sts128<0>(t, v[0]); sts128<0>(t1, v[1]);
                __syncwarp();
            }
            TKX(3)
            bar_sync(BAR_TABLE, 2 * NC * 32);
            stage3(p, sb, w, opaque(lane), role, epoch >> 5 & 31u);
            TKX(4)
            bar_arrive(BAR_ACC, (NE + NC) * 32);
        }
    }
    if (hw < W_M1) {
        bar_arrive(BAR_DONE, (NE + 1) * 32);
        TKX(4)
        finish_rows(p, sb);
    }
}

__global__ void fb_scatter(const uint2* __restrict__ m, const int* __restrict__ idx_in, const int* __restrict__ idx_out,
                           const uint16_t* __restrict__ angle, const __nv_bfloat16* __restrict__ ang_freq, int T, int e0, int e1) {
    const uint32_t fb = *reinterpret_cast<const uint16_t*>(ang_freq);
    for (long long t = blockIdx.x * (long long)blockDim.x + threadIdx.x; t < T; t += (long long)gridDim.x * blockDim.x) {
        int o = idx_out[t];
        if (o < e0 || o >= e1) continue;
        float c = bf16r(cos_bf(hmul_bf2(angle[t], fb) & 0xffffu));
        uint2 v = __ldg(m + idx_in[t]);
        red4(&g_ovf[o - e0], c * bf_lo(v.x), c * bf_hi(v.x), c * bf_lo(v.y), c * bf_hi(v.y));
    }
}
__global__ void fb_final(const Params p, int e0, int e1) {
    int e = e0 + blockIdx.x * blockDim.x + threadIdx.x;
    if (e >= e1) return;
    float4 a4 = g_ovf[e - e0];
    g_ovf[e - e0] = make_float4(0.f, 0.f, 0.f, 0.f);
    float a[4] = {a4.x, a4.y, a4.z, a4.w};
    float d = __bfloat162float(p.dist[e]);
    float g[4] = {0, 0, 0, 0}, h[4] = {0, 0, 0, 0};
    for (int r = 0; r < 8; r++) {
        float df = bf16r(d - __bfloat162float(p.centers[r]));
        float rb = bf16r(expf(bf16r(-10.0f * bf16r(df * df))));
        for (int k = 0; k < 4; k++) {
            g[k] += rb * __bfloat162float(p.w_sbf[r * 4 + k]);
            h[k] += rb * __bfloat162float(p.w_rbf[r * 4 + k]);
        }
    }
    float ag[4];
    for (int k = 0; k < 4; k++) {
        float s = 0.f;
        for (int j = 0; j < 4; j++) s += a[j] * __bfloat162float(p.w_down[j * 4 + k]);
        ag[k] = bf16r(s * g[k]);
    }
    uint2 mv = p.m[e];
    float mm[4] = {bf_lo(mv.x), bf_hi(mv.x), bf_lo(mv.y), bf_hi(mv.y)};
    __nv_bfloat16 o[4];
    for (int k = 0; k < 4; k++) {
        float u = 0.f;
        for (int j = 0; j < 4; j++) u += ag[j] * __bfloat162float(p.w_up[j * 4 + k]);
        o[k] = __float2bfloat16_rn(mm[k] + bf16r(bf16r(u) * bf16r(h[k])));
    }
    p.out[e] = *reinterpret_cast<uint2*>(o);
}

}

static cudaTextureObject_t make_tex(const void* ptr, size_t bytes, int words) {
    cudaResourceDesc rd = {}; cudaTextureDesc td = {};
    rd.resType = cudaResourceTypeLinear; rd.res.linear.devPtr = const_cast<void*>(ptr); rd.res.linear.sizeInBytes = bytes;
    rd.res.linear.desc = cudaCreateChannelDesc(32, words > 1 ? 32 : 0, words > 2 ? 32 : 0, words > 2 ? 32 : 0, cudaChannelFormatKindUnsigned);
    td.readMode = cudaReadModeElementType;
    cudaTextureObject_t t = 0;
    if (cudaCreateTextureObject(&t, &rd, &td, nullptr) != cudaSuccess) { t = 0; (void)cudaGetLastError(); }
    return t;
}

extern "C" void kernel_launch(void* const* d_in, const int* in_sizes, int n_in, void* d_out, int out_size) {
    typedef const __nv_bfloat16* B;
    Params p;
    p.m = (const uint2*)d_in[0]; p.idx_in = (const uint2*)d_in[1]; p.idx_out = (const uint2*)d_in[2]; p.dist = (B)d_in[3];
    p.angle = (const uint32_t*)d_in[4]; p.centers = (B)d_in[5]; p.ang_freq = (B)d_in[6]; p.w_rbf = (B)d_in[7]; p.w_sbf = (B)d_in[8];
    p.w_down = (B)d_in[9]; p.w_up = (B)d_in[10]; p.out = (uint2*)d_out;
    p.E = in_sizes[3]; p.T = in_sizes[1]; p.T2 = p.T >> 1; p.zero = 0;
    p.R1 = p.R2 = p.rounds = p.lastn = p.full = 0; p.i1 = p.i2 = p.k1 = p.k2 = 0.f;
    static int ok = -1;
    static unsigned char* ring = nullptr;
    if (ok < 0) {
        void* ra = nullptr;
        cudaGetSymbolAddress(&ra, g_ring);
        ring = reinterpret_cast<unsigned char*>(((uintptr_t)ra + PAGE - 1) & ~(uintptr_t)(PAGE - 1));
        int dev = 0, sms = 0, occ = 0;
        cudaGetDevice(&dev);
        cudaDeviceGetAttribute(&sms, cudaDevAttrMultiProcessorCount, dev);
        cudaError_t e = cudaFuncSetAttribute(fused_kernel, cudaFuncAttributeMaxDynamicSharedMemorySize, SMEM_BYTES);
        if (e == cudaSuccess) e = cudaOccupancyMaxActiveBlocksPerMultiprocessor(&occ, fused_kernel, NTHR, SMEM_BYTES);
        ok = (e == cudaSuccess && occ >= 1 && sms >= NB) ? 1 : 0;
        (void)cudaGetLastError();
    }
    p.ring = ring;
    static cudaTextureObject_t tx[3];
    static const void* of[3];
    static int of_t = -1;
    if (of[0] != d_in[1] || of[1] != d_in[2] || of[2] != d_in[4] || of_t != p.T) {
        tx[0] = make_tex(p.idx_in, (size_t)(p.T >> 2) * 16, 4); tx[1] = make_tex(p.idx_out, (size_t)(p.T >> 2) * 16, 4); tx[2] = make_tex(p.angle, (size_t)(p.T >> 2) * 8, 2);
        of[0] = d_in[1]; of[1] = d_in[2]; of[2] = d_in[4]; of_t = p.T;
    }
    p.ti = tx[0]; p.to = tx[1]; p.ta = tx[2];
    const bool fused = ok == 1 && p.E <= EMAX && p.E >= 2 * NB && p.E % 2 == 0 && p.T >= 2;
    if (fused) {
        p.R1 = ((p.E + NG - 1) / NG + 1) & ~1;
        if (p.R1 > 1024) p.R1 = (p.R1 + 15) & ~15;
        p.R2 = ((p.E + NB - 1) / NB + 1) & ~1;
        p.i1 = nextafterf(1.f / p.R1, 2.f); p.i2 = nextafterf(1.f / p.R2, 2.f); p.k1 = -(float)p.R1; p.k2 = -8.f * p.R2;
        const int per = NB * NPR;
        int full = p.T2 / per, rest = p.T2 - full * per;
        p.full = p.ti && p.to && p.ta ? full : 0;
        p.lastn = (rest + NB - 1) / NB;
        if (p.lastn > NPR / 2) { full++; p.lastn = 0; }
        if (full < D) { full = D; p.lastn = 0; }
        p.rounds = full + 1;
        fused_kernel<<<NB, NTHR, SMEM_BYTES>>>(p);
    } else {
        for (int e0 = 0; e0 < p.E; e0 += EMAX) {
            int e1 = p.E - e0 < EMAX ? p.E : e0 + EMAX;
            fb_scatter<<<1056, 256>>>(p.m, (const int*)d_in[1], (const int*)d_in[2], (const uint16_t*)d_in[4], p.ang_freq, p.T, e0, e1);
            fb_final<<<(e1 - e0 + 255) / 256, 256>>>(p, e0, e1);
        }
    }
}
```

```cpp
#include <cuda_runtime.h>
#include <cuda_bf16.h>
#include <stdint.h>
#include <math.h>

#define LATEE 0
#define AHEAD 3
#define RSPLIT (D - 1)
#define TEX0 1
#define KDRY 4
#define SMP1 0
#define SMP2 1
#define FUNR 1
#define RARE(x) __builtin_expect(!!(x), 0)
namespace {

constexpr int NB = 132, NG = 66;
constexpr int R2MAX = 6062, R1MAX = 12128;
constexpr int EMAX = NB * R2MAX;
constexpr int NTHR = 1024;
constexpr int NS1 = 8, NC = 11, J = 6;
constexpr int NPR = 960;
constexpr int D = 3;
constexpr int WIN = 16896;
constexpr int NDUM = 16;
constexpr uint32_t DUMMY = 0xc0000000u;

constexpr int OFF_ACC = WIN, OFF_BAR = OFF_ACC + R2MAX * 8;
constexpr int OFF_H1 = 0x10000 + WIN, OFF_M = OFF_H1 + WIN, OFF_PROBE = OFF_M + R1MAX * 8;
constexpr int OFF_CNT1 = OFF_H1 + 0x20000 + WIN, OFF_CNT2 = OFF_CNT1 + (NG + NDUM + 2) * 4;
constexpr int OFF_HIST = OFF_ACC;
constexpr int OFF_WSM = OFF_CNT2 + (NB + NDUM) * 4 + 16;
constexpr int SMEM_BYTES = OFF_WSM + 128;
static_assert(SMEM_BYTES <= 232448 && OFF_BAR + 64 <= 0x10000 && OFF_PROBE + 256 <= 0x30000, "smem");
static_assert(OFF_BAR % 8 == 0 && OFF_WSM % 16 == 0 && OFF_CNT2 % 16 == 0, "align");
static_assert(NC * J == NG && NC * 32 * 6 * 16 == 2 * WIN, "shape");

template <int HOP> struct H {
    static constexpr int S = HOP == 1 ? 32 : 16, NBIN = HOP == 1 ? NG : NB, CAP = 2 * S, SH = HOP == 1 ? 11 : 12;
    static constexpr int TB = HOP == 1 ? 17 : 28, CNT = HOP == 1 ? OFF_CNT1 : OFF_CNT2, STG = HOP == 1 ? OFF_H1 : 0;
    static constexpr uint32_t INC = (1u << SH) + 8u, PM = (S - 1) * 8, TAG = 7u << TB;
    static __device__ __forceinline__ uint32_t tag(uint32_t R) { return R << TB & TAG; }
    static __device__ __forceinline__ uint32_t init(uint32_t R) { return tag(R) | ((1u << TB) - 0x10000u); }
    static __device__ __forceinline__ uint32_t mark(uint32_t R, uint32_t line) { return ((HOP == 1 ? R >> 1 : R) + line) & 3u; }
    static __device__ __forceinline__ uint32_t win(int r) { return HOP == 1 ? (r & 1) << 17 : (0x310u >> (r % 3 * 4) & 3u) << 16; }
};

constexpr uint32_t PAGE = 1u << 21;
constexpr int NPAGE = NC + 2;
__device__ __align__(256) unsigned char g_ring[(size_t)(NPAGE + 1) * PAGE];
constexpr int MISC = 0xa0000;
constexpr int M_CNT = MISC + 1024, M_PAR = M_CNT + 4;
constexpr int M_BASE = M_CNT + 8;
constexpr int M_FLAG = MISC + 2048;
constexpr int PROBE = MISC + 0x40000;
__device__ __forceinline__ uint32_t cred_off(uint32_t role) { return role * 4 + min(role >> 5, 3u) * (16384 - 128); }
struct Ring {
    uint64_t main, mid;
    uint32_t par;
    __device__ __forceinline__ Ring(const unsigned char* ring, uint32_t pars, int k) {
        main = reinterpret_cast<uint64_t>(ring) + ((uint64_t)k << 20);
        par = pars >> (k >> 1) & 1u;
        mid = reinterpret_cast<uint64_t>(ring) + (uint64_t)NC * PAGE + (((k >> 3 << 20) + (k >> 2 & 1) * 0x11000u + (k & 1) * 2048) ^ (k >> 1 & 1) * 0x3000u ^ (pars >> (NC + (k >> 4)) & 1u) << 12);
    }
};
constexpr int NLO = 60, NHI = 72;
__host__ __device__ constexpr uint32_t src_off(int j) { return (j % 3) << 14 | (j / 3) << 18; }
__device__ __forceinline__ uint32_t slot_off(uint32_t s) { return (0xa930u >> s * 4 & 15u) << 16; }
__device__ __forceinline__ uint32_t slot_steps(uint32_t R) { return (uint32_t)(0x30a09030aull >> (2 - R % 3) * 8) & 0xffffffu; }
__device__ __forceinline__ void slot_next(uint32_t& a, uint32_t st) { a ^= st & 0xf0000u; }
__device__ __forceinline__ uint32_t slot_rot(uint32_t st) { return __byte_perm(st, 0u, 0x4102); }
constexpr int RPAD = 6064, DROW = 6144;
__device__ __align__(128) uint8_t g_dirty[NB * DROW];
constexpr int BOX = 32, BOXN = 24, LATE = 8;
__device__ __align__(128) uint2 g_box[NB * NB * BOX];
__device__ __align__(128) float4 g_ovf[NB * RPAD];

struct Params {
    const uint2* m; const uint2* idx_in; const uint2* idx_out; const __nv_bfloat16* dist; const uint32_t* angle;
    const __nv_bfloat16* centers; const __nv_bfloat16* ang_freq; const __nv_bfloat16* w_rbf; const __nv_bfloat16* w_sbf;
    const __nv_bfloat16* w_down; const __nv_bfloat16* w_up; uint2* out; unsigned char* ring;
    cudaTextureObject_t ti, to, ta;
    int E, T, T2, R1, R2, rounds, lastn, full; uint32_t zero; float i1, i2, k1, k2;
};

__device__ __forceinline__ float bf16r(float x) { return __bfloat162float(__float2bfloat16_rn(x)); }
__device__ __forceinline__ float bf_lo(uint32_t v) { return __uint_as_float(v << 16); }
__device__ __forceinline__ float bf_hi(uint32_t v) { return __uint_as_float(v & 0xffff0000u); }
__device__ __forceinline__ void red4(float4* a, float x, float y, float z, float w) {
    asm volatile("red.global.add.v4.f32 [%0], {%1,%2,%3,%4};" ::"l"(a), "f"(x), "f"(y), "f"(z), "f"(w) : "memory");
}
__device__ __forceinline__ void bar_sync(int id, int n) { __syncwarp(); asm volatile("bar.sync %0, %1;" ::"r"(id), "r"(n) : "memory"); }
__device__ __forceinline__ void bar_arrive(int id, int n) { __syncwarp(); asm volatile("bar.arrive %0, %1;" ::"r"(id), "r"(n) : "memory"); }
template <int OFF> __device__ __forceinline__ uint32_t atoms_add(uint32_t addr, uint32_t v) {
    uint32_t r; asm volatile("atom.shared.add.u32 %0, [%1+%3], %2;" : "=r"(r) : "r"(addr), "r"(v), "n"(OFF) : "memory"); return r;
}
__device__ __forceinline__ void sts64(uint32_t addr, uint32_t x, uint32_t y) {
    asm volatile("st.shared.v2.u32 [%0], {%1,%2};" ::"r"(addr), "r"(x), "r"(y) : "memory");
}
__device__ __forceinline__ void sts32(uint32_t addr, uint32_t x) { asm volatile("st.shared.u32 [%0], %1;" ::"r"(addr), "r"(x) : "memory"); }
template <int OFF = 0> __device__ __forceinline__ uint2 lds64(uint32_t addr) {
    uint2 v; asm volatile("ld.shared.v2.u32 {%0,%1}, [%2+%3];" : "=r"(v.x), "=r"(v.y) : "r"(addr), "n"(OFF) : "memory"); return v;
}
__device__ __forceinline__ uint32_t lds32(uint32_t addr) {
    uint32_t v; asm volatile("ld.shared.u32 %0, [%1];" : "=r"(v) : "r"(addr) : "memory"); return v;
}
template <int OFF> __device__ __forceinline__ void sts128(uint32_t a, const uint4& v) {
    asm volatile("st.shared.v4.u32 [%0+%5], {%1,%2,%3,%4};" ::"r"(a), "r"(v.x), "r"(v.y), "r"(v.z), "r"(v.w), "n"(OFF) : "memory");
}
__device__ __forceinline__ uint4 lds128(uint32_t a) {
    uint4 v; asm volatile("ld.shared.v4.u32 {%0,%1,%2,%3}, [%4];" : "=r"(v.x), "=r"(v.y), "=r"(v.z), "=r"(v.w) : "r"(a) : "memory"); return v;
}
__device__ __forceinline__ uint32_t ld_rlx32(const uint32_t* p) {
    uint32_t v; asm volatile("ld.relaxed.gpu.global.u32 %0, [%1];" : "=r"(v) : "l"(p) : "memory"); return v;
}
__device__ __forceinline__ uint2 ld_rlx64(const void* p) {
    uint2 v; asm volatile("ld.relaxed.gpu.global.v2.u32 {%0,%1}, [%2];" : "=r"(v.x), "=r"(v.y) : "l"(p) : "memory"); return v;
}
__device__ __forceinline__ float4 ld_rlx128f(const float4* p) {
    float4 v; asm volatile("ld.relaxed.gpu.global.v4.f32 {%0,%1,%2,%3}, [%4];" : "=f"(v.x), "=f"(v.y), "=f"(v.z), "=f"(v.w) : "l"(p) : "memory"); return v;
}
__device__ __forceinline__ float4 take(float4* p, bool q) {
    float4 v;
    asm volatile("{ .reg .b128 a; .reg .b64 x, y; .reg .pred q; mov.b64 x, 0; mov.b128 a, {x, x}; setp.ne.u32 q, %5, 0;\n"
                 "@q atom.relaxed.gpu.global.exch.b128 a, [%4], a; mov.b128 {x, y}, a; mov.b64 {%0,%1}, x; mov.b64 {%2,%3}, y; }"
                 : "=f"(v.x), "=f"(v.y), "=f"(v.z), "=f"(v.w) : "l"(p), "r"((uint32_t)q) : "memory");
    return v;
}
__device__ __forceinline__ void fence_gpu() { asm volatile("fence.acq_rel.gpu;" ::: "memory"); }
__device__ __forceinline__ void st_rlx32(uint32_t* p, uint32_t v) { asm volatile("st.relaxed.gpu.global.u32 [%0], %1;" ::"l"(p), "r"(v) : "memory"); }
__device__ __forceinline__ uint32_t hmul_bf2(uint32_t a, uint32_t b) {
    uint32_t r; asm("mul.rn.bf16x2 %0, %1, %2;" : "=r"(r) : "r"(a), "r"(b)); return r;
}
__device__ __forceinline__ uint32_t hsub_bf2(uint32_t a, uint32_t b) {
    uint32_t r; asm("sub.rn.bf16x2 %0, %1, %2;" : "=r"(r) : "r"(a), "r"(b)); return r;
}
__device__ __forceinline__ uint32_t hadd_bf2(uint32_t a, uint32_t b) {
    uint32_t r; asm("add.rn.bf16x2 %0, %1, %2;" : "=r"(r) : "r"(a), "r"(b)); return r;
}
__device__ __forceinline__ int opaque(int v) { return __shfl_sync(0xffffffffu, v, threadIdx.x); }
constexpr int SPIN_LIMIT = 1 << 22;

__constant__ uint32_t c_inv2pi[8] = {0u, 0x28be60dbu, 0x9391054au, 0x7f09d5f4u, 0x7d4d3770u, 0x36d8a566u, 0x4f10e410u, 0x7f9458eau};
constexpr uint32_t BIGX = 0x4280u;
__device__ __forceinline__ float cos_big(uint32_t xb) {
    uint32_t e = (xb >> 7) & 0xffu, M = (xb & 0x7fu) | 0x80u;
    uint32_t pp = e - 102u;
    uint32_t wi = pp >> 5;
    uint32_t t0 = c_inv2pi[wi], t1 = c_inv2pi[wi + 1], t2 = c_inv2pi[wi + 2];
    uint32_t f = M * __funnelshift_l(t1, t0, pp) + __umulhi(M, __funnelshift_l(t2, t1, pp));
    float c = __cosf((float)(int)f * 1.4629180792671596e-9f);
    return e == 255u ? __uint_as_float(0x7fc00000u) : c;
}
__device__ __forceinline__ float cos_bf(uint32_t xb) {
    return (xb & 0x7fffu) > BIGX ? cos_big(xb) : __cosf(__uint_as_float(xb << 16));
}
__device__ __forceinline__ uint32_t pack_bf2(float lo, float hi) {
    uint32_t r; asm("cvt.rn.bf16x2.f32 %0, %1, %2;" : "=r"(r) : "f"(hi), "f"(lo)); return r;
}
template <int N> __device__ __forceinline__ uint32_t pick(int k, const uint32_t (&a)[N]) {
    uint32_t v = a[0];
#pragma unroll
    for (int i = 1; i < N; i++) if (k == i) v = a[i];
    return v;
}
template <int N> __device__ __forceinline__ uint2 pick(int k, const uint2 (&a)[N]) {
    uint2 v = a[0];
#pragma unroll
    for (int i = 1; i < N; i++) if (k == i) v = a[i];
    return v;
}
__device__ __forceinline__ uint32_t imul(uint32_t a, float s) { uint32_t r; asm("mul.rz.f32 %0, %1, %2;" : "=r"(r) : "r"(a), "f"(s)); return r; }
__device__ __forceinline__ uint32_t ifma(uint32_t a, float s, uint32_t c) { uint32_t r; asm("fma.rn.f32 %0, %1, %2, %3;" : "=r"(r) : "r"(a), "f"(s), "r"(c)); return r; }
__device__ __forceinline__ void side_add(uint32_t bin, uint32_t row, float a, float b, float c, float d) {
    red4(&g_ovf[bin * RPAD + row], a, b, c, d);
    g_dirty[bin * DROW + row] = 1;
}
__device__ __forceinline__ void slow_triplet(const Params& p, uint32_t ii, uint32_t oo, float c) {
    const uint2 v = __ldg(p.m + ii);
    const uint32_t bo = imul(oo, p.i2);
    side_add(bo, oo - bo * p.R2, c * bf_lo(v.x), c * bf_hi(v.x), c * bf_lo(v.y), c * bf_hi(v.y));
}
__device__ __forceinline__ void slow_rec1(const Params& p, uint32_t x, uint32_t y, uint32_t bin) {
    const uint2 v = __ldg(p.m + bin * p.R1 + (y & 0xffffu));
    const float c = bf_hi(y);
    side_add(x & 0xffu, __byte_perm(x, 0u, 0x4413) >> 3, c * bf_lo(v.x), c * bf_hi(v.x), c * bf_lo(v.y), c * bf_hi(v.y));
}
__device__ __forceinline__ uint32_t aux_of(uint32_t w0, uint32_t w1, uint32_t k = 0) {
    uint32_t u; asm("lop3.b32 %0, %1, %2, 0xf000f000, 0xe4;" : "=r"(u) : "r"(w0), "r"((w1 >> 4) + k));
    return __byte_perm(u, 0u, 0x4413);
}
__device__ __forceinline__ void slow_rec2(const Params& p, uint32_t w0, uint32_t w1, uint32_t bin, float unit) {
    side_add(bin, aux_of(w0, w1) >> 3, (float)((int)(w0 & 0xfffu) - 2048) * unit, (float)((int)(w0 >> 16 & 0xfffu) - 2048) * unit,
             (float)((int)(w1 & 0xfffu) - 2048) * unit, (float)((int)(w1 >> 16 & 0xfffu) - 2048) * unit);
}
template <uint32_t M> __device__ __forceinline__ uint32_t and_or(uint32_t a, uint32_t c) {
    uint32_t r; asm("lop3.b32 %0, %1, %2, %3, 0xea;" : "=r"(r) : "r"(a), "n"(M), "r"(c)); return r;
}
template <uint32_t M> __device__ __forceinline__ uint32_t xor_and(uint32_t a, uint32_t c) {
    uint32_t r; asm("lop3.b32 %0, %1, %2, %3, 0x48;" : "=r"(r) : "r"(a), "n"(M), "r"(c)); return r;
}
__device__ __forceinline__ uint32_t mux(uint32_t a, uint32_t b, uint32_t m) {
    uint32_t r; asm("lop3.b32 %0, %1, %2, %3, 0xd8;" : "=r"(r) : "r"(a), "r"(b), "r"(m)); return r;
}
__device__ __forceinline__ uint32_t and_xor(uint32_t a, uint32_t m, uint32_t c) {
    uint32_t r; asm("lop3.b32 %0, %1, %2, %3, 0x6a;" : "=r"(r) : "r"(a), "r"(m), "r"(c)); return r;
}
__device__ __forceinline__ uint2 ld_in(const uint2* a) {
    uint2 v; asm volatile("ld.global.nc.L1::no_allocate.v2.u32 {%0,%1}, [%2];" : "=r"(v.x), "=r"(v.y) : "l"(a)); return v;
}
__device__ __forceinline__ uint32_t ld_in(const uint32_t* a) {
    uint32_t v; asm volatile("ld.global.nc.L1::no_allocate.u32 %0, [%1];" : "=r"(v) : "l"(a)); return v;
}
__device__ __forceinline__ void ld_in4(const uint2* p, uint2& a, uint2& b) {
    asm volatile("ld.global.nc.L1::no_allocate.v4.u32 {%0,%1,%2,%3}, [%4];" : "=r"(a.x), "=r"(a.y), "=r"(b.x), "=r"(b.y) : "l"(p));
}
__device__ __forceinline__ void tex4(cudaTextureObject_t t, int i, uint2& a, uint2& b) {
    asm volatile("tex.1d.v4.u32.s32 {%0,%1,%2,%3}, [%4, {%5}];" : "=r"(a.x), "=r"(a.y), "=r"(b.x), "=r"(b.y) : "l"(t), "r"(i));
}
__device__ __forceinline__ void tex2(cudaTextureObject_t t, int i, uint32_t& a, uint32_t& b) {
    asm volatile("{ .reg .b32 z, w; tex.1d.v4.u32.s32 {%0,%1,z,w}, [%2, {%3}]; }" : "=r"(a), "=r"(b) : "l"(t), "r"(i) : "memory");
}
template <int OFF> __device__ __forceinline__ void put_rec(uint32_t ret, uint32_t lim, uint32_t addr, uint32_t x, uint32_t y) {
    asm volatile("{ .reg .pred q; setp.lt.u32 q, %0, %1; @q st.shared.v2.u32 [%2+%5], {%3,%4}; }" ::"r"(ret), "r"(lim), "r"(addr), "r"(x), "r"(y), "n"(OFF) : "memory");
}
__device__ __forceinline__ uint32_t mbar_try(uint32_t mb, uint32_t parity) {
    uint32_t ok;
    asm volatile("{ .reg .pred q; mbarrier.try_wait.parity.shared::cta.b64 q, [%1], %2; selp.u32 %0, 1, 0, q; }" : "=r"(ok) : "r"(mb), "r"(parity) : "memory");
    return ok;
}
__device__ __forceinline__ void mbar_wait(uint32_t mb, uint32_t parity) {
    if (!mbar_try(mb, parity)) {
        int it = 0;
        while (!mbar_try(mb, parity)) if (++it > SPIN_LIMIT) __trap();
    }
}
__device__ __forceinline__ void mbar_init(uint32_t mb, uint32_t n) { asm volatile("mbarrier.init.shared::cta.b64 [%0], %1;" ::"r"(mb), "r"(n) : "memory"); }
__device__ __forceinline__ void mbar_arrive(uint32_t mb) { asm volatile("mbarrier.arrive.shared::cta.b64 _, [%0];" ::"r"(mb) : "memory"); }
constexpr int B_FULL = OFF_BAR, B_OPEN = OFF_BAR + 16, B_FREE = OFF_BAR + 32;
constexpr int W_END = OFF_BAR + 40, W_SIDE = OFF_BAR + 44, W_PAR = OFF_BAR + 48, W_ROLE = OFF_BAR + 52, W_EXP = OFF_BAR + 56, W_UNIT = OFF_BAR + 60, W_NLIST = OFF_PROBE + 112, W_WRAP = OFF_PROBE + 116, W_BASE = OFF_PROBE + 120, B_TAB = OFF_PROBE + 128, B_ROWS = OFF_PROBE + 248;
enum { BAR_S1 = 1, BAR_SIDE, BAR_PROBE, BAR_PAR, BAR_TABLE, BAR_DONE, BAR_TFREE, BAR_ACC, BAR_FLAG, BAR_FLAG1, BAR_H1, BAR_BASE };
constexpr int W_M1 = NS1 + NC, W_M2 = 31;

extern __shared__ __align__(1024) unsigned char smem[];
#define RTS(c, i)
#define TK_DECL
#define TK(i)
#define TK_CNT(i)
#define TK_OUT
#define TK_ARG
#define TK_PASS
#define TKS(i) TK(i)
#define TKX(i)
#define TKY(i) {}
#define TKZ(i, d)

__device__ __forceinline__ void prefetch_l2(const void* a) { asm volatile("prefetch.global.L2 [%0];" ::"l"(a)); }
__device__ __forceinline__ void wait_flags(const Params& p, uint32_t sb, int lane, uint32_t need) {
    const unsigned char* f = p.ring + M_FLAG + (lds32(sb + W_SIDE) << 12);
    int it = 0;
    while (true) {
        uint32_t a[5];
        asm volatile("ld.acquire.gpu.global.v4.u32 {%0,%1,%2,%3}, [%4];" : "=r"(a[0]), "=r"(a[1]), "=r"(a[2]), "=r"(a[3]) : "l"(f + lane * 16) : "memory");
        asm volatile("ld.acquire.gpu.global.u32 %0, [%1];" : "=r"(a[4]) : "l"(f + 512 + (lane & 3) * 4) : "memory");
        const uint32_t d = (a[0] ^ need) | (a[1] ^ need) | (a[2] ^ need) | (a[3] ^ need) | (a[4] ^ need);
        if (__all_sync(0xffffffffu, d == 0)) break;
        __nanosleep(50);
        if (++it > SPIN_LIMIT) __trap();
    }
}
__device__ __forceinline__ float exp_fast(float x) { float r; asm("ex2.approx.ftz.f32 %0, %1;" : "=f"(r) : "f"(x * 1.4426950408889634f)); return r; }
constexpr uint32_t BIAS = 0x3d803d80u, ZERO = 0x7d80u;
__device__ __forceinline__ float2 acc_fix(uint32_t old, uint32_t q) {
    const uint32_t u = old + BIAS, n = u + q - 0x08000800u;
    return make_float2((float)((int)(u & 0xffffu) + (int)(q & 0xffffu) - 2048 - (int)(n & 0xffffu)), (float)((int)(u >> 16) + (int)(q >> 16) - 2048 - (int)(n >> 16)));
}
constexpr int NE = NS1 + NC, NPAIR = (R2MAX / 2 + NE * 32 - 1) / (NE * 32), NTILE = 16, NG0 = NS1 * 8 * NTILE;
constexpr int OFF_G = OFF_M, GH = R2MAX * 8, OFF_LIST = OFF_G;
static_assert(2 * R2MAX <= R1MAX && NG0 * 16 + 112 <= WIN && 3 * NG0 >= NPAIR * NE * 32 && NPAIR * NE * 64 <= DROW, "gates");
__device__ __forceinline__ int gate_g(int k) { return (k < NG0 ? OFF_H1 : OFF_G) + k * 16; }
__device__ __forceinline__ int gate_h(int k) { return (k < NG0 ? OFF_H1 + 0x20000 : OFF_G + GH) + k * 16; }
__device__ __forceinline__ uint2 out_row(int row, const float4& o, const float4& add, const uint2& mv) {
    const float* w = reinterpret_cast<const float*>(smem + OFF_WSM);
    const float unit = *reinterpret_cast<const float*>(smem + W_UNIT), K = 8388608.f + ZERO;
    const uint2 ac = reinterpret_cast<const uint2*>(smem + OFF_ACC)[row];
    const uint32_t* g = reinterpret_cast<const uint32_t*>(smem + gate_g(row >> 1)) + (row & 1), *h = reinterpret_cast<const uint32_t*>(smem + gate_h(row >> 1)) + (row & 1);
    const uint32_t c0 = ac.x + BIAS, c1 = ac.y + BIAS;
    const float a[4] = {fmaf(__uint_as_float(__byte_perm(c0, 0x4b00u, 0x5410)) - K, unit, o.x), fmaf(__uint_as_float(__byte_perm(c0, 0x4b00u, 0x5432)) - K, unit, o.y),
                        fmaf(__uint_as_float(__byte_perm(c1, 0x4b00u, 0x5410)) - K, unit, o.z), fmaf(__uint_as_float(__byte_perm(c1, 0x4b00u, 0x5432)) - K, unit, o.w)};
    float sd[4], uu[4];
#pragma unroll
    for (int k = 0; k < 4; k++) sd[k] = fmaf(a[3], w[12 + k], fmaf(a[2], w[8 + k], fmaf(a[1], w[4 + k], a[0] * w[k])));
    const uint32_t a01 = hmul_bf2(pack_bf2(sd[0] + add.x, sd[1] + add.y), g[0]), a23 = hmul_bf2(pack_bf2(sd[2] + add.z, sd[3] + add.w), g[2]);
#pragma unroll
    for (int k = 0; k < 4; k++) uu[k] = fmaf(bf_hi(a23), w[28 + k], fmaf(bf_lo(a23), w[24 + k], fmaf(bf_hi(a01), w[20 + k], bf_lo(a01) * w[16 + k])));
    return make_uint2(hadd_bf2(mv.x, hmul_bf2(pack_bf2(uu[0], uu[1]), h[0])), hadd_bf2(mv.y, hmul_bf2(pack_bf2(uu[2], uu[3]), h[2])));
}
__device__ __forceinline__ void mma16(float (&c)[4], const uint32_t (&a)[4], uint32_t b0, uint32_t b1) {
    asm volatile("mma.sync.aligned.m16n8k16.row.col.f32.bf16.bf16.f32 {%0,%1,%2,%3}, {%4,%5,%6,%7}, {%8,%9}, {%0,%1,%2,%3};"
                 : "+f"(c[0]), "+f"(c[1]), "+f"(c[2]), "+f"(c[3]) : "r"(a[0]), "r"(a[1]), "r"(a[2]), "r"(a[3]), "r"(b0), "r"(b1));
}
__device__ __forceinline__ void finish_rows(const Params& p, uint32_t sb, bool s1) {
    int tid;
    if (s1) {
        asm volatile("mov.u32 %0, %%tid.x;" : "=r"(tid));
        const int lane = tid & 31;
        const int row0 = lds32(sb + W_ROLE) * p.R2, np = min(p.R2, p.E - row0) >> 1;
        const uint16_t* wg = reinterpret_cast<const uint16_t*>(lane & 16 ? p.w_rbf : p.w_sbf) + (lane & 3) * 8 + (lane >> 2 & 3);
        const uint16_t* cp = reinterpret_cast<const uint16_t*>(p.centers) + (lane & 3) * 2;
        const uint32_t wb = __shfl_sync(0xffffffffu, __ldg(wg) | (uint32_t)__ldg(wg + 4) << 16, tid), cen = __shfl_sync(0xffffffffu, __ldg(cp) | (uint32_t)__ldg(cp + 1) << 16, tid);
        uint32_t ds[NTILE / 4];
        int q = (row0 >> 1) + (tid >> 2) + (lane & 3) * NS1 * 8;
        auto dist = [&]() {
#pragma unroll
            for (int j = 0; j < NTILE / 4; j++) ds[j] = ld_in(reinterpret_cast<const uint32_t*>(p.dist) + min(q + j * NS1 * 32, (p.E >> 1) - 1));
            q += NG0;
        };
        dist();
        for (int i = tid * 8; i < np; i += NS1 * 32 * 8) prefetch_l2(p.m + row0 + 2 * i);
#pragma unroll 1
        for (int pass = 0; pass < 3; pass++) {
            uint2 v[NTILE];
#pragma unroll
            for (int i = 0; i < NTILE; i++) {
                const uint32_t x = __shfl_sync(0xffffffffu, ds[i >> 2], i & 3, 4);
                uint32_t rb[2];
#pragma unroll
                for (int u = 0; u < 2; u++) {
                    const uint32_t df = hsub_bf2(__byte_perm(x, 0u, u ? 0x3232 : 0x1010), cen);
                    const uint32_t ar = hmul_bf2(hmul_bf2(df, df), 0xc120c120u);
                    rb[u] = pack_bf2(exp_fast(bf_lo(ar)), exp_fast(bf_hi(ar)));
                }
                float c[4];
                asm volatile("mma.sync.aligned.m16n8k8.row.col.f32.bf16.bf16.f32 {%0,%1,%2,%3}, {%4,%5}, {%6}, {%7,%7,%7,%7};"
                             : "=f"(c[0]), "=f"(c[1]), "=f"(c[2]), "=f"(c[3]) : "r"(rb[0]), "r"(rb[1]), "r"(wb), "f"(0.f));
                v[i] = make_uint2(pack_bf2(c[0], c[1]), pack_bf2(c[2], c[3]));
            }
            if (pass < 2) {
                dist();
                if (pass) bar_sync(BAR_TFREE, NE * 32); else bar_sync(BAR_H1, (NS1 + 1) * 32);
            }
            asm volatile("mov.u32 %0, %%tid.x;" : "=r"(tid));
            const int k0 = pass * NG0 + (tid >> 2);
            const uint32_t a = sb + (tid & 2 ? gate_h(k0) : gate_g(k0)) + (tid & 1) * 8;
#pragma unroll
            for (int i = 0; i < NTILE; i++) if (i < NTILE - 1 || k0 + i * NS1 * 8 < R2MAX / 2) sts64(a + i * NS1 * 8 * 16, v[i].x, v[i].y);
            static_assert(2 * NG0 + (NTILE - 1) * NS1 * 8 <= R2MAX / 2, "gates");
            TKY(1)
        }
    } else bar_arrive(BAR_TFREE, NE * 32);
    asm volatile("mov.u32 %0, %%tid.x;" : "=r"(tid));
    const int role = lds32(sb + W_ROLE), row0 = role * p.R2, np = min(p.R2, p.E - row0) >> 1, lane = tid & 31;
    uint32_t wb[8];
#pragma unroll
    for (int i = 0; i < 8; i++) {
        const uint32_t a = sb + OFF_WSM + ((i & 4) * 4 + (i & 1) * 8 + (i & 2) + (lane >> 2 & 1)) * 4;
        wb[i] = (lane & 3) == lane >> 3 ? __byte_perm(lds32(a), lds32(a + 16), 0x7632) : 0u;
    }
    const uint32_t k0 = (lds32(sb + W_UNIT) >> 16) * 0x10001u + 0x03800380u;
    uint8_t* dirty = g_dirty + role * DROW + tid * 2;
    auto flags = [&]() {
        uint32_t f[NPAIR], m = 0;
#pragma unroll
        for (int i = 0; i < NPAIR; i++) asm volatile("ld.relaxed.gpu.global.u16 %0, [%1];" : "=r"(f[i]) : "l"(dirty + i * NE * 64) : "memory");
#pragma unroll
        for (int i = 0; i < NPAIR; i++) m |= ((f[i] | f[i] >> 7) & 3u) << 2 * i;
        return m;
    };
    auto row_of = [&](int j) { return 2 * tid + (j >> 1) * NE * 64 + (j & 1); };
    if (s1) bar_sync(BAR_FLAG1, (NS1 + 1) * 32); else bar_sync(BAR_FLAG, (NC + 1) * 32);
    TKY(2)
    uint32_t kept = flags(), left = 0, bad = 0, at = __popc(kept);
    TKZ(3, kept)
#pragma unroll
    for (int i = 1; i < 32; i *= 2) { const uint32_t t = __shfl_up_sync(0xffffffffu, at, i); if (lane >= i) at += t; }
    if (const uint32_t n = __shfl_sync(0xffffffffu, at, 31)) {
        uint32_t q = 0;
        if (lane == 0) q = atoms_add<W_NLIST>(sb, n);
        q = __shfl_sync(0xffffffffu, q, 0);
        if (q + n > NG0) { left = kept; kept = 0; }
        else {
            q = sb + OFF_LIST + q * 16;
            at = q + (at - __popc(kept)) * 16;
            uint32_t to = at;
#pragma unroll 1
            for (uint32_t m = kept; m; m &= m - 1, to += 16) sts32(to, row_of(__ffs(m) - 1));
            __syncwarp();
#pragma unroll 1
            for (to = q + lane * 16; to < q + n * 16; to += 512) {
                const float4 o = take(&g_ovf[role * RPAD + lds32(to)], true);
                const float4* w = reinterpret_cast<const float4*>(smem + OFF_WSM);
                sts128<0>(to, make_uint4(__float_as_uint(fmaf(o.w, w[3].x, fmaf(o.z, w[2].x, fmaf(o.y, w[1].x, o.x * w[0].x)))),
                                         __float_as_uint(fmaf(o.w, w[3].y, fmaf(o.z, w[2].y, fmaf(o.y, w[1].y, o.x * w[0].y)))),
                                         __float_as_uint(fmaf(o.w, w[3].z, fmaf(o.z, w[2].z, fmaf(o.y, w[1].z, o.x * w[0].z)))),
                                         __float_as_uint(fmaf(o.w, w[3].w, fmaf(o.z, w[2].w, fmaf(o.y, w[1].w, o.x * w[0].w))))));
            }
        }
    }
    mbar_wait(sb + B_ROWS, 0);
    TKX(5)
    bar_sync(BAR_ACC, (NE + NC) * 32);
    TKX(6)
    uint32_t from = at, bit = 1;
    uint4* out = reinterpret_cast<uint4*>(p.out + row0) + tid;
constexpr int FU = FUNR;
#pragma unroll FU
    for (int k = tid; bit < 1u << 2 * NPAIR; k += NE * 32, bit *= 4, out += NE * 32) {
        const uint4 ac = lds128(sb + OFF_ACC + k * 16), g = lds128(sb + gate_g(k)), h = lds128(sb + gate_h(k));
        const uint4 mv = lds128(sb + (row0 * 8 & 127) + k * 16 + (k < NG0 ? 0 : k < 2 * NG0 ? 0x10000 - NG0 * 16 : 0x30000 - NG0 * 32));
        const uint32_t u[4] = {ac.x + BIAS, ac.z + BIAS, ac.y + BIAS, ac.w + BIAS};
        uint32_t a[4];
        float c[4] = {0.f, 0.f, 0.f, 0.f}, d[4] = {0.f, 0.f, 0.f, 0.f};
#pragma unroll
        for (int j = 0; j < 2; j++)
            asm volatile("{ .reg .pred q; setp.ne.u32 q, %5, 0; @q ld.shared.v2.f32 {%0,%1}, [%4]; @q ld.shared.v2.f32 {%2,%3}, [%4+8]; @q add.u32 %4, %4, 16; }"
                         : "+f"(c[2 * j]), "+f"(c[2 * j + 1]), "+f"(d[2 * j]), "+f"(d[2 * j + 1]), "+r"(from) : "r"(kept & bit << j) : "memory");
#pragma unroll
        for (int j = 0; j < 4; j++) a[j] = hsub_bf2(and_or<0x007f007fu>(u[j] >> 9, k0 + 0x04800480u), k0 + 0x04c004c0u);
        mma16(c, a, wb[0], wb[1]); mma16(d, a, wb[2], wb[3]);
#pragma unroll
        for (int j = 0; j < 4; j++) a[j] = and_or<0x007f007fu>(u[j] >> 2, k0 + 0x01000100u);
        mma16(c, a, wb[0], wb[1]); mma16(d, a, wb[2], wb[3]);
#pragma unroll
        for (int j = 0; j < 4; j++) a[j] = and_or<0x00030003u>(u[j], k0);
        mma16(c, a, wb[0], wb[1]); mma16(d, a, wb[2], wb[3]);
        a[0] = hmul_bf2(pack_bf2(c[0], c[1]), g.x); a[1] = hmul_bf2(pack_bf2(c[2], c[3]), g.y);
        a[2] = hmul_bf2(pack_bf2(d[0], d[1]), g.z); a[3] = hmul_bf2(pack_bf2(d[2], d[3]), g.w);
#pragma unroll
        for (int j = 0; j < 4; j++) c[j] = d[j] = 0.f;
        mma16(c, a, wb[4], wb[5]); mma16(d, a, wb[6], wb[7]);
        if (k < np) {
            *out = make_uint4(hadd_bf2(mv.x, hmul_bf2(pack_bf2(c[0], c[1]), h.x)), hadd_bf2(mv.y, hmul_bf2(pack_bf2(d[0], d[1]), h.z)),
                              hadd_bf2(mv.z, hmul_bf2(pack_bf2(c[2], c[3]), h.y)), hadd_bf2(mv.w, hmul_bf2(pack_bf2(d[2], d[3]), h.w)));
            if (c[0] != c[0] || c[2] != c[2]) bad |= 3u * bit;
        }
    }
    const bool wrap = lds32(sb + W_WRAP);
    if (RARE(wrap)) left = flags();
#pragma unroll 1
    for (uint32_t m = left | bad; RARE(m); m &= m - 1) {
        const int j = __ffs(m) - 1, row = row_of(j);
        uint4 v = make_uint4(0u, 0u, 0u, 0u);
        if (kept >> j & 1u) v = lds128(at + __popc(kept & ((1u << j) - 1u)) * 16);
        p.out[row0 + row] = out_row(row, take(&g_ovf[role * RPAD + row], left >> j & 1u),
                                    make_float4(__uint_as_float(v.x), __uint_as_float(v.y), __uint_as_float(v.z), __uint_as_float(v.w)), p.m[row0 + row]);
        if (wrap) g_dirty[role * DROW + row] = 0;
    }
}

template <int HOP> __device__ __forceinline__ uint2 null_rec(int lane, uint32_t R) {
    if (HOP == 1) return make_uint2(0x800000u | H<1>::tag(R), (OFF_CNT1 - OFF_M) / 8);
    return make_uint2(0x08000800u | lane << 28, 0x0fff0000u | H<2>::tag(R));
}
template <int HOP> __device__ __forceinline__ void fill(uint32_t win, int ct, uint32_t R) {
    const uint2 v = null_rec<HOP>(ct, R);
#pragma unroll
    for (int i = 0; i < WIN / (NC * 512); i++) sts128<0>(win + ct * 16 + i * NC * 512, make_uint4(v.x, v.y, v.x, v.y));
}
template <int HOP> __device__ __forceinline__ void reset(uint32_t win, int lane, uint32_t R) {
    const uint2 v = null_rec<HOP>(lane, R);
    const uint32_t a = win + lane * 32 + H<HOP>::mark(R, lane >> 2) * 8;
#pragma unroll
    for (int i = 0; i < 16; i++) sts64(a + i * 1024, v.x, v.y);
    if (lane < 16) sts64(a + 16384, v.x, v.y);
}
__device__ __forceinline__ bool elect() {
    uint32_t q; asm volatile("{ .reg .pred q; elect.sync _|q, 0xffffffff; selp.u32 %0, 1, 0, q; }" : "=r"(q)); return q;
}
__device__ __forceinline__ const unsigned char* mk_ptr(uint32_t lo, uint32_t hi) { return reinterpret_cast<const unsigned char*>((uint64_t)hi << 32 | lo); }
__device__ __forceinline__ void bulk_store(uint32_t lo, uint32_t hi, uint32_t src, uint32_t n) {
    asm volatile("cp.async.bulk.global.shared::cta.bulk_group [%0], [%1], %2;" ::"l"(mk_ptr(lo, hi)), "r"(src), "r"(n) : "memory");
}
template <int HOP>
__device__ __forceinline__ void manager(const Params& p, uint32_t sb, int lane, int role, uint32_t base) {
    typedef H<HOP> h;
    constexpr int SMP = HOP == 1 ? SMP1 : SMP2;
    constexpr int V = h::NBIN / 32, PB = h::S * 8;
    const int RT = p.rounds + HOP - 1, lo = HOP == 1 && role >= NG ? NG : 0, hi = lo + h::NBIN;
    const int w = (role - lo) / (HOP * J), j = (role - lo - w * HOP * J) / HOP;
    const Ring rg(p.ring, __reduce_or_sync(0xffffffffu, lds32(sb + W_PAR)), 2 * w + HOP - 1);
    const uint32_t side = lds32(sb + W_SIDE), dhi = rg.main >> 32, mhi = rg.mid >> 32;
    const uint32_t c0 = HOP == 2 ? role & 1 : 0, up = (HOP == 1 && lo) ^ rg.par ^ c0;
    uint32_t dA = ((uint32_t)rg.main + src_off(j) + (c0 << 16) + (up ? 4096 : 12288)) ^ slot_off(base % 3);
    uint32_t dM = ((uint32_t)rg.mid + src_off(j) + c0 * 1024) ^ slot_off(base % 3);
    const int a0 = max(64, lo), b1 = min(68, hi);
    int n0 = (min(NHI, hi) - a0) * PB, a1 = (max(NLO, lo) - lo) * PB;
    const unsigned char* cr = reinterpret_cast<const unsigned char*>(rg.main) + MISC + ((side ^ rg.par) << 12);
    const unsigned char* cr0 = cr + cred_off(lo + lane * V), *cr1 = cr + cred_off(lo + 32 * V + min(lane, V - 1));
    const uint32_t ca0 = sb + h::CNT + lane * V * 4, ca1 = sb + h::CNT + (32 * V + min(lane, V + NDUM)) * 4;
    const uint32_t rot0 = (lane * V & 7) * 16, rot1 = lane * 16;
    uint32_t st = slot_steps(base);
    uint32_t init = h::init(base), prim = sb + h::STG + (HOP == 1 ? h::win(base) : 0u);
    uint32_t cs[5] = {0, 0, 0, 0, 0};
    auto sample = [&]() {
        if (V == 2) asm volatile("ld.relaxed.gpu.global.v2.u32 {%0,%1}, [%2];" : "=r"(cs[0]), "=r"(cs[1]) : "l"(cr0) : "memory");
        else asm volatile("ld.relaxed.gpu.global.v4.u32 {%0,%1,%2,%3}, [%4];" : "=r"(cs[0]), "=r"(cs[1]), "=r"(cs[2]), "=r"(cs[3]) : "l"(cr0) : "memory");
        cs[V] = ld_rlx32(reinterpret_cast<const uint32_t*>(cr1));
    };
    uint32_t low[5] = {rot0, rot0 + 16, rot0 + 32, rot0 + 48, rot1};
    TK_DECL
#pragma unroll 1
    for (int r = 0;; r++) {
        const uint32_t R = base + r, ninit = h::init(R + 1), done = prim;
        TK(5)
        mbar_wait(sb + B_FULL + (HOP - 1) * 8, r & 1);
        TK(0)
        if (SMP == 1) sample();
        uint32_t c[5];
        if (V == 2) asm volatile("ld.shared.v2.u32 {%0,%1}, [%2];" : "=r"(c[0]), "=r"(c[1]) : "r"(ca0) : "memory");
        else asm volatile("ld.shared.v4.u32 {%0,%1,%2,%3}, [%4];" : "=r"(c[0]), "=r"(c[1]), "=r"(c[2]), "=r"(c[3]) : "r"(ca0) : "memory");
        c[V] = lds32(ca1);
        uint32_t nc[5];
#pragma unroll
        for (int k = 0; k <= V; k++) {
            const uint32_t rot = k < V ? rot0 + k * 16 : rot1, z = ninit + (HOP == 1 ? rot : low[k]);
            if (HOP == 2) low[k] = min((max((int)(c[k] - low[k] - init - h::CAP * h::INC), 0) >> h::SH) * 128u + low[k], rot + BOXN * 128u);
            nc[k] = min(max(c[k] + (ninit - init - h::S * h::INC), z), (HOP == 1 ? z : ninit + low[k]) + (h::CAP - h::S) * h::INC);
        }
        if (V == 2) sts64(ca0, nc[0], nc[1]); else sts128<0>(ca0, make_uint4(nc[0], nc[1], nc[2], nc[3]));
        sts32(ca1, lane < V ? nc[V] : lane < V + NDUM ? DUMMY : r);
        __syncwarp();
        if (lane == 0) mbar_arrive(sb + B_OPEN + (HOP - 1) * 8);
        TK(1)
        TK(2)
        asm volatile("fence.proxy.async.shared::cta;" ::: "memory");
        TK(6)
        if (r >= D) {
            int it = 0;
            while (true) {
                uint32_t bad = 0;
#pragma unroll
                for (int k = 0; k <= V; k++) bad |= cs[k] - (R - D + 1);
                if (!__any_sync(0xffffffffu, bad >> 20)) break;
                if (++it > SPIN_LIMIT) __trap();
                if (it > 1) __nanosleep(100);
                sample();
            }
        }
        TK(3)
        if (SMP == 2) sample();
        if (elect()) {
            const uint32_t dB = (HOP == 1 ? dA ^ 0x10000u : dA) + (up ? 8192 : -8192), sm = prim + (lo ? 2 * PB : 0);
            bulk_store(dA, dhi, sm, 8192);
            bulk_store(dB, dhi, HOP == 1 ? sm + 8192 : prim + 68 * PB, 8192);
            if (n0 > 0) bulk_store(dM + (a0 - 64) * PB, mhi, prim + (a0 - lo) * PB, n0);
            if (a1 < (b1 - lo) * PB) bulk_store((dM ^ 4096u) + (uint32_t)((lo - NLO) * PB + a1), mhi, prim + a1, (b1 - lo) * PB - a1);
            asm volatile("cp.async.bulk.commit_group;" ::: "memory");
            if (r != RT - 1) asm volatile("cp.async.bulk.wait_group.read 0;" ::: "memory");
        }
        __syncwarp();
        TK(4)
        prim = HOP == 1 ? prim ^ 0x20000u : prim >= sb + 0x30000u ? sb : prim + (prim - sb) + 0x10000u;
        if (r == RT - 1) break;
        if (SMP == 3) sample();
        reset<HOP>(done, lane, R + HOP + 1);
        if (HOP == 1) {
            __syncwarp();
            if (lane == 0) mbar_arrive(sb + B_FREE);
        }
        if (RARE(r == RSPLIT || r == RT - D - 1)) {
            uint32_t n = NHI, m = NLO;
            if (r < RT - D - 1) {
                int it = 0;
                while (true) {
                    n = ld_rlx32(reinterpret_cast<const uint32_t*>(p.ring + M_CNT + (side << 12)));
                    if ((n & 0xffffu) + (n >> 16) == NB) break;
                    if (++it > SPIN_LIMIT) __trap();
                }
                m = n = min(max(__reduce_or_sync(0xffffffffu, n) & 0xffffu, (uint32_t)NLO), (uint32_t)NHI);
            }
            n0 = (min((int)n, hi) - a0) * PB;
            a1 = (max((int)m, lo) - lo) * PB;
        }
        if (HOP == 2 && RARE(r == RT - LATE)) fence_gpu();
        if (SMP == 0) sample();
        slot_next(dA, st); slot_next(dM, st);
        st = slot_rot(st);
        init = ninit;
    }
    TK_OUT
}

#define POLL_NS 200
#define POLL_NS3 400
template <int HOP> struct Reader {
    uint32_t lo, hi, st, line;
    uint32_t* cred;
    __device__ __forceinline__ void init(const Params& p, uint32_t sb, int w, int lane, int role, uint32_t base) {
        constexpr int PB = H<HOP>::S * 8;
        const int first = HOP == 1 ? (role >= NG ? NG : 0) + w * J : w * 2 * J;
        const Ring rg(p.ring, lds32(sb + W_PAR), 2 * w + HOP - 1);
        const uint32_t side = lds32(sb + W_SIDE);
        const bool mid = side ? role < 68 : role >= 64;
        const uint32_t i = role - (side ? (mid ? NLO : 68) : (mid ? 64 : 0));
        const uint32_t c = HOP == 1 ? i >> 5 : lane >> 3 & 1, in = (HOP == 1 ? (i & 31) * PB + (lane & 15) * 16 : i * PB + (lane & 7) * 16) + (lane >> 4) * src_off(3);
        lo = (in + (mid ? ((uint32_t)rg.mid ^ side << 12) + c * 1024 : (uint32_t)rg.main + (c << 16) + (side ^ rg.par ^ c ? 4096 : 12288))) ^ slot_off(base % 3);
        hi = __reduce_or_sync(0xffffffffu, (uint32_t)((mid ? rg.mid : rg.main) >> 32));
        st = slot_steps(base);
        line = opaque((HOP == 1 ? 2 * (role % NG) + (lane >> 3 & 1) : role) + (lane & 1) * 2);
        const bool both = first >= NLO && first < NHI;
        cred = lane < 1 + both ? reinterpret_cast<uint32_t*>(rg.main + MISC + (((both ? lane : first >= NG) ^ rg.par) << 12) + cred_off(role)) : nullptr;
    }
    template <int K> __device__ __forceinline__ void load1(uint2 (&v)[J]) const {
        asm volatile("ld.relaxed.gpu.global.v4.u32 {%0,%1,%2,%3}, [%4+%5];" : "=r"(v[2 * K].x), "=r"(v[2 * K].y), "=r"(v[2 * K + 1].x), "=r"(v[2 * K + 1].y)
                     : "l"(mk_ptr(lo, hi)), "n"(src_off(K)) : "memory");
    }
    static __device__ __forceinline__ uint32_t word(const uint2& v) { return HOP == 1 ? v.x : v.y; }
    template <int K> __device__ __forceinline__ void again(uint2 (&v)[J], uint32_t want, uint32_t m0, uint32_t m1, uint32_t grp) const {
        if (__ballot_sync(0xffffffffu, ((word(v[2 * K]) ^ want) & m0) | ((word(v[2 * K + 1]) ^ want) & m1)) & grp) load1<K>(v);
    }
    __device__ __forceinline__ void load(uint2 (&rec)[J]) const { load1<0>(rec); load1<1>(rec); load1<2>(rec); }
    __device__ __forceinline__ void check(uint2 (&rec)[J], uint32_t R, uint32_t ns, int lane TK_ARG) {
        const uint32_t want = H<HOP>::tag(R), mk = H<HOP>::mark(R, line);
        const uint32_t m0 = mk == 0 ? H<HOP>::TAG : 0u, m1 = mk == 1 ? H<HOP>::TAG : 0u;
        int it = 0;
        while (true) {
            uint32_t b0 = 0, b1 = 0;
#pragma unroll
            for (int j = 0; j < J; j += 2) { b0 |= word(rec[j]) ^ want; b1 |= word(rec[j + 1]) ^ want; }
            if (!__any_sync(0xffffffffu, (b0 & m0) | (b1 & m1))) break;
            if (++it > SPIN_LIMIT) __trap();
            __nanosleep(ns);
            TK_CNT(7)
            const uint32_t grp = 0xffu << (lane & 24u);
            again<0>(rec, want, m0, m1, grp); again<1>(rec, want, m0, m1, grp); again<2>(rec, want, m0, m1, grp);
        }
        if (cred) st_rlx32(cred, R + 1);
        __syncwarp();
        slot_next(lo, st);
        st = slot_rot(st);
    }
    __device__ __forceinline__ void finish() const { if (cred) st_rlx32(cred, 0u); }
};

#define NPROBE 2
__device__ __forceinline__ uint32_t probe(unsigned char* a, uint32_t zero) {
    *reinterpret_cast<uint4*>(a) = make_uint4(0u, 0u, 0u, 0u);
    *reinterpret_cast<uint4*>(a + 16) = make_uint4(0u, 0u, 0u, 0u);
    uint32_t best = ~0u, v = threadIdx.x, prev = 0;
#pragma unroll
    for (int t = 0; t <= NPROBE + 1; t++) {
        uint32_t now;
        if (t <= NPROBE) asm volatile("atom.relaxed.gpu.global.add.u32 %0, [%1], 1;" : "=r"(v) : "l"(a + (v & zero)) : "memory");
        else asm volatile("red.relaxed.gpu.global.add.u32 [%0], 1;" ::"l"(a + (v & zero)) : "memory");
        asm volatile("mov.u32 %0, %%clock;" : "=r"(now) :: "memory");
        if (t > 1) best = min(best, now - prev);
        prev = now;
    }
    return best;
}
template <bool B> struct BoolC { static constexpr bool value = B; };

__device__ __forceinline__ void stage1(const Params& p, uint32_t sb, const int pos0, int lane, const bool half) {
    typedef H<1> h;
    constexpr int NP = 4;
    static_assert(NPR == NS1 * NP * 32 - NP * 16, "tiles");
    const int RT = p.rounds;
    uint32_t ff = *reinterpret_cast<const uint16_t*>(p.ang_freq) * 0x10001u;
    auto pair_of = [&](int r, int pos) {
        const int q = r < RT - 1 ? (r * NB + blockIdx.x) * NPR + pos : (RT - 1) * NB * NPR + blockIdx.x * p.lastn + pos;
        return pos < (r < RT - 1 ? NPR : r == RT - 1 ? p.lastn : 0) && q < p.T2 ? q : -1;
    };
    uint2 vi[NP], vo[NP]; uint32_t va[NP];
    auto load_edge = [&](int r) {
#pragma unroll
        for (int u = 0; u < NP; u++) {
            const int q = max(pair_of(r, pos0 + u * 32), 0);
            vi[u] = ld_in(p.idx_in + q); vo[u] = ld_in(p.idx_out + q); va[u] = ld_in(p.angle + q);
        }
    };
    if (TEX0 && p.full) {
#pragma unroll
        for (int u = 0; u < NP; u += 2) {
            const int k = ((blockIdx.x * NPR + pos0 + lane) >> 1) + (!u ? 0 : half ? 0x40000000 : 32);
            tex2(p.ta, k, va[u], va[u + 1]); tex4(p.to, k, vo[u], vo[u + 1]); tex4(p.ti, k, vi[u], vi[u + 1]);
        }
    } else load_edge(0);
    if (blockIdx.x == 0 && pos0 == 0 && (p.T & 1)) {
        const int t = p.T - 1;
        slow_triplet(p, reinterpret_cast<const uint32_t*>(p.idx_in)[t], reinterpret_cast<const uint32_t*>(p.idx_out)[t],
                     bf16r(cos_bf(hmul_bf2(reinterpret_cast<const uint16_t*>(p.angle)[t], ff) & 0xffffu)));
    }
    ff = __reduce_or_sync(0xffffffffu, ff);
    bar_sync(BAR_S1, (NS1 + NC) * 32);
    uint32_t R = __reduce_or_sync(0xffffffffu, lds32(sb + W_BASE) & 31u);
    TK_DECL
    auto step = [&](const int r, const int qn, auto edge) {
        constexpr bool EDGE = decltype(edge)::value;
        uint32_t cc[NP], big = 0;
#pragma unroll
        for (int u = 0; u < NP; u++) {
            va[u] = hmul_bf2(va[u], ff);
            cc[u] = pack_bf2(__cosf(bf_lo(va[u])), __cosf(bf_hi(va[u])));
            big |= hmul_bf2(va[u], 0x3d003d00u);
        }
        if (RARE(big & 0x40004000u)) {
#pragma unroll 1
            for (int u = 0; u < NP; u++) {
                const uint32_t a = pick(u, va);
                float c0 = cos_bf(a & 0xffffu), c1 = cos_bf(a >> 16);
                if ((c0 != c0 || c1 != c1) && (EDGE ? pair_of(r, pos0 + u * 32) >= 0 : !half || u < 2)) {
                    const uint2 i2 = pick(u, vi), o2 = pick(u, vo);
                    if (c0 != c0) slow_triplet(p, i2.x, o2.x, c0);
                    if (c1 != c1) slow_triplet(p, i2.y, o2.y, c1);
                }
                const uint32_t v = pack_bf2(c0 != c0 ? 0.f : c0, c1 != c1 ? 0.f : c1);
#pragma unroll
                for (int k = 0; k < NP; k++) if (k == u) cc[k] = v;
            }
        }
        uint32_t bin[2 * NP], x[2 * NP], y[2 * NP];
        uint32_t dep = 0;
        auto loads = [&]() {
            const int q = qn + (dep & p.zero);
#pragma unroll
            for (int u = 0; u < NP; u += 2) {
                const int k = !u ? q : q + (half ? 0x40000000 : 32);
                tex2(p.ta, k, va[u], va[u + 1]); tex4(p.to, k, vo[u], vo[u + 1]); tex4(p.ti, k, vi[u], vi[u + 1]);
            }
        };
#pragma unroll
        for (int j = 0; j < 2 * NP; j++) {
            const uint32_t ii = j & 1 ? vi[j >> 1].y : vi[j >> 1].x, oo = j & 1 ? vo[j >> 1].y : vo[j >> 1].x;
            bin[j] = imul(ii, p.i1);
            y[j] = __byte_perm(ifma(bin[j], p.k1, ii), cc[j >> 1], j & 1 ? 0x7610 : 0x5410);
            const uint32_t bo = imul(oo, p.i2);
            x[j] = __byte_perm(ifma(bo, p.k2, imul(oo, 8.f)), bo, 0x0514);
            dep |= x[j] | y[j];
            if (EDGE && pair_of(r, pos0 + (j >> 1) * 32) < 0) bin[j] = NG + (lane & (NDUM - 1));
        }
        if (!EDGE) loads();
        else if (!LATEE) load_edge(r + 1);
        const uint32_t init = h::init(R), lim = init + ((EDGE && r == RT - 1 ? h::S : h::CAP) << h::SH);
        TKS(0)
        mbar_wait(sb + B_OPEN, ~R & 1);
        TKS(1)
        bool freed = false;
        uint32_t over = 0;
#pragma unroll
        for (int g = 0; g < 2 * NP; g += NP) if (!g || EDGE || !half) {
            constexpr int G = NP;
            uint32_t ret[G];
            int mx = 0;
#pragma unroll
            for (int j = 0; j < G; j++) ret[j] = atoms_add<h::CNT>(sb + imul(bin[g + j], 4.f), h::INC);
#pragma unroll
            for (int j = 0; j < G; j++) mx = j ? max(mx, (int)ret[j]) : (int)ret[j];
            if (!freed && __any_sync(0xffffffffu, mx >= (int)(init + 0x10000u))) { TKS(2) mbar_wait(sb + B_FREE, ~R & 1); freed = true; TKS(3) }
            TKS(2)
#pragma unroll
            for (int j = 0; j < G; j++) {
                x[g + j] = and_or<h::TAG>(ret[j], x[g + j]);
                put_rec<h::STG>(ret[j], lim, sb + and_or<0x20000u | h::PM>(ret[j], imul(bin[g + j], 256.f)), x[g + j], y[g + j]);
            }
            if (RARE(mx >= (int)lim)) {
#pragma unroll
                for (int j = 0; j < G; j++) if ((int)ret[j] >= (int)lim) over |= 1u << (g + j);
            }
        }
        __syncwarp();
        if (elect()) mbar_arrive(sb + B_FULL);
        R++;
        TKS(4)
#pragma unroll 1
        while (RARE(over)) {
            TK_CNT(7)
            const int j = __ffs(over) - 1;
            over &= over - 1;
            slow_rec1(p, pick(j, x), pick(j, y), pick(j, bin));
        }
        __syncwarp();
        if (LATEE && EDGE && r < RT - 1) load_edge(r + 1);
    };
#pragma unroll 1
    for (int q = opaque(((NB + blockIdx.x) * NPR + pos0 + lane) >> 1), r = 1; r < p.full; r++, q += NB * NPR / 2) step(r - 1, q, BoolC<false>());
#pragma unroll 1
    for (int r = max(p.full - 1, 0); r < RT; r++) step(r, 0, BoolC<true>());
    TK_OUT
}

__device__ __forceinline__ void stage2(const Params& p, uint32_t sb, int w, int lane, int role, uint32_t base1, uint32_t base) {
    typedef H<2> h;
    const int RT = p.rounds + 1;
    Reader<1> rd;
    rd.init(p, sb, w, lane, role, base1 + 3);
    uint2 rec[J];
#pragma unroll
    for (int j = 0; j < J; j++) rec[j] = null_rec<1>(lane, base1);
    uint32_t kb = sb + 0x10000u, am = 0x10000u | h::PM;
    const float unit = __uint_as_float(__reduce_or_sync(0xffffffffu, lds32(sb + W_UNIT)));
    TK_DECL
#pragma unroll 1
    for (int r = 0; r < RT; r++) {
        rd.check(rec, base1 + r, POLL_NS, lane TK_PASS);
        if (RARE(r == 1)) bar_sync(BAR_TABLE, 2 * NC * 32);
        const uint32_t want = H<1>::tag(base1 + r);
        TKS(0)
        uint2 mv[J];
#pragma unroll
        for (int j = 0; j < J; j++) {
            mv[j] = make_uint2(0u, 0u);
            const uint32_t a = sb + imul(rec[j].y & 0xffffu, 8.f);
            if (!xor_and<0x8e0000u>(rec[j].x, want)) mv[j] = lds64<OFF_M>(a);
        }
        uint32_t fl = 0;
#pragma unroll
        for (int j = 0; j < J; j++) fl |= mv[j].y;
        if (RARE(fl & 0x40000000u)) {
#pragma unroll 1
            for (int j = 0; j < J; j++) {
                const uint2 v = pick(j, mv), w = pick(j, rec);
                if ((v.y & 0x40000000u) && !((w.x ^ want) & 0x8e0000u)) {
                    if (v.x & 0x40000000u) slow_rec1(p, w.x, w.y, lds32(sb + W_ROLE) % NG);
                    else {
                        const float c = bf_hi(w.y), s = __uint_as_float(lds32(sb + W_UNIT)) * 1024.f;
                        side_add(w.x & 0xffu, __byte_perm(w.x, 0u, 0x4413) >> 3, c * (bf_lo(v.x) * s), c * (bf_hi(v.x) * s),
                                 c * (bf_lo(v.y) * s), c * (bf_hi(v.y & 0xbfffffffu) * s));
                    }
                }
            }
#pragma unroll
            for (int j = 0; j < J; j++) if (mv[j].y & 0x40000000u) rec[j].x = 0x800000u;
        }
        uint32_t w0[J], w1[J], bin[J], ret[J];
#pragma unroll
        for (int j = 0; j < J; j++) {
            const float c = bf_hi(rec[j].y), MG = 8194.0f;
            const uint32_t x = rec[j].x;
            const float v[4] = {bf_lo(mv[j].x), bf_hi(mv[j].x), bf_lo(mv[j].y), bf_hi(mv[j].y)};
            w0[j] = and_or<0xf000f000u>(x, __byte_perm(__float_as_uint(fmaf(c, v[0], MG)), __float_as_uint(fmaf(c, v[1], MG)), 0x5410));
            w1[j] = and_or<0xf000f000u>(x << 4, __byte_perm(__float_as_uint(fmaf(c, v[2], MG)), __float_as_uint(fmaf(c, v[3], MG)), 0x5410));
            bin[j] = min(xor_and<0x8e00ffu>(x, want), NB + (lane & (NDUM - 1)));
        }
        const uint32_t lim = h::init(base + r) + (r == RT - 1 ? 0x10000u : 0x20000u);
        rd.load(rec);
        TKS(1)
        mbar_wait(sb + B_OPEN + 8, (r - 1) & 1);
        TKS(2)
#pragma unroll
        for (int j = 0; j < J; j++) ret[j] = atoms_add<h::CNT>(sb + imul(bin[j], 4.f), h::INC);
        uint32_t mx = 0;
#pragma unroll
        for (int j = 0; j < J; j++) {
            w1[j] = and_or<h::TAG>(ret[j], w1[j]);
            put_rec<0>(ret[j], lim, and_xor(ret[j], am, bin[j] * 128 + kb), w0[j], w1[j]);
            mx = __viaddmax_u32(ret[j], 0u - DUMMY, mx);
        }
        __syncwarp();
        if (lane == 0) mbar_arrive(sb + B_FULL + 8);
        TKS(3)
        if (RARE(mx >= lim - DUMMY)) {
            uint32_t over = 0;
#pragma unroll
            for (int j = 0; j < J; j++) if (ret[j] - DUMMY >= lim - DUMMY) over |= 1u << j;
#pragma unroll 1
            do {
                const int j = __ffs(over) - 1;
                over &= over - 1;
                const uint32_t b = pick(j, bin), v = pick(j, ret) - lim, e = v >> h::SH, at = ((v - e * h::INC - (b & 7u) * 16u - h::CAP * 8) >> 7) + e;
                if (max(at, e) < BOXN && r < RT - LATE) g_box[(b * NB + role) * BOX + at] = make_uint2(pick(j, w0), pick(j, w1) | h::TAG);
                else slow_rec2(p, pick(j, w0), pick(j, w1), b, unit);
            } while (over);
        }
        __syncwarp();
        am = am >= 0x30000u ? 0x10000u | h::PM : am + 0x10000u;
        kb ^= am & 0x30000u;
        TKS(4)
    }
    rd.finish();
    TK_OUT
}

__device__ __forceinline__ void add_recs(uint32_t sb, int lane, const uint2 (&rec)[J], uint32_t want) {
    const uint32_t t = 0u - (lane & 1u), k = (t & 1u << 26) - (want >> 4);
    uint32_t o0[J], o1[J], g = 0;
#pragma unroll
    for (int j = 0; j < J; j++) {
        o0[j] = 0; o1[j] = 0;
        if (xor_and<0x7fffffffu>(rec[j].y, want) < 0x0ffc0000u) {
            const uint32_t a = aux_of(rec[j].x, rec[j].y, k);
            const uint32_t v0 = (rec[j].x & 0x0fff0fffu) - 0x08000800u, v1 = (rec[j].y & 0x0fff0fffu) - 0x08000800u;
            o0[j] = atoms_add<OFF_ACC>(sb + a, mux(v0, v1, t));
            o1[j] = atoms_add<OFF_ACC>(sb + (a ^ 4u), mux(v1, v0, t));
        }
    }
#pragma unroll
    for (int j = 0; j < J; j++) g |= o0[j] | o1[j];
    if (RARE(__any_sync(0xffffffffu, g & 0x80008000u))) {
#pragma unroll 1
        for (int j = 0; j < J; j++) {
            const uint2 w = pick(j, rec);
            const uint32_t aux = aux_of(w.x, w.y), p0 = pick(j, o0), p1 = pick(j, o1);
            const float2 a = acc_fix(t ? p1 : p0, w.x & 0x0fff0fffu), b = acc_fix(t ? p0 : p1, w.y & 0x0fff0fffu);
            const float unit = __uint_as_float(lds32(sb + W_UNIT));
            if (xor_and<0x7fffffffu>(w.y, want) < 0x0ffc0000u && (a.x != 0.f || a.y != 0.f || b.x != 0.f || b.y != 0.f)) {
                side_add(lds32(sb + W_ROLE), aux >> 3, a.x * unit, a.y * unit, b.x * unit, b.y * unit);
                sts32(sb + W_WRAP, 1u);
            }
            __syncwarp();
        }
    }
}
__device__ __forceinline__ void stage3(const Params& p, uint32_t sb, int w, int lane, int role, uint32_t base) {
    const int RT = p.rounds + 1;
    Reader<2> rd;
    rd.init(p, sb, w, lane, role, base);
    uint2 rec[J];
    TK_DECL
#pragma unroll 1
    for (int r = 0; r < RT; r++) {
        rd.load(rec);
        rd.check(rec, base + r, r < RT - 2 ? POLL_NS3 : 100, lane TK_PASS);
        RTS((r & 127) == 41 && w == 0, 1 + (r >> 7))
        TK(0)
        add_recs(sb, lane, rec, H<2>::tag(base + r));
        TK(1)
        if (RARE((uint32_t)(r - (RT - LATE + 1)) < 2u)) {
            static_assert(BOX == 32, "box");
            float4* box = reinterpret_cast<float4*>(g_box) + (lds32(sb + W_ROLE) * NB + (w * 2 + r - (RT - LATE + 1)) * J) * (BOX / 2) + lane;
            TKY(0)
#pragma unroll
            for (int j = 0; j < J / 2; j++) {
                const float4 v = ld_rlx128f(box + j * 32);
                rec[2 * j] = make_uint2(__float_as_uint(v.x), __float_as_uint(v.y)); rec[2 * j + 1] = make_uint2(__float_as_uint(v.z), __float_as_uint(v.w));
            }
#pragma unroll
            for (int j = 0; j < J / 2; j++) if (rec[2 * j].x) box[j * 32] = make_float4(0.f, 0.f, 0.f, 0.f);
            add_recs(sb, lane, rec, H<2>::TAG);
            TKY(1)
        }
    }
    rd.finish();
    TK_OUT
}

__device__ __forceinline__ uint32_t row_max(uint32_t x, uint32_t y) {
    const uint32_t mx = __vmaxu2(x & 0x7fff7fffu, y & 0x7fff7fffu);
    return max(mx & 0xffffu, mx >> 16);
}
__device__ __forceinline__ uint32_t amax2(uint32_t a, uint32_t b) {
    uint32_t r; asm("max.NaN.xorsign.abs.bf16x2 %0, %1, %2;" : "=r"(r) : "r"(a), "r"(b)); return r;
}
constexpr int NTAB = 9, TABC = 2 * NC * 32 * 16;
__device__ __forceinline__ void load_piece(const Params& p, uint32_t sb, int role, int i) {
    const int r0 = (role >= NG ? role - NG : role) * p.R1, n = max(min(min(p.R1, p.E - r0) * 8 - i * TABC, TABC), 0);
    asm volatile("mbarrier.arrive.expect_tx.shared::cta.b64 _, [%0], %1;" ::"r"(sb + B_TAB + i * 8), "r"(n) : "memory");
    if (n) asm volatile("cp.async.bulk.shared::cluster.global.mbarrier::complete_tx::bytes [%0], [%1], %2, [%3];"
                        ::"r"(sb + OFF_M + i * TABC), "l"(p.m + r0 + i * (TABC / 8)), "r"(n), "r"(sb + B_TAB + i * 8) : "memory");
}
static_assert(NTAB * TABC >= R1MAX * 8 && NTAB * TABC - TABC / 2 <= R1MAX * 8, "table");
constexpr int EWIN = 5;

__global__ void __launch_bounds__(NTHR, 1) fused_kernel(const Params p) {
    const int tid = threadIdx.x, lane = tid & 31;
    const int hw = __reduce_max_sync(0xffffffffu, tid >> 5);
    const uint32_t sb = __reduce_or_sync(0xffffffffu, (uint32_t)__cvta_generic_to_shared(smem));
    TKX(0)
    RTS(tid == 0, 0)
    uint32_t cta;
    asm volatile("mov.u32 %0, %%ctaid.x;" : "=r"(cta));
    if (hw != W_M1 && hw != W_M2) {
        const int job = hw < W_M1 ? hw : hw - 1;
        if (lane == 0 && job < 2 * NPAGE + 2)
            sts32(sb + OFF_PROBE + job * 4, probe(p.ring + (size_t)max(job / 2 - 1, 0) * PAGE + PROBE + (cta & 31) * 128 + (cta >> 5 & 3) * 16384 + (cta >> 7 << 20) +
                                                  ((job & 1) << 12 ^ (job < 2 ? 0x3000 : 0)), p.zero));
        if (job < 4) bar_arrive(BAR_SIDE, 5 * 32); else bar_arrive(BAR_PROBE, 27 * 32);
        TKX(1)
    }
    if (hw < NS1) {
        stage1(p, sb, hw * 128 + lane, lane, hw == NS1 - 1);
    } else if (hw == W_M1) {
        const uint32_t epoch = ld_rlx32(reinterpret_cast<const uint32_t*>(p.ring + M_BASE)) ^ 33u;
        if (lane == 0) {
            if (sb & 255u) __trap();
            mbar_init(sb + B_FULL, NS1); mbar_init(sb + B_OPEN, 1); mbar_init(sb + B_FREE, 1);
            for (int i = 0; i < NTAB; i++) mbar_init(sb + B_TAB + i * 8, 1);
            asm volatile("fence.proxy.async.shared::cta;" ::: "memory");
        }
        const uint32_t base = __reduce_or_sync(0xffffffffu, epoch) & 31u;
        if (lane == 0) { sts32(sb + W_BASE, epoch); sts64(sb + W_NLIST, 0u, 0u); }
        if (lane == 0 && (base & 1u)) { mbar_arrive(sb + B_OPEN); mbar_arrive(sb + B_FREE); }
        bar_arrive(BAR_BASE, (NC + 1) * 32);
        TKY(5)
        bar_sync(BAR_SIDE, 5 * 32);
        TKY(6)
        {
            const uint2 la = lds64<OFF_PROBE>(sb), lb = lds64<OFF_PROBE + 8>(sb);
            const uint32_t side = min(la.y, lb.y) < min(la.x, lb.x);
            uint32_t v = 0;
            if (lane == 0) {
                asm volatile("atom.relaxed.gpu.global.add.u32 %0, [%1], %2;" : "=r"(v) : "l"(p.ring + M_CNT), "r"(side ? 0x10000u : 1u) : "memory");
                asm volatile("red.relaxed.gpu.global.add.u32 [%0], %1;" ::"l"(p.ring + M_CNT + 4096), "r"(side ? 0x10000u : 1u) : "memory");
            }
            bar_sync(BAR_PROBE, 27 * 32);
            const uint2 l = lds64<OFF_PROBE + 8>(sb + min(lane, NPAGE - 1) * 8);
            const uint32_t mine = (__ballot_sync(0xffffffffu, (l.y < l.x) != side) & ~1u) | 0x80000000u;
            if (lane == 0) {
                uint32_t par;
                asm volatile("atom.relaxed.gpu.global.cas.b32 %0, [%1], 0, %2;" : "=r"(par) : "l"(p.ring + M_PAR), "r"(mine) : "memory");
                const uint32_t role = side ? NB - 1 - (v >> 16) : v & 0xffffu;
#pragma unroll 1
                for (int i = 0; i < AHEAD; i++) load_piece(p, sb, role, i);
                sts32(sb + W_ROLE, role); sts32(sb + W_SIDE, role < NLO ? 0u : role >= NHI ? 1u : side);
                sts32(sb + W_END, (epoch | 1023u) + 1u + (base + p.rounds) % 24u + ((epoch >> 5 & 31u) + p.rounds + 1) % 24u * 32u);
                sts32(sb + W_PAR, par ? par : mine);
            }
            TKX(2)
        }
        bar_arrive(BAR_PAR, (2 * NC + 2) * 32);
        manager<1>(p, sb, opaque(lane), __reduce_max_sync(0xffffffffu, lds32(sb + W_ROLE)), base);
        asm volatile("cp.async.bulk.wait_group 0;" ::: "memory");
        bar_arrive(BAR_H1, (NS1 + 1) * 32);
        TKX(4)
        {
            const int role = lds32(sb + W_ROLE);
#pragma unroll 1
            for (int i = lane * 16; i < DROW; i += 4 * 512) {
                float4 f[4];
#pragma unroll
                for (int u = 0; u < 4; u++) f[u] = ld_rlx128f(reinterpret_cast<const float4*>(g_dirty + role * DROW + i + u * 512));
#pragma unroll
                for (int u = 0; u < 4; u++) {
                    if (__float_as_uint(f[u].x) | __float_as_uint(f[u].y)) prefetch_l2(g_ovf + role * RPAD + i + u * 512);
                    if (__float_as_uint(f[u].z) | __float_as_uint(f[u].w)) prefetch_l2(g_ovf + role * RPAD + i + u * 512 + 8);
                }
            }
        }
        bar_sync(BAR_DONE, (NE + 1) * 32);
        TKY(0)
        if (lane < 2) { fence_gpu(); st_rlx32(reinterpret_cast<uint32_t*>(p.ring + M_FLAG + lane * 4096) + blockIdx.x, lds32(sb + W_END)); }
        TKY(1)
        wait_flags(p, sb, lane, lds32(sb + W_END));
        TKX(5)
        bar_arrive(BAR_FLAG, (NC + 1) * 32); bar_arrive(BAR_FLAG1, (NS1 + 1) * 32);
        if (blockIdx.x == 0) {
            if (lane == 0) *reinterpret_cast<uint32_t*>(p.ring + M_BASE) = lds32(sb + W_END) ^ 33u;
            if (lane < 3) *reinterpret_cast<uint32_t*>(p.ring + (lane & 2 ? M_PAR : M_CNT + (lane & 1) * 4096)) = 0;
        }
    } else if (hw == W_M2) {
        uint2 sm[16];
#pragma unroll
        for (int i = 0; i < 8; i++) ld_in4(p.m + 2 * min((i * 8 + (lane >> 2)) * (p.E >> 7) + (lane & 3), (p.E >> 1) - 1), sm[2 * i], sm[2 * i + 1]);
        const float wd = __bfloat162float(lane & 16 ? p.w_up[lane & 15] : p.w_down[lane & 15]);
        if (lane == 0) { mbar_init(sb + B_FULL + 8, NC); mbar_init(sb + B_OPEN + 8, 1); mbar_init(sb + B_ROWS, 1); }
        sts128<OFF_HIST>(sb + lane * 16, make_uint4(0u, 0u, 0u, 0u)); sts128<OFF_HIST + 512>(sb + lane * 16, make_uint4(0u, 0u, 0u, 0u));
        __syncwarp();
#pragma unroll
        for (int i = 0; i < 16; i++) atoms_add<OFF_HIST>(sb + (row_max(sm[i].x, sm[i].y) >> 7) * 4, 1u);
        __syncwarp();
        uint32_t best = 0;
#pragma unroll 1
        for (int e = 11 + lane; e <= 230; e += 32) {
            uint32_t c = 0;
#pragma unroll
            for (int i = 0; i < EWIN; i++) c += lds32(sb + OFF_HIST + (e - i) * 4);
            best = max(best, c << 8 | (255 - e));
        }
        const uint32_t e = 255 - (__reduce_max_sync(0xffffffffu, best) & 255u);
        if (lane == 0) { sts32(sb + W_EXP, e); sts32(sb + W_UNIT, (e - 10) << 23); }
        reinterpret_cast<float*>(smem + OFF_WSM)[lane] = wd;
        TKY(5)
        bar_sync(BAR_PAR, (2 * NC + 2) * 32);
        manager<2>(p, sb, opaque(lane), __reduce_max_sync(0xffffffffu, lds32(sb + W_ROLE)), __reduce_or_sync(0xffffffffu, lds32(sb + W_BASE)) >> 5 & 31u);
        TKX(4)
        asm volatile("cp.async.bulk.wait_group.read 0;" ::: "memory");
        __syncwarp();
        if (lane == 0) {
            const int row0 = lds32(sb + W_ROLE) * p.R2, np = min(p.R2, p.E - row0) >> 1, off = row0 * 8 & 127;
            asm volatile("mbarrier.arrive.expect_tx.shared::cta.b64 _, [%0], %1;" ::"r"(sb + B_ROWS), "r"(max(np, 0) * 16 + (max(np, 0) + NG0 - 1) / NG0 * off) : "memory");
#pragma unroll 1
            for (int k = 0; k < np; k += NG0)
                asm volatile("cp.async.bulk.shared::cluster.global.mbarrier::complete_tx::bytes [%0], [%1], %2, [%3];"
                             ::"r"(sb + H<2>::win(k / NG0)), "l"(p.m + (row0 - off / 8 + 2 * k)), "r"(min(np - k, NG0) * 16 + off), "r"(sb + B_ROWS) : "memory");
        }
        asm volatile("cp.async.bulk.wait_group 0;" ::: "memory");
    } else {
        const int w = __reduce_max_sync(0xffffffffu, hw < W_M1 ? hw - NS1 : hw - W_M1 - 1), ct = w * 32 + lane;
        if (hw < W_M1) {
            bar_sync(BAR_BASE, (NC + 1) * 32);
            const uint32_t b1 = lds32(sb + W_BASE) & 31u, b2 = lds32(sb + W_BASE) >> 5 & 31u;
            if (ct < NG + NDUM) sts32(sb + OFF_CNT1 + ct * 4, ct < NG ? H<1>::init(b1) + (ct & 7) * 16 : DUMMY);
            if (ct <= NB + NDUM) sts32(sb + OFF_CNT2 + ct * 4, ct < NB ? H<2>::init(b2) + (ct & 7) * 16 : DUMMY);
            fill<1>(sb + OFF_H1 + H<1>::win(b1), ct, b1); fill<1>(sb + OFF_H1 + H<1>::win(b1 + 1), ct, b1 + 1);
            bar_arrive(BAR_S1, (NS1 + NC) * 32);
#pragma unroll
            for (int i = 0; i < 3; i++) fill<2>(sb + H<2>::win(i), ct, b2 + i);
        }
        bar_sync(BAR_PAR, (2 * NC + 2) * 32);
        TKY(4)
        const int role = __reduce_max_sync(0xffffffffu, lds32(sb + W_ROLE));
        const uint32_t epoch = __reduce_or_sync(0xffffffffu, lds32(sb + W_BASE));
        if (hw < W_M1) {
            for (int i = ct; i < R2MAX / 2; i += NC * 32) reinterpret_cast<uint4*>(smem + OFF_ACC)[i] = make_uint4(0x40004000u, 0x40004000u, 0x40004000u, 0x40004000u);
            mbar_wait(sb + B_TAB + KDRY * 8, 0);
            stage2(p, sb, w, opaque(lane), role, (epoch & 31u) - 1u, epoch >> 5 & 31u);
        } else {
            const int e = lds32(sb + W_EXP);
            const uint32_t sc = (uint32_t)(254 - e) * 0x800080u, top = (e << 7 | 0x807fu) * 0x10001u;
            auto conv = [&](uint32_t& x, uint32_t& y) {
                const uint32_t mx = row_max(x, y);
                const int d = e - (int)(mx >> 7);
                x = hmul_bf2(x, sc); y = hmul_bf2(y, sc);
                if (d >= EWIN) y |= 0x40000000u;
                if (d < 0 || (d >= EWIN && e > 127)) { x = 0x40000000u; y = x; }
                if (mx == 0) { x = 0; y = 0; }
            };
#pragma unroll 1
            for (int i = 0; i < NTAB; i++) {
                mbar_wait(sb + B_TAB + i * 8, 0);
                if (ct == 0 && i < NTAB - AHEAD) load_piece(p, sb, role, i + AHEAD);
                const uint32_t t = sb + OFF_M + i * TABC + ct * 16, t1 = t + TABC / 2 < sb + OFF_M + R1MAX * 8 ? t + TABC / 2 : t;
                uint4 v[2] = {lds128(t), lds128(t1)};
                uint32_t ok = ~0u;
#pragma unroll
                for (int u = 0; u < 2; u++) {
                    const uint32_t a = amax2(v[u].x, v[u].y), b = amax2(v[u].z, v[u].w), mx = amax2(__byte_perm(a, b, 0x5410), __byte_perm(a, b, 0x7632)) & 0x7fff7fffu;
                    ok &= (top - mx) ^ (top - EWIN * 0x800080u - mx);
                }
                if (RARE(~ok & 0x80008000u)) {
#pragma unroll 1
                    for (int u = 0; u < 4; u++) {
                        conv(v[0].x, v[0].y);
                        const uint2 f = make_uint2(v[0].x, v[0].y);
                        v[0] = make_uint4(v[0].z, v[0].w, v[1].x, v[1].y); v[1] = make_uint4(v[1].z, v[1].w, f.x, f.y);
                    }
                } else {
#pragma unroll
                    for (int u = 0; u < 2; u++) v[u] = make_uint4(hmul_bf2(v[u].x, sc), hmul_bf2(v[u].y, sc), hmul_bf2(v[u].z, sc), hmul_bf2(v[u].w, sc));
                }
                sts128<0>(t, v[0]); sts128<0>(t1, v[1]);
                __syncwarp();
            }
            TKX(3)
            bar_sync(BAR_TABLE, 2 * NC * 32);
            stage3(p, sb, w, opaque(lane), role, epoch >> 5 & 31u);
            TKX(4)
            bar_sync(BAR_ACC, (NE + NC) * 32);
            if (!lds32(sb + W_WRAP)) {
                int i;
                asm volatile("mov.u32 %0, %%tid.x;" : "=r"(i));
                uint4* f = reinterpret_cast<uint4*>(g_dirty + lds32(sb + W_ROLE) * DROW) + (i - (W_M1 + 1) * 32);
                f[0] = make_uint4(0u, 0u, 0u, 0u);
                if (i < (W_M1 + 1 - NC) * 32 + DROW / 16) f[NC * 32] = make_uint4(0u, 0u, 0u, 0u);
            }
        }
    }
    if (hw < W_M1) {
        bar_arrive(BAR_DONE, (NE + 1) * 32);
        TKX(4)
        finish_rows(p, sb, hw < NS1);
    }
}

__global__ void fb_scatter(const uint2* __restrict__ m, const int* __restrict__ idx_in, const int* __restrict__ idx_out,
                           const uint16_t* __restrict__ angle, const __nv_bfloat16* __restrict__ ang_freq, int T, int e0, int e1) {
    const uint32_t fb = *reinterpret_cast<const uint16_t*>(ang_freq);
    for (long long t = blockIdx.x * (long long)blockDim.x + threadIdx.x; t < T; t += (long long)gridDim.x * blockDim.x) {
        int o = idx_out[t];
        if (o < e0 || o >= e1) continue;
        float c = bf16r(cos_bf(hmul_bf2(angle[t], fb) & 0xffffu));
        uint2 v = __ldg(m + idx_in[t]);
        red4(&g_ovf[o - e0], c * bf_lo(v.x), c * bf_hi(v.x), c * bf_lo(v.y), c * bf_hi(v.y));
    }
}
__global__ void fb_final(const Params p, int e0, int e1) {
    int e = e0 + blockIdx.x * blockDim.x + threadIdx.x;
    if (e >= e1) return;
    float4 a4 = g_ovf[e - e0];
    g_ovf[e - e0] = make_float4(0.f, 0.f, 0.f, 0.f);
    float a[4] = {a4.x, a4.y, a4.z, a4.w};
    float d = __bfloat162float(p.dist[e]);
    float g[4] = {0, 0, 0, 0}, h[4] = {0, 0, 0, 0};
    for (int r = 0; r < 8; r++) {
        float df = bf16r(d - __bfloat162float(p.centers[r]));
        float rb = bf16r(expf(bf16r(-10.0f * bf16r(df * df))));
        for (int k = 0; k < 4; k++) {
            g[k] += rb * __bfloat162float(p.w_sbf[r * 4 + k]);
            h[k] += rb * __bfloat162float(p.w_rbf[r * 4 + k]);
        }
    }
    float ag[4];
    for (int k = 0; k < 4; k++) {
        float s = 0.f;
        for (int j = 0; j < 4; j++) s += a[j] * __bfloat162float(p.w_down[j * 4 + k]);
        ag[k] = bf16r(s * g[k]);
    }
    uint2 mv = p.m[e];
    float mm[4] = {bf_lo(mv.x), bf_hi(mv.x), bf_lo(mv.y), bf_hi(mv.y)};
    __nv_bfloat16 o[4];
    for (int k = 0; k < 4; k++) {
        float u = 0.f;
        for (int j = 0; j < 4; j++) u += ag[j] * __bfloat162float(p.w_up[j * 4 + k]);
        o[k] = __float2bfloat16_rn(mm[k] + bf16r(bf16r(u) * bf16r(h[k])));
    }
    p.out[e] = *reinterpret_cast<uint2*>(o);
}

}

static cudaTextureObject_t make_tex(const void* ptr, size_t bytes, int words) {
    cudaResourceDesc rd = {}; cudaTextureDesc td = {};
    rd.resType = cudaResourceTypeLinear; rd.res.linear.devPtr = const_cast<void*>(ptr); rd.res.linear.sizeInBytes = bytes;
    rd.res.linear.desc = cudaCreateChannelDesc(32, words > 1 ? 32 : 0, words > 2 ? 32 : 0, words > 2 ? 32 : 0, cudaChannelFormatKindUnsigned);
    td.readMode = cudaReadModeElementType;
    cudaTextureObject_t t = 0;
    if (cudaCreateTextureObject(&t, &rd, &td, nullptr) != cudaSuccess) { t = 0; (void)cudaGetLastError(); }
    return t;
}

extern "C" void kernel_launch(void* const* d_in, const int* in_sizes, int n_in, void* d_out, int out_size) {
    typedef const __nv_bfloat16* B;
    Params p;
    p.m = (const uint2*)d_in[0]; p.idx_in = (const uint2*)d_in[1]; p.idx_out = (const uint2*)d_in[2]; p.dist = (B)d_in[3];
    p.angle = (const uint32_t*)d_in[4]; p.centers = (B)d_in[5]; p.ang_freq = (B)d_in[6]; p.w_rbf = (B)d_in[7]; p.w_sbf = (B)d_in[8];
    p.w_down = (B)d_in[9]; p.w_up = (B)d_in[10]; p.out = (uint2*)d_out;
    p.E = in_sizes[3]; p.T = in_sizes[1]; p.T2 = p.T >> 1; p.zero = 0;
    p.R1 = p.R2 = p.rounds = p.lastn = p.full = 0; p.i1 = p.i2 = p.k1 = p.k2 = 0.f;
    static int ok = -1;
    static unsigned char* ring = nullptr;
    if (ok < 0) {
        void* ra = nullptr;
        cudaGetSymbolAddress(&ra, g_ring);
        ring = reinterpret_cast<unsigned char*>(((uintptr_t)ra + PAGE - 1) & ~(uintptr_t)(PAGE - 1));
        int dev = 0, sms = 0, occ = 0;
        cudaGetDevice(&dev);
        cudaDeviceGetAttribute(&sms, cudaDevAttrMultiProcessorCount, dev);
        cudaError_t e = cudaFuncSetAttribute(fused_kernel, cudaFuncAttributeMaxDynamicSharedMemorySize, SMEM_BYTES);
        if (e == cudaSuccess) e = cudaOccupancyMaxActiveBlocksPerMultiprocessor(&occ, fused_kernel, NTHR, SMEM_BYTES);
        ok = (e == cudaSuccess && occ >= 1 && sms >= NB) ? 1 : 0;
        (void)cudaGetLastError();
    }
    p.ring = ring;
    static cudaTextureObject_t tx[3];
    static const void* of[3];
    static int of_t = -1;
    if (of[0] != d_in[1] || of[1] != d_in[2] || of[2] != d_in[4] || of_t != p.T) {
        tx[0] = make_tex(p.idx_in, (size_t)(p.T >> 2) * 16, 4); tx[1] = make_tex(p.idx_out, (size_t)(p.T >> 2) * 16, 4); tx[2] = make_tex(p.angle, (size_t)(p.T >> 2) * 8, 2);
        of[0] = d_in[1]; of[1] = d_in[2]; of[2] = d_in[4]; of_t = p.T;
    }
    p.ti = tx[0]; p.to = tx[1]; p.ta = tx[2];
    const bool fused = ok == 1 && p.E <= EMAX && p.E >= 2 * NB && p.E % 2 == 0 && p.T >= 2;
    if (fused) {
        p.R1 = ((p.E + NG - 1) / NG + 1) & ~1;
        if (p.R1 > 1024) p.R1 = (p.R1 + 15) & ~15;
        p.R2 = ((p.E + NB - 1) / NB + 1) & ~1;
        p.i1 = nextafterf(1.f / p.R1, 2.f); p.i2 = nextafterf(1.f / p.R2, 2.f); p.k1 = -(float)p.R1; p.k2 = -8.f * p.R2;
        const int per = NB * NPR;
        int full = p.T2 / per, rest = p.T2 - full * per;
        p.full = p.ti && p.to && p.ta ? full : 0;
        p.lastn = (rest + NB - 1) / NB;
        if (p.lastn > NPR / 2) { full++; p.lastn = 0; }
        if (full < D) { full = D; p.lastn = 0; }
        p.rounds = full + 1;
        fused_kernel<<<NB, NTHR, SMEM_BYTES>>>(p);
    } else {
        for (int e0 = 0; e0 < p.E; e0 += EMAX) {
            int e1 = p.E - e0 < EMAX ? p.E : e0 + EMAX;
            fb_scatter<<<1056, 256>>>(p.m, (const int*)d_in[1], (const int*)d_in[2], (const uint16_t*)d_in[4], p.ang_freq, p.T, e0, e1);
            fb_final<<<(e1 - e0 + 255) / 256, 256>>>(p, e0, e1);
        }
    }
}
```

```cpp
#include <cuda_runtime.h>
#include <cuda_bf16.h>
#include <stdint.h>
#include <math.h>

#define LATEE 0
#define AHEAD 3
#define RSPLIT (D - 1)
#define TEX0 1
#define KDRY 4
#define SMP1 0
#define SMP2 1
#define FUNR 1
#define DRY2 1
#define PFH 1
#define NPF 6
#define GU 16
#define MBF 1
#define RARE(x) __builtin_expect(!!(x), 0)
namespace {

constexpr int NB = 132, NG = 66;
constexpr int R2MAX = 6062, R1MAX = 12128;
constexpr int EMAX = NB * R2MAX;
constexpr int NTHR = 1024;
constexpr int NS1 = 8, NC = 11, J = 6;
constexpr int NPR = 960;
constexpr int D = 3;
constexpr int WIN = 16896;
constexpr int NDUM = 16;
constexpr uint32_t DUMMY = 0xc0000000u;

constexpr int OFF_ACC = WIN, OFF_BAR = OFF_ACC + R2MAX * 8;
constexpr int OFF_H1 = 0x10000 + WIN, OFF_M = OFF_H1 + WIN, OFF_PROBE = OFF_M + R1MAX * 8;
constexpr int OFF_CNT1 = OFF_H1 + 0x20000 + WIN, OFF_CNT2 = OFF_CNT1 + (NG + NDUM + 2) * 4;
constexpr int OFF_HIST = OFF_ACC;
constexpr int OFF_WSM = OFF_CNT2 + (NB + NDUM) * 4 + 16;
constexpr int OFF_WB = OFF_WSM + 128, OFF_WG = OFF_WB + 64;
constexpr int SMEM_BYTES = OFF_WG + 256;
static_assert(SMEM_BYTES <= 232448 && OFF_BAR + 64 <= 0x10000 && OFF_PROBE + 256 <= 0x30000, "smem");
static_assert(OFF_BAR % 8 == 0 && OFF_WSM % 16 == 0 && OFF_CNT2 % 16 == 0, "align");
static_assert(NC * J == NG && NC * 32 * 6 * 16 == 2 * WIN, "shape");

template <int HOP> struct H {
    static constexpr int S = HOP == 1 ? 32 : 16, NBIN = HOP == 1 ? NG : NB, CAP = 2 * S, SH = HOP == 1 ? 11 : 12;
    static constexpr int TB = HOP == 1 ? 17 : 28, CNT = HOP == 1 ? OFF_CNT1 : OFF_CNT2, STG = HOP == 1 ? OFF_H1 : 0;
    static constexpr uint32_t INC = (1u << SH) + 8u, PM = (S - 1) * 8, TAG = 7u << TB;
    static __device__ __forceinline__ uint32_t tag(uint32_t R) { return R << TB & TAG; }
    static __device__ __forceinline__ uint32_t init(uint32_t R) { return tag(R) | ((1u << TB) - 0x10000u); }
    static __device__ __forceinline__ uint32_t mark(uint32_t R, uint32_t line) { return ((HOP == 1 ? R >> 1 : R) + line) & 3u; }
    static __device__ __forceinline__ uint32_t win(int r) { return HOP == 1 ? (r & 1) << 17 : (0x310u >> (r % 3 * 4) & 3u) << 16; }
};

constexpr uint32_t PAGE = 1u << 21;
constexpr int NPAGE = NC + 2;
__device__ __align__(256) unsigned char g_ring[(size_t)(NPAGE + 1) * PAGE];
constexpr int MISC = 0xa0000;
constexpr int M_CNT = MISC + 1024, M_PAR = M_CNT + 4;
constexpr int M_BASE = M_CNT + 8;
constexpr int M_FLAG = MISC + 2048;
constexpr int PROBE = MISC + 0x40000;
__device__ __forceinline__ uint32_t cred_off(uint32_t role) { return role * 4 + min(role >> 5, 3u) * (16384 - 128); }
struct Ring {
    uint64_t main, mid;
    uint32_t par;
    __device__ __forceinline__ Ring(const unsigned char* ring, uint32_t pars, int k) {
        main = reinterpret_cast<uint64_t>(ring) + ((uint64_t)k << 20);
        par = pars >> (k >> 1) & 1u;
        mid = reinterpret_cast<uint64_t>(ring) + (uint64_t)NC * PAGE + (((k >> 3 << 20) + (k >> 2 & 1) * 0x11000u + (k & 1) * 2048) ^ (k >> 1 & 1) * 0x3000u ^ (pars >> (NC + (k >> 4)) & 1u) << 12);
    }
};
constexpr int NLO = 60, NHI = 72;
__host__ __device__ constexpr uint32_t src_off(int j) { return (j % 3) << 14 | (j / 3) << 18; }
__device__ __forceinline__ uint32_t slot_off(uint32_t s) { return (0xa930u >> s * 4 & 15u) << 16; }
__device__ __forceinline__ uint32_t slot_steps(uint32_t R) { return (uint32_t)(0x30a09030aull >> (2 - R % 3) * 8) & 0xffffffu; }
__device__ __forceinline__ void slot_next(uint32_t& a, uint32_t st) { a ^= st & 0xf0000u; }
__device__ __forceinline__ uint32_t slot_rot(uint32_t st) { return __byte_perm(st, 0u, 0x4102); }
constexpr int RPAD = 6064, DROW = 6144;
__device__ __align__(128) uint8_t g_dirty[NB * DROW];
constexpr int BOX = 32, BOXN = 24, LATE = 8;
__device__ __align__(128) uint2 g_box[NB * NB * BOX];
__device__ __align__(128) float4 g_ovf[NB * RPAD];

struct Params {
    const uint2* m; const uint2* idx_in; const uint2* idx_out; const __nv_bfloat16* dist; const uint32_t* angle;
    const __nv_bfloat16* centers; const __nv_bfloat16* ang_freq; const __nv_bfloat16* w_rbf; const __nv_bfloat16* w_sbf;
    const __nv_bfloat16* w_down; const __nv_bfloat16* w_up; uint2* out; unsigned char* ring;
    cudaTextureObject_t ti, to, ta;
    int E, T, T2, R1, R2, rounds, lastn, full; uint32_t zero; float i1, i2, k1, k2;
};

__device__ __forceinline__ float bf16r(float x) { return __bfloat162float(__float2bfloat16_rn(x)); }
__device__ __forceinline__ float bf_lo(uint32_t v) { return __uint_as_float(v << 16); }
__device__ __forceinline__ float bf_hi(uint32_t v) { return __uint_as_float(v & 0xffff0000u); }
__device__ __forceinline__ void red4(float4* a, float x, float y, float z, float w) {
    asm volatile("red.global.add.v4.f32 [%0], {%1,%2,%3,%4};" ::"l"(a), "f"(x), "f"(y), "f"(z), "f"(w) : "memory");
}
__device__ __forceinline__ void bar_sync(int id, int n) { __syncwarp(); asm volatile("bar.sync %0, %1;" ::"r"(id), "r"(n) : "memory"); }
__device__ __forceinline__ void bar_arrive(int id, int n) { __syncwarp(); asm volatile("bar.arrive %0, %1;" ::"r"(id), "r"(n) : "memory"); }
template <int OFF> __device__ __forceinline__ uint32_t atoms_add(uint32_t addr, uint32_t v) {
    uint32_t r; asm volatile("atom.shared.add.u32 %0, [%1+%3], %2;" : "=r"(r) : "r"(addr), "r"(v), "n"(OFF) : "memory"); return r;
}
__device__ __forceinline__ void sts64(uint32_t addr, uint32_t x, uint32_t y) {
    asm volatile("st.shared.v2.u32 [%0], {%1,%2};" ::"r"(addr), "r"(x), "r"(y) : "memory");
}
__device__ __forceinline__ void sts32(uint32_t addr, uint32_t x) { asm volatile("st.shared.u32 [%0], %1;" ::"r"(addr), "r"(x) : "memory"); }
template <int OFF = 0> __device__ __forceinline__ uint2 lds64(uint32_t addr) {
    uint2 v; asm volatile("ld.shared.v2.u32 {%0,%1}, [%2+%3];" : "=r"(v.x), "=r"(v.y) : "r"(addr), "n"(OFF) : "memory"); return v;
}
__device__ __forceinline__ uint32_t lds32(uint32_t addr) {
    uint32_t v; asm volatile("ld.shared.u32 %0, [%1];" : "=r"(v) : "r"(addr) : "memory"); return v;
}
template <int OFF> __device__ __forceinline__ void sts128(uint32_t a, const uint4& v) {
    asm volatile("st.shared.v4.u32 [%0+%5], {%1,%2,%3,%4};" ::"r"(a), "r"(v.x), "r"(v.y), "r"(v.z), "r"(v.w), "n"(OFF) : "memory");
}
__device__ __forceinline__ uint4 lds128(uint32_t a) {
    uint4 v; asm volatile("ld.shared.v4.u32 {%0,%1,%2,%3}, [%4];" : "=r"(v.x), "=r"(v.y), "=r"(v.z), "=r"(v.w) : "r"(a) : "memory"); return v;
}
__device__ __forceinline__ uint32_t ld_rlx32(const uint32_t* p) {
    uint32_t v; asm volatile("ld.relaxed.gpu.global.u32 %0, [%1];" : "=r"(v) : "l"(p) : "memory"); return v;
}
__device__ __forceinline__ uint2 ld_rlx64(const void* p) {
    uint2 v; asm volatile("ld.relaxed.gpu.global.v2.u32 {%0,%1}, [%2];" : "=r"(v.x), "=r"(v.y) : "l"(p) : "memory"); return v;
}
__device__ __forceinline__ float4 ld_rlx128f(const float4* p) {
    float4 v; asm volatile("ld.relaxed.gpu.global.v4.f32 {%0,%1,%2,%3}, [%4];" : "=f"(v.x), "=f"(v.y), "=f"(v.z), "=f"(v.w) : "l"(p) : "memory"); return v;
}
__device__ __forceinline__ float4 take(float4* p, bool q) {
    float4 v;
    asm volatile("{ .reg .b128 a; .reg .b64 x, y; .reg .pred q; mov.b64 x, 0; mov.b128 a, {x, x}; setp.ne.u32 q, %5, 0;\n"
                 "@q atom.relaxed.gpu.global.exch.b128 a, [%4], a; mov.b128 {x, y}, a; mov.b64 {%0,%1}, x; mov.b64 {%2,%3}, y; }"
                 : "=f"(v.x), "=f"(v.y), "=f"(v.z), "=f"(v.w) : "l"(p), "r"((uint32_t)q) : "memory");
    return v;
}
__device__ __forceinline__ void fence_gpu() { asm volatile("fence.acq_rel.gpu;" ::: "memory"); }
__device__ __forceinline__ void st_rlx32(uint32_t* p, uint32_t v) { asm volatile("st.relaxed.gpu.global.u32 [%0], %1;" ::"l"(p), "r"(v) : "memory"); }
__device__ __forceinline__ uint32_t hmul_bf2(uint32_t a, uint32_t b) {
    uint32_t r; asm("mul.rn.bf16x2 %0, %1, %2;" : "=r"(r) : "r"(a), "r"(b)); return r;
}
__device__ __forceinline__ uint32_t hsub_bf2(uint32_t a, uint32_t b) {
    uint32_t r; asm("sub.rn.bf16x2 %0, %1, %2;" : "=r"(r) : "r"(a), "r"(b)); return r;
}
__device__ __forceinline__ uint32_t hadd_bf2(uint32_t a, uint32_t b) {
    uint32_t r; asm("add.rn.bf16x2 %0, %1, %2;" : "=r"(r) : "r"(a), "r"(b)); return r;
}
__device__ __forceinline__ int opaque(int v) { return __shfl_sync(0xffffffffu, v, threadIdx.x); }
constexpr int SPIN_LIMIT = 1 << 22;

__constant__ uint32_t c_inv2pi[8] = {0u, 0x28be60dbu, 0x9391054au, 0x7f09d5f4u, 0x7d4d3770u, 0x36d8a566u, 0x4f10e410u, 0x7f9458eau};
constexpr uint32_t BIGX = 0x4280u;
__device__ __forceinline__ float cos_big(uint32_t xb) {
    uint32_t e = (xb >> 7) & 0xffu, M = (xb & 0x7fu) | 0x80u;
    uint32_t pp = e - 102u;
    uint32_t wi = pp >> 5;
    uint32_t t0 = c_inv2pi[wi], t1 = c_inv2pi[wi + 1], t2 = c_inv2pi[wi + 2];
    uint32_t f = M * __funnelshift_l(t1, t0, pp) + __umulhi(M, __funnelshift_l(t2, t1, pp));
    float c = __cosf((float)(int)f * 1.4629180792671596e-9f);
    return e == 255u ? __uint_as_float(0x7fc00000u) : c;
}
__device__ __forceinline__ float cos_bf(uint32_t xb) {
    return (xb & 0x7fffu) > BIGX ? cos_big(xb) : __cosf(__uint_as_float(xb << 16));
}
__device__ __forceinline__ uint32_t pack_bf2(float lo, float hi) {
    uint32_t r; asm("cvt.rn.bf16x2.f32 %0, %1, %2;" : "=r"(r) : "f"(hi), "f"(lo)); return r;
}
template <int N> __device__ __forceinline__ uint32_t pick(int k, const uint32_t (&a)[N]) {
    uint32_t v = a[0];
#pragma unroll
    for (int i = 1; i < N; i++) if (k == i) v = a[i];
    return v;
}
template <int N> __device__ __forceinline__ uint2 pick(int k, const uint2 (&a)[N]) {
    uint2 v = a[0];
#pragma unroll
    for (int i = 1; i < N; i++) if (k == i) v = a[i];
    return v;
}
__device__ __forceinline__ uint32_t imul(uint32_t a, float s) { uint32_t r; asm("mul.rz.f32 %0, %1, %2;" : "=r"(r) : "r"(a), "f"(s)); return r; }
__device__ __forceinline__ uint32_t ifma(uint32_t a, float s, uint32_t c) { uint32_t r; asm("fma.rn.f32 %0, %1, %2, %3;" : "=r"(r) : "r"(a), "f"(s), "r"(c)); return r; }
extern __shared__ __align__(1024) unsigned char smem[];
__device__ __forceinline__ void side_add(uint32_t bin, uint32_t row, float a, float b, float c, float d) {
    red4(&g_ovf[bin * RPAD + row], a, b, c, d);
    g_dirty[bin * DROW + row] = 1;
}
__device__ __forceinline__ void slow_triplet(const Params& p, uint32_t ii, uint32_t oo, float c) {
    const uint2 v = __ldg(p.m + ii);
    const uint32_t bo = imul(oo, p.i2);
    side_add(bo, oo - bo * p.R2, c * bf_lo(v.x), c * bf_hi(v.x), c * bf_lo(v.y), c * bf_hi(v.y));
}
__device__ __forceinline__ void slow_rec1(const Params& p, uint32_t x, uint32_t y, uint32_t bin) {
    const uint2 v = __ldg(p.m + bin * p.R1 + (y & 0xffffu));
    const float c = bf_hi(y);
    side_add(x & 0xffu, __byte_perm(x, 0u, 0x4413) >> 3, c * bf_lo(v.x), c * bf_hi(v.x), c * bf_lo(v.y), c * bf_hi(v.y));
}
__device__ __forceinline__ uint32_t aux_of(uint32_t w0, uint32_t w1, uint32_t k = 0) {
    uint32_t u; asm("lop3.b32 %0, %1, %2, 0xf000f000, 0xe4;" : "=r"(u) : "r"(w0), "r"((w1 >> 4) + k));
    return __byte_perm(u, 0u, 0x4413);
}
__device__ __forceinline__ void slow_rec2(const Params& p, uint32_t w0, uint32_t w1, uint32_t bin, float unit) {
    side_add(bin, aux_of(w0, w1) >> 3, (float)((int)(w0 & 0xfffu) - 2048) * unit, (float)((int)(w0 >> 16 & 0xfffu) - 2048) * unit,
             (float)((int)(w1 & 0xfffu) - 2048) * unit, (float)((int)(w1 >> 16 & 0xfffu) - 2048) * unit);
}
template <uint32_t M> __device__ __forceinline__ uint32_t and_or(uint32_t a, uint32_t c) {
    uint32_t r; asm("lop3.b32 %0, %1, %2, %3, 0xea;" : "=r"(r) : "r"(a), "n"(M), "r"(c)); return r;
}
template <uint32_t M> __device__ __forceinline__ uint32_t xor_and(uint32_t a, uint32_t c) {
    uint32_t r; asm("lop3.b32 %0, %1, %2, %3, 0x48;" : "=r"(r) : "r"(a), "n"(M), "r"(c)); return r;
}
__device__ __forceinline__ uint32_t mux(uint32_t a, uint32_t b, uint32_t m) {
    uint32_t r; asm("lop3.b32 %0, %1, %2, %3, 0xd8;" : "=r"(r) : "r"(a), "r"(b), "r"(m)); return r;
}
__device__ __forceinline__ uint32_t and_xor(uint32_t a, uint32_t m, uint32_t c) {
    uint32_t r; asm("lop3.b32 %0, %1, %2, %3, 0x6a;" : "=r"(r) : "r"(a), "r"(m), "r"(c)); return r;
}
__device__ __forceinline__ uint2 ld_in(const uint2* a) {
    uint2 v; asm volatile("ld.global.nc.L1::no_allocate.v2.u32 {%0,%1}, [%2];" : "=r"(v.x), "=r"(v.y) : "l"(a)); return v;
}
__device__ __forceinline__ uint32_t ld_in(const uint32_t* a) {
    uint32_t v; asm volatile("ld.global.nc.L1::no_allocate.u32 %0, [%1];" : "=r"(v) : "l"(a)); return v;
}
__device__ __forceinline__ void ld_in4(const uint2* p, uint2& a, uint2& b) {
    asm volatile("ld.global.nc.L1::no_allocate.v4.u32 {%0,%1,%2,%3}, [%4];" : "=r"(a.x), "=r"(a.y), "=r"(b.x), "=r"(b.y) : "l"(p));
}
__device__ __forceinline__ void tex4(cudaTextureObject_t t, int i, uint2& a, uint2& b) {
    asm volatile("tex.1d.v4.u32.s32 {%0,%1,%2,%3}, [%4, {%5}];" : "=r"(a.x), "=r"(a.y), "=r"(b.x), "=r"(b.y) : "l"(t), "r"(i));
}
__device__ __forceinline__ void tex2(cudaTextureObject_t t, int i, uint32_t& a, uint32_t& b) {
    asm volatile("{ .reg .b32 z, w; tex.1d.v4.u32.s32 {%0,%1,z,w}, [%2, {%3}]; }" : "=r"(a), "=r"(b) : "l"(t), "r"(i) : "memory");
}
template <int OFF> __device__ __forceinline__ void put_rec(uint32_t ret, uint32_t lim, uint32_t addr, uint32_t x, uint32_t y) {
    asm volatile("{ .reg .pred q; setp.lt.u32 q, %0, %1; @q st.shared.v2.u32 [%2+%5], {%3,%4}; }" ::"r"(ret), "r"(lim), "r"(addr), "r"(x), "r"(y), "n"(OFF) : "memory");
}
__device__ __forceinline__ uint32_t mbar_try(uint32_t mb, uint32_t parity) {
    uint32_t ok;
    asm volatile("{ .reg .pred q; mbarrier.try_wait.parity.shared::cta.b64 q, [%1], %2; selp.u32 %0, 1, 0, q; }" : "=r"(ok) : "r"(mb), "r"(parity) : "memory");
    return ok;
}
__device__ __forceinline__ void mbar_wait(uint32_t mb, uint32_t parity) {
    if (!mbar_try(mb, parity)) {
        int it = 0;
        while (!mbar_try(mb, parity)) if (++it > SPIN_LIMIT) __trap();
    }
}
__device__ __forceinline__ void mbar_init(uint32_t mb, uint32_t n) { asm volatile("mbarrier.init.shared::cta.b64 [%0], %1;" ::"r"(mb), "r"(n) : "memory"); }
__device__ __forceinline__ void mbar_arrive(uint32_t mb) { asm volatile("mbarrier.arrive.shared::cta.b64 _, [%0];" ::"r"(mb) : "memory"); }
constexpr int B_FULL = OFF_BAR, B_OPEN = OFF_BAR + 16, B_FREE = OFF_BAR + 32;
constexpr int W_END = OFF_BAR + 40, W_SIDE = OFF_BAR + 44, W_PAR = OFF_BAR + 48, W_ROLE = OFF_BAR + 52, W_EXP = OFF_BAR + 56, W_UNIT = OFF_BAR + 60, W_NLIST = OFF_PROBE + 112, W_WRAP = OFF_PROBE + 116, W_BASE = OFF_PROBE + 120, B_TAB = OFF_PROBE + 128, B_ROWS = OFF_PROBE + 248, B_TFREE = OFF_PROBE + 240, B_FLAG = OFF_PROBE + 232, B_INIT = OFF_PROBE + 224, W_ITEM = OFF_PROBE + 124;
enum { BAR_S1 = 1, BAR_SIDE, BAR_PROBE, BAR_PAR, BAR_TABLE, BAR_DONE, BAR_ACC, BAR_FLAG, BAR_FLAG1, BAR_H1, BAR_BASE, BAR_ROWS };
constexpr int W_M1 = NS1 + NC, W_M2 = 31;

#define RTS(c, i)
#define TK_DECL
#define TK(i)
#define TK_CNT(i)
#define TK_OUT
#define TK_ARG
#define TK_PASS
#define TKS(i) TK(i)
#define TKX(i)
#define TKY(i) {}
#define TKZ(i, d)

__device__ __forceinline__ void prefetch_l2(const void* a) { asm volatile("prefetch.global.L2 [%0];" ::"l"(a)); }
__device__ __forceinline__ void wait_flags(const Params& p, uint32_t sb, int lane, uint32_t need) {
    const unsigned char* f = p.ring + M_FLAG + (lds32(sb + W_SIDE) << 12);
    int it = 0;
    while (true) {
        uint32_t a[5];
        asm volatile("ld.acquire.gpu.global.v4.u32 {%0,%1,%2,%3}, [%4];" : "=r"(a[0]), "=r"(a[1]), "=r"(a[2]), "=r"(a[3]) : "l"(f + lane * 16) : "memory");
        asm volatile("ld.acquire.gpu.global.u32 %0, [%1];" : "=r"(a[4]) : "l"(f + 512 + (lane & 3) * 4) : "memory");
        const uint32_t d = (a[0] ^ need) | (a[1] ^ need) | (a[2] ^ need) | (a[3] ^ need) | (a[4] ^ need);
        if (__all_sync(0xffffffffu, d == 0)) break;
        __nanosleep(50);
        if (++it > SPIN_LIMIT) __trap();
    }
}
__device__ __forceinline__ float exp_fast(float x) { float r; asm("ex2.approx.ftz.f32 %0, %1;" : "=f"(r) : "f"(x * 1.4426950408889634f)); return r; }
constexpr uint32_t BIAS = 0x3d803d80u, ZERO = 0x7d80u;
__device__ __forceinline__ float2 acc_fix(uint32_t old, uint32_t q) {
    const uint32_t u = old + BIAS, n = u + q - 0x08000800u;
    return make_float2((float)((int)(u & 0xffffu) + (int)(q & 0xffffu) - 2048 - (int)(n & 0xffffu)), (float)((int)(u >> 16) + (int)(q >> 16) - 2048 - (int)(n >> 16)));
}
constexpr int NE = NS1 + NC, NPAIR = (R2MAX / 2 + NE * 32 - 1) / (NE * 32), NTILE = 16, NG0 = NS1 * 8 * NTILE;
constexpr int OFF_G = OFF_M, GH = R2MAX * 8, OFF_LIST = OFF_G;
static_assert(2 * R2MAX <= R1MAX && NG0 * 16 + 112 <= WIN && 3 * NG0 >= NPAIR * NE * 32 && NPAIR * NE * 64 <= DROW, "gates");
__device__ __forceinline__ int gate_g(int k) { return (k < NG0 ? OFF_H1 : OFF_G) + k * 16; }
__device__ __forceinline__ int gate_h(int k) { return (k < NG0 ? OFF_H1 + 0x20000 : OFF_G + GH) + k * 16; }
__device__ __forceinline__ uint2 out_row(int row, const float4& o, const float4& add, const uint2& mv) {
    const float* w = reinterpret_cast<const float*>(smem + OFF_WSM);
    const float unit = *reinterpret_cast<const float*>(smem + W_UNIT), K = 8388608.f + ZERO;
    const uint2 ac = reinterpret_cast<const uint2*>(smem + OFF_ACC)[row];
    const uint32_t* g = reinterpret_cast<const uint32_t*>(smem + gate_g(row >> 1)) + (row & 1), *h = reinterpret_cast<const uint32_t*>(smem + gate_h(row >> 1)) + (row & 1);
    const uint32_t c0 = ac.x + BIAS, c1 = ac.y + BIAS;
    const float a[4] = {fmaf(__uint_as_float(__byte_perm(c0, 0x4b00u, 0x5410)) - K, unit, o.x), fmaf(__uint_as_float(__byte_perm(c0, 0x4b00u, 0x5432)) - K, unit, o.y),
                        fmaf(__uint_as_float(__byte_perm(c1, 0x4b00u, 0x5410)) - K, unit, o.z), fmaf(__uint_as_float(__byte_perm(c1, 0x4b00u, 0x5432)) - K, unit, o.w)};
    float sd[4], uu[4];
#pragma unroll
    for (int k = 0; k < 4; k++) sd[k] = fmaf(a[3], w[12 + k], fmaf(a[2], w[8 + k], fmaf(a[1], w[4 + k], a[0] * w[k])));
    const uint32_t a01 = hmul_bf2(pack_bf2(sd[0] + add.x, sd[1] + add.y), g[0]), a23 = hmul_bf2(pack_bf2(sd[2] + add.z, sd[3] + add.w), g[2]);
#pragma unroll
    for (int k = 0; k < 4; k++) uu[k] = fmaf(bf_hi(a23), w[28 + k], fmaf(bf_lo(a23), w[24 + k], fmaf(bf_hi(a01), w[20 + k], bf_lo(a01) * w[16 + k])));
    return make_uint2(hadd_bf2(mv.x, hmul_bf2(pack_bf2(uu[0], uu[1]), h[0])), hadd_bf2(mv.y, hmul_bf2(pack_bf2(uu[2], uu[3]), h[2])));
}
__device__ __forceinline__ void mma16(float (&c)[4], const uint32_t (&a)[4], uint32_t b0, uint32_t b1) {
    asm volatile("mma.sync.aligned.m16n8k16.row.col.f32.bf16.bf16.f32 {%0,%1,%2,%3}, {%4,%5,%6,%7}, {%8,%9}, {%0,%1,%2,%3};"
                 : "+f"(c[0]), "+f"(c[1]), "+f"(c[2]), "+f"(c[3]) : "r"(a[0]), "r"(a[1]), "r"(a[2]), "r"(a[3]), "r"(b0), "r"(b1));
}
__device__ __forceinline__ void finish_rows(const Params& p, uint32_t sb, bool s1) {
    int tid;
    bool wet = !DRY2;
    {
        asm volatile("mov.u32 %0, %%tid.x;" : "=r"(tid));
        const int lane = tid & 31;
        if (s1) mbar_wait(sb + B_INIT, 0); else if (lane == 0) mbar_arrive(sb + B_TFREE);
#pragma unroll 1
        for (bool own = s1;; own = false, wet = true) {
            asm volatile("mov.u32 %0, %%tid.x;" : "=r"(tid));
            uint32_t item = tid >> 5;
            if (!own) item = tid & 31 ? 0u : atoms_add<W_ITEM>(sb, 1u);
            item = __reduce_max_sync(0xffffffffu, item);
            if (item >= 3 * NS1) break;
            const int kb = item / NS1 * NG0 + item % NS1 * 8, q = (lds32(sb + W_ROLE) * p.R2 >> 1) + kb + (tid >> 2 & 7) + (tid & 3) * NS1 * 8;
            uint32_t ds[NTILE / 4];
            TKY(7)
#pragma unroll
            for (int j = 0; j < NTILE / 4; j++) ds[j] = ld_in(reinterpret_cast<const uint32_t*>(p.dist) + min(q + j * NS1 * 32, (p.E >> 1) - 1));
            const uint2 wc = lds64<OFF_WG>(sb + (tid & 31) * 8);
            const uint32_t wb = wc.x, cen = wc.y;
            TKZ(4, (ds[0] ^ ds[1] ^ ds[2] ^ ds[3] ^ wb ^ cen))
            uint2 v[NTILE];
#pragma unroll 1
            for (int t = 0; t < NTILE; t += GU) {
#pragma unroll
            for (int i = 0; i < NTILE - GU; i++) v[i] = v[i + GU];
#pragma unroll
            for (int i = 0; i < GU; i++) {
                const uint32_t x = __shfl_sync(0xffffffffu, ds[i >> 2], i & 3, 4);
                uint32_t rb[2];
#pragma unroll
                for (int u = 0; u < 2; u++) {
                    const uint32_t df = hsub_bf2(__byte_perm(x, 0u, u ? 0x3232 : 0x1010), cen);
                    const uint32_t ar = hmul_bf2(hmul_bf2(df, df), 0xc120c120u);
                    rb[u] = pack_bf2(exp_fast(bf_lo(ar)), exp_fast(bf_hi(ar)));
                }
                float c[4];
                asm volatile("mma.sync.aligned.m16n8k8.row.col.f32.bf16.bf16.f32 {%0,%1,%2,%3}, {%4,%5}, {%6}, {%7,%7,%7,%7};"
                             : "=f"(c[0]), "=f"(c[1]), "=f"(c[2]), "=f"(c[3]) : "r"(rb[0]), "r"(rb[1]), "r"(wb), "f"(0.f));
                v[NTILE - GU + i] = make_uint2(pack_bf2(c[0], c[1]), pack_bf2(c[2], c[3]));
            }
#pragma unroll
            for (int j = 0; j < (NTILE - GU) / 4; j++) ds[j] = ds[j + GU / 4];
            }
            TKZ(5, (v[15].x ^ v[9].y))
            if (own) bar_sync(BAR_H1, (NS1 + 1) * 32); else mbar_wait(sb + B_TFREE, 0);
            asm volatile("mov.u32 %0, %%tid.x;" : "=r"(tid));
            const int k0 = kb + (tid >> 2 & 7);
            const uint32_t a = sb + (tid & 2 ? gate_h(k0) : gate_g(k0)) + (tid & 1) * 8;
#pragma unroll
            for (int i = 0; i < NTILE; i++) if (i < NTILE - 1 || k0 + i * NS1 * 8 < R2MAX / 2) sts64(a + i * NS1 * 8 * 16, v[i].x, v[i].y);
            static_assert(2 * NG0 + (NTILE - 1) * NS1 * 8 <= R2MAX / 2, "gates");
            TKY(1)
        }
    }
    asm volatile("mov.u32 %0, %%tid.x;" : "=r"(tid));
    const int role = lds32(sb + W_ROLE), row0 = role * p.R2, np = min(p.R2, p.E - row0) >> 1, lane = tid & 31;
    uint4 wd = make_uint4(0u, 0u, 0u, 0u), wu = wd;
    if ((lane & 3) == lane >> 3) { wd = lds128(sb + OFF_WB + (lane & 4) * 8); wu = lds128(sb + OFF_WB + 16 + (lane & 4) * 8); }
    const uint32_t wb[8] = {wd.x, wd.y, wd.z, wd.w, wu.x, wu.y, wu.z, wu.w};
    const uint32_t k0 = (lds32(sb + W_UNIT) >> 16) * 0x10001u + 0x03800380u;
    uint8_t* dirty = g_dirty + role * DROW + tid * 2;
    auto flags = [&](uint32_t on) {
        uint32_t f[NPAIR], m = 0;
#pragma unroll
        for (int i = 0; i < NPAIR; i++) asm volatile("{ .reg .pred q; setp.ne.u32 q, %2, 0; mov.u32 %0, 0; @q ld.relaxed.gpu.global.u16 %0, [%1]; }" : "=r"(f[i]) : "l"(dirty + i * NE * 64), "r"(on) : "memory");
#pragma unroll
        for (int i = 0; i < NPAIR; i++) m |= ((f[i] | f[i] >> 7) & 3u) << 2 * i;
        return m;
    };
    auto row_of = [&](int j) { return 2 * tid + (j >> 1) * NE * 64 + (j & 1); };
    uint32_t kept, left = 0, bad = 0, at;
#pragma unroll 1
    for (;; wet = true) {
    if (wet) mbar_wait(sb + B_FLAG, 0);
    TKY(2)
    kept = flags(wet);
    at = __popc(kept);
    TKZ(3, kept)
#pragma unroll
    for (int i = 1; i < 32; i *= 2) { const uint32_t t = __shfl_up_sync(0xffffffffu, at, i); if (lane >= i) at += t; }
    const uint32_t n = __shfl_sync(0xffffffffu, at, 31);
    if (n || !wet) {
        uint32_t q = 0;
        if (lane == 0) q = atoms_add<W_NLIST>(sb, n);
        q = __shfl_sync(0xffffffffu, q, 0);
        if (q + n > NG0) { sts32(sb + W_WRAP, 1u); kept = 0; }
        else {
            q = sb + OFF_LIST + q * 16;
            at = q + (at - __popc(kept)) * 16;
            uint32_t to = at;
            uint32_t m = kept;
#pragma unroll 1
            do {
                if (m) sts32(to, row_of(__ffs(m) - 1));
                m &= m - 1; to += 16;
            } while (m);
            __syncwarp();
            to = q + lane * 16;
#pragma unroll 1
            do {
                const bool on = to < q + n * 16;
                float4 o = make_float4(0.f, 0.f, 0.f, 0.f);
                asm volatile("{ .reg .pred q; setp.ne.u32 q, %5, 0; @q ld.relaxed.gpu.global.v4.f32 {%0,%1,%2,%3}, [%4]; }"
                             : "+f"(o.x), "+f"(o.y), "+f"(o.z), "+f"(o.w) : "l"(&g_ovf[role * RPAD + lds32(to)]), "r"((uint32_t)on) : "memory");
                const float4* w = reinterpret_cast<const float4*>(smem + OFF_WSM);
                const uint4 v = make_uint4(__float_as_uint(fmaf(o.w, w[3].x, fmaf(o.z, w[2].x, fmaf(o.y, w[1].x, o.x * w[0].x)))),
                                           __float_as_uint(fmaf(o.w, w[3].y, fmaf(o.z, w[2].y, fmaf(o.y, w[1].y, o.x * w[0].y)))),
                                           __float_as_uint(fmaf(o.w, w[3].z, fmaf(o.z, w[2].z, fmaf(o.y, w[1].z, o.x * w[0].z)))),
                                           __float_as_uint(fmaf(o.w, w[3].w, fmaf(o.z, w[2].w, fmaf(o.y, w[1].w, o.x * w[0].w)))));
                if (on) sts128<0>(to, v);
                to += 512;
            } while (to < q + n * 16);
        }
    }
    TKY(6)
    if (wet) {
        mbar_wait(sb + B_ROWS, 0);
        TKX(5)
        bar_sync(BAR_ACC, (NE + NC) * 32);
    }
    const int lim = wet ? np : 0;
    uint32_t from = at, bit = wet ? 1u : 1u << (2 * NPAIR - 2);
    uint4* out = reinterpret_cast<uint4*>(p.out + row0) + tid;
constexpr int FU = FUNR;
#pragma unroll FU
    for (int k = tid; bit < 1u << 2 * NPAIR; k += NE * 32, bit *= 4, out += NE * 32) {
        const uint4 ac = lds128(sb + OFF_ACC + k * 16), g = lds128(sb + gate_g(k)), h = lds128(sb + gate_h(k));
        const uint4 mv = lds128(sb + (row0 * 8 & 127) + k * 16 + (k < NG0 ? 0 : k < 2 * NG0 ? 0x10000 - NG0 * 16 : 0x30000 - NG0 * 32));
        const uint32_t u[4] = {ac.x + BIAS, ac.z + BIAS, ac.y + BIAS, ac.w + BIAS};
        uint32_t a[4];
        float c[4] = {0.f, 0.f, 0.f, 0.f}, d[4] = {0.f, 0.f, 0.f, 0.f};
#pragma unroll
        for (int j = 0; j < 2; j++)
            asm volatile("{ .reg .pred q; setp.ne.u32 q, %5, 0; @q ld.shared.v2.f32 {%0,%1}, [%4]; @q ld.shared.v2.f32 {%2,%3}, [%4+8]; @q add.u32 %4, %4, 16; }"
                         : "+f"(c[2 * j]), "+f"(c[2 * j + 1]), "+f"(d[2 * j]), "+f"(d[2 * j + 1]), "+r"(from) : "r"(kept & bit << j) : "memory");
#pragma unroll
        for (int j = 0; j < 4; j++) a[j] = hsub_bf2(and_or<0x007f007fu>(u[j] >> 9, k0 + 0x04800480u), k0 + 0x04c004c0u);
        mma16(c, a, wb[0], wb[1]); mma16(d, a, wb[2], wb[3]);
#pragma unroll
        for (int j = 0; j < 4; j++) a[j] = and_or<0x007f007fu>(u[j] >> 2, k0 + 0x01000100u);
        mma16(c, a, wb[0], wb[1]); mma16(d, a, wb[2], wb[3]);
#pragma unroll
        for (int j = 0; j < 4; j++) a[j] = and_or<0x00030003u>(u[j], k0);
        mma16(c, a, wb[0], wb[1]); mma16(d, a, wb[2], wb[3]);
        a[0] = hmul_bf2(pack_bf2(c[0], c[1]), g.x); a[1] = hmul_bf2(pack_bf2(c[2], c[3]), g.y);
        a[2] = hmul_bf2(pack_bf2(d[0], d[1]), g.z); a[3] = hmul_bf2(pack_bf2(d[2], d[3]), g.w);
#pragma unroll
        for (int j = 0; j < 4; j++) c[j] = d[j] = 0.f;
        mma16(c, a, wb[4], wb[5]); mma16(d, a, wb[6], wb[7]);
        if (k < lim) {
            *out = make_uint4(hadd_bf2(mv.x, hmul_bf2(pack_bf2(c[0], c[1]), h.x)), hadd_bf2(mv.y, hmul_bf2(pack_bf2(d[0], d[1]), h.z)),
                              hadd_bf2(mv.z, hmul_bf2(pack_bf2(c[2], c[3]), h.y)), hadd_bf2(mv.w, hmul_bf2(pack_bf2(d[2], d[3]), h.w)));
            if (c[0] != c[0] || c[2] != c[2]) bad |= 3u * bit;
        }
    }
    if (wet) break;
    }
    const bool wrap = lds32(sb + W_WRAP);
    if (RARE(wrap)) { left = flags(1u); kept = 0; }
#pragma unroll 1
    for (uint32_t m = left | bad; RARE(m); m &= m - 1) {
        const int j = __ffs(m) - 1, row = row_of(j);
        uint4 v = make_uint4(0u, 0u, 0u, 0u);
        if (kept >> j & 1u) v = lds128(at + __popc(kept & ((1u << j) - 1u)) * 16);
        p.out[row0 + row] = out_row(row, take(&g_ovf[role * RPAD + row], left >> j & 1u),
                                    make_float4(__uint_as_float(v.x), __uint_as_float(v.y), __uint_as_float(v.z), __uint_as_float(v.w)), p.m[row0 + row]);
        if (wrap) g_dirty[role * DROW + row] = 0;
    }
}

template <int HOP> __device__ __forceinline__ uint2 null_rec(int lane, uint32_t R) {
    if (HOP == 1) return make_uint2(0x800000u | H<1>::tag(R), (OFF_CNT1 - OFF_M) / 8);
    return make_uint2(0x08000800u | lane << 28, 0x0fff0000u | H<2>::tag(R));
}
template <int HOP> __device__ __forceinline__ void fill(uint32_t win, int ct, uint32_t R) {
    const uint2 v = null_rec<HOP>(ct, R);
#pragma unroll
    for (int i = 0; i < WIN / (NC * 512); i++) sts128<0>(win + ct * 16 + i * NC * 512, make_uint4(v.x, v.y, v.x, v.y));
}
template <int HOP> __device__ __forceinline__ void reset(uint32_t win, int lane, uint32_t R) {
    const uint2 v = null_rec<HOP>(lane, R);
    const uint32_t a = win + lane * 32 + H<HOP>::mark(R, lane >> 2) * 8;
#pragma unroll
    for (int i = 0; i < 16; i++) sts64(a + i * 1024, v.x, v.y);
    if (lane < 16) sts64(a + 16384, v.x, v.y);
}
__device__ __forceinline__ bool elect() {
    uint32_t q; asm volatile("{ .reg .pred q; elect.sync _|q, 0xffffffff; selp.u32 %0, 1, 0, q; }" : "=r"(q)); return q;
}
__device__ __forceinline__ const unsigned char* mk_ptr(uint32_t lo, uint32_t hi) { return reinterpret_cast<const unsigned char*>((uint64_t)hi << 32 | lo); }
__device__ __forceinline__ void bulk_store(uint32_t lo, uint32_t hi, uint32_t src, uint32_t n) {
    asm volatile("cp.async.bulk.global.shared::cta.bulk_group [%0], [%1], %2;" ::"l"(mk_ptr(lo, hi)), "r"(src), "r"(n) : "memory");
}
template <int HOP>
__device__ __forceinline__ void manager(const Params& p, uint32_t sb, int lane, int role, uint32_t base) {
    typedef H<HOP> h;
    constexpr int SMP = HOP == 1 ? SMP1 : SMP2;
    constexpr int V = h::NBIN / 32, PB = h::S * 8;
    const int RT = p.rounds + HOP - 1, lo = HOP == 1 && role >= NG ? NG : 0, hi = lo + h::NBIN;
    const int w = (role - lo) / (HOP * J), j = (role - lo - w * HOP * J) / HOP;
    const Ring rg(p.ring, __reduce_or_sync(0xffffffffu, lds32(sb + W_PAR)), 2 * w + HOP - 1);
    const uint32_t side = lds32(sb + W_SIDE), dhi = rg.main >> 32, mhi = rg.mid >> 32;
    const uint32_t c0 = HOP == 2 ? role & 1 : 0, up = (HOP == 1 && lo) ^ rg.par ^ c0;
    uint32_t dA = ((uint32_t)rg.main + src_off(j) + (c0 << 16) + (up ? 4096 : 12288)) ^ slot_off(base % 3);
    uint32_t dM = ((uint32_t)rg.mid + src_off(j) + c0 * 1024) ^ slot_off(base % 3);
    const int a0 = max(64, lo), b1 = min(68, hi);
    int n0 = (min(NHI, hi) - a0) * PB, a1 = (max(NLO, lo) - lo) * PB;
    const unsigned char* cr = reinterpret_cast<const unsigned char*>(rg.main) + MISC + ((side ^ rg.par) << 12);
    const unsigned char* cr0 = cr + cred_off(lo + lane * V), *cr1 = cr + cred_off(lo + 32 * V + min(lane, V - 1));
    const uint32_t ca0 = sb + h::CNT + lane * V * 4, ca1 = sb + h::CNT + (32 * V + min(lane, V + NDUM)) * 4;
    const uint32_t rot0 = (lane * V & 7) * 16, rot1 = lane * 16;
    uint32_t st = slot_steps(base);
    uint32_t init = h::init(base), prim = sb + h::STG + (HOP == 1 ? h::win(base) : 0u);
    uint32_t cs[5] = {0, 0, 0, 0, 0};
    auto sample = [&]() {
        if (V == 2) asm volatile("ld.relaxed.gpu.global.v2.u32 {%0,%1}, [%2];" : "=r"(cs[0]), "=r"(cs[1]) : "l"(cr0) : "memory");
        else asm volatile("ld.relaxed.gpu.global.v4.u32 {%0,%1,%2,%3}, [%4];" : "=r"(cs[0]), "=r"(cs[1]), "=r"(cs[2]), "=r"(cs[3]) : "l"(cr0) : "memory");
        cs[V] = ld_rlx32(reinterpret_cast<const uint32_t*>(cr1));
    };
    uint32_t low[5] = {rot0, rot0 + 16, rot0 + 32, rot0 + 48, rot1};
    TK_DECL
#pragma unroll 1
    for (int r = 0;; r++) {
        const uint32_t R = base + r, ninit = h::init(R + 1), done = prim;
        TK(5)
        mbar_wait(sb + B_FULL + (HOP - 1) * 8, r & 1);
        TK(0)
        if (SMP == 1) sample();
        uint32_t c[5];
        if (V == 2) asm volatile("ld.shared.v2.u32 {%0,%1}, [%2];" : "=r"(c[0]), "=r"(c[1]) : "r"(ca0) : "memory");
        else asm volatile("ld.shared.v4.u32 {%0,%1,%2,%3}, [%4];" : "=r"(c[0]), "=r"(c[1]), "=r"(c[2]), "=r"(c[3]) : "r"(ca0) : "memory");
        c[V] = lds32(ca1);
        uint32_t nc[5];
#pragma unroll
        for (int k = 0; k <= V; k++) {
            const uint32_t rot = k < V ? rot0 + k * 16 : rot1, z = ninit + (HOP == 1 ? rot : low[k]);
            if (HOP == 2) low[k] = min((max((int)(c[k] - low[k] - init - h::CAP * h::INC), 0) >> h::SH) * 128u + low[k], rot + BOXN * 128u);
            nc[k] = min(max(c[k] + (ninit - init - h::S * h::INC), z), (HOP == 1 ? z : ninit + low[k]) + (h::CAP - h::S) * h::INC);
        }
        if (V == 2) sts64(ca0, nc[0], nc[1]); else sts128<0>(ca0, make_uint4(nc[0], nc[1], nc[2], nc[3]));
        sts32(ca1, lane < V ? nc[V] : lane < V + NDUM ? DUMMY : r);
        __syncwarp();
        if (lane == 0) mbar_arrive(sb + B_OPEN + (HOP - 1) * 8);
        TK(1)
        TK(2)
        asm volatile("fence.proxy.async.shared::cta;" ::: "memory");
        TK(6)
        if (r >= D) {
            int it = 0;
            while (true) {
                uint32_t bad = 0;
#pragma unroll
                for (int k = 0; k <= V; k++) bad |= cs[k] - (R - D + 1);
                if (!__any_sync(0xffffffffu, bad >> 20)) break;
                if (++it > SPIN_LIMIT) __trap();
                if (it > 1) __nanosleep(100);
                sample();
            }
        }
        TK(3)
        if (SMP == 2) sample();
        if (elect()) {
            const uint32_t dB = (HOP == 1 ? dA ^ 0x10000u : dA) + (up ? 8192 : -8192), sm = prim + (lo ? 2 * PB : 0);
            bulk_store(dA, dhi, sm, 8192);
            bulk_store(dB, dhi, HOP == 1 ? sm + 8192 : prim + 68 * PB, 8192);
            if (n0 > 0) bulk_store(dM + (a0 - 64) * PB, mhi, prim + (a0 - lo) * PB, n0);
            if (a1 < (b1 - lo) * PB) bulk_store((dM ^ 4096u) + (uint32_t)((lo - NLO) * PB + a1), mhi, prim + a1, (b1 - lo) * PB - a1);
            asm volatile("cp.async.bulk.commit_group;" ::: "memory");
            if (r != RT - 1) asm volatile("cp.async.bulk.wait_group.read 0;" ::: "memory");
        }
        __syncwarp();
        TK(4)
        prim = HOP == 1 ? prim ^ 0x20000u : prim >= sb + 0x30000u ? sb : prim + (prim - sb) + 0x10000u;
        if (r == RT - 1) break;
        if (SMP == 3) sample();
        reset<HOP>(done, lane, R + HOP + 1);
        if (HOP == 1) {
            __syncwarp();
            if (lane == 0) mbar_arrive(sb + B_FREE);
        }
        if (RARE(r == RSPLIT || r == RT - D - 1)) {
            uint32_t n = NHI, m = NLO;
            if (HOP == PFH && r == RT - D - 1 && lane < 2) {
                const int row0 = role * p.R2, nr = min(p.R2, p.E - row0) & ~7;
                const uint64_t a = lane ? reinterpret_cast<uint64_t>(p.dist + row0) + 15 & ~15ull : reinterpret_cast<uint64_t>(p.m + row0);
                if (nr > 8) asm volatile("cp.async.bulk.prefetch.L2.global [%0], %1;" ::"l"(a), "r"(lane ? nr * 2 - 16 : nr * 8) : "memory");
            }
            if (r < RT - D - 1) {
                int it = 0;
                while (true) {
                    n = ld_rlx32(reinterpret_cast<const uint32_t*>(p.ring + M_CNT + (side << 12)));
                    if ((n & 0xffffu) + (n >> 16) == NB) break;
                    if (++it > SPIN_LIMIT) __trap();
                }
                m = n = min(max(__reduce_or_sync(0xffffffffu, n) & 0xffffu, (uint32_t)NLO), (uint32_t)NHI);
            }
            n0 = (min((int)n, hi) - a0) * PB;
            a1 = (max((int)m, lo) - lo) * PB;
        }
        if (HOP == 2 && RARE(r == RT - LATE)) fence_gpu();
        if (SMP == 0) sample();
        slot_next(dA, st); slot_next(dM, st);
        st = slot_rot(st);
        init = ninit;
    }
    TK_OUT
}

#define POLL_NS 200
#define POLL_NS3 400
template <int HOP> struct Reader {
    uint32_t lo, hi, st, line;
    uint32_t* cred;
    __device__ __forceinline__ void init(const Params& p, uint32_t sb, int w, int lane, int role, uint32_t base) {
        constexpr int PB = H<HOP>::S * 8;
        const int first = HOP == 1 ? (role >= NG ? NG : 0) + w * J : w * 2 * J;
        const Ring rg(p.ring, lds32(sb + W_PAR), 2 * w + HOP - 1);
        const uint32_t side = lds32(sb + W_SIDE);
        const bool mid = side ? role < 68 : role >= 64;
        const uint32_t i = role - (side ? (mid ? NLO : 68) : (mid ? 64 : 0));
        const uint32_t c = HOP == 1 ? i >> 5 : lane >> 3 & 1, in = (HOP == 1 ? (i & 31) * PB + (lane & 15) * 16 : i * PB + (lane & 7) * 16) + (lane >> 4) * src_off(3);
        lo = (in + (mid ? ((uint32_t)rg.mid ^ side << 12) + c * 1024 : (uint32_t)rg.main + (c << 16) + (side ^ rg.par ^ c ? 4096 : 12288))) ^ slot_off(base % 3);
        hi = __reduce_or_sync(0xffffffffu, (uint32_t)((mid ? rg.mid : rg.main) >> 32));
        st = slot_steps(base);
        line = opaque((HOP == 1 ? 2 * (role % NG) + (lane >> 3 & 1) : role) + (lane & 1) * 2);
        const bool both = first >= NLO && first < NHI;
        cred = lane < 1 + both ? reinterpret_cast<uint32_t*>(rg.main + MISC + (((both ? lane : first >= NG) ^ rg.par) << 12) + cred_off(role)) : nullptr;
    }
    template <int K> __device__ __forceinline__ void load1(uint2 (&v)[J]) const {
        asm volatile("ld.relaxed.gpu.global.v4.u32 {%0,%1,%2,%3}, [%4+%5];" : "=r"(v[2 * K].x), "=r"(v[2 * K].y), "=r"(v[2 * K + 1].x), "=r"(v[2 * K + 1].y)
                     : "l"(mk_ptr(lo, hi)), "n"(src_off(K)) : "memory");
    }
    static __device__ __forceinline__ uint32_t word(const uint2& v) { return HOP == 1 ? v.x : v.y; }
    template <int K> __device__ __forceinline__ void again(uint2 (&v)[J], uint32_t want, uint32_t m0, uint32_t m1, uint32_t grp) const {
        if (__ballot_sync(0xffffffffu, ((word(v[2 * K]) ^ want) & m0) | ((word(v[2 * K + 1]) ^ want) & m1)) & grp) load1<K>(v);
    }
    __device__ __forceinline__ void load(uint2 (&rec)[J]) const { load1<0>(rec); load1<1>(rec); load1<2>(rec); }
    __device__ __forceinline__ void check(uint2 (&rec)[J], uint32_t R, uint32_t ns, int lane TK_ARG) {
        const uint32_t want = H<HOP>::tag(R), mk = H<HOP>::mark(R, line);
        const uint32_t m0 = mk == 0 ? H<HOP>::TAG : 0u, m1 = mk == 1 ? H<HOP>::TAG : 0u;
        int it = 0;
        while (true) {
            uint32_t b0 = 0, b1 = 0;
#pragma unroll
            for (int j = 0; j < J; j += 2) { b0 |= word(rec[j]) ^ want; b1 |= word(rec[j + 1]) ^ want; }
            if (!__any_sync(0xffffffffu, (b0 & m0) | (b1 & m1))) break;
            if (++it > SPIN_LIMIT) __trap();
            __nanosleep(ns);
            TK_CNT(7)
            const uint32_t grp = 0xffu << (lane & 24u);
            again<0>(rec, want, m0, m1, grp); again<1>(rec, want, m0, m1, grp); again<2>(rec, want, m0, m1, grp);
        }
        if (cred) st_rlx32(cred, R + 1);
        __syncwarp();
        slot_next(lo, st);
        st = slot_rot(st);
    }
    __device__ __forceinline__ void finish() const { if (cred) st_rlx32(cred, 0u); }
};

#define NPROBE 2
__device__ __forceinline__ uint32_t probe(unsigned char* a, uint32_t zero) {
    *reinterpret_cast<uint4*>(a) = make_uint4(0u, 0u, 0u, 0u);
    *reinterpret_cast<uint4*>(a + 16) = make_uint4(0u, 0u, 0u, 0u);
    uint32_t best = ~0u, v = threadIdx.x, prev = 0;
#pragma unroll
    for (int t = 0; t <= NPROBE + 1; t++) {
        uint32_t now;
        if (t <= NPROBE) asm volatile("atom.relaxed.gpu.global.add.u32 %0, [%1], 1;" : "=r"(v) : "l"(a + (v & zero)) : "memory");
        else asm volatile("red.relaxed.gpu.global.add.u32 [%0], 1;" ::"l"(a + (v & zero)) : "memory");
        asm volatile("mov.u32 %0, %%clock;" : "=r"(now) :: "memory");
        if (t > 1) best = min(best, now - prev);
        prev = now;
    }
    return best;
}
template <bool B> struct BoolC { static constexpr bool value = B; };

__device__ __forceinline__ void stage1(const Params& p, uint32_t sb, const int pos0, int lane, const bool half) {
    typedef H<1> h;
    constexpr int NP = 4;
    static_assert(NPR == NS1 * NP * 32 - NP * 16, "tiles");
    const int RT = p.rounds;
    uint32_t ff = *reinterpret_cast<const uint16_t*>(p.ang_freq) * 0x10001u;
    auto pair_of = [&](int r, int pos) {
        const int q = r < RT - 1 ? (r * NB + blockIdx.x) * NPR + pos : (RT - 1) * NB * NPR + blockIdx.x * p.lastn + pos;
        return pos < (r < RT - 1 ? NPR : r == RT - 1 ? p.lastn : 0) && q < p.T2 ? q : -1;
    };
    uint2 vi[NP], vo[NP]; uint32_t va[NP];
    auto load_edge = [&](int r) {
#pragma unroll
        for (int u = 0; u < NP; u++) {
            const int q = max(pair_of(r, pos0 + u * 32), 0);
            vi[u] = ld_in(p.idx_in + q); vo[u] = ld_in(p.idx_out + q); va[u] = ld_in(p.angle + q);
        }
    };
    if (TEX0 && p.full) {
#pragma unroll
        for (int u = 0; u < NP; u += 2) {
            const int k = ((blockIdx.x * NPR + pos0 + lane) >> 1) + (!u ? 0 : half ? 0x40000000 : 32);
            tex2(p.ta, k, va[u], va[u + 1]); tex4(p.to, k, vo[u], vo[u + 1]); tex4(p.ti, k, vi[u], vi[u + 1]);
        }
    } else load_edge(0);
    if (blockIdx.x == 0 && pos0 == 0 && (p.T & 1)) {
        const int t = p.T - 1;
        slow_triplet(p, reinterpret_cast<const uint32_t*>(p.idx_in)[t], reinterpret_cast<const uint32_t*>(p.idx_out)[t],
                     bf16r(cos_bf(hmul_bf2(reinterpret_cast<const uint16_t*>(p.angle)[t], ff) & 0xffffu)));
    }
    ff = __reduce_or_sync(0xffffffffu, ff);
    bar_sync(BAR_S1, (NS1 + NC) * 32);
    uint32_t R = __reduce_or_sync(0xffffffffu, lds32(sb + W_BASE) & 31u);
    TK_DECL
    auto step = [&](const int r, const int qn, auto edge) {
        constexpr bool EDGE = decltype(edge)::value;
        uint32_t cc[NP], big = 0;
#pragma unroll
        for (int u = 0; u < NP; u++) {
            va[u] = hmul_bf2(va[u], ff);
            cc[u] = pack_bf2(__cosf(bf_lo(va[u])), __cosf(bf_hi(va[u])));
            big |= hmul_bf2(va[u], 0x3d003d00u);
        }
        if (RARE(big & 0x40004000u)) {
#pragma unroll 1
            for (int u = 0; u < NP; u++) {
                const uint32_t a = pick(u, va);
                float c0 = cos_bf(a & 0xffffu), c1 = cos_bf(a >> 16);
                if ((c0 != c0 || c1 != c1) && (EDGE ? pair_of(r, pos0 + u * 32) >= 0 : !half || u < 2)) {
                    const uint2 i2 = pick(u, vi), o2 = pick(u, vo);
                    if (c0 != c0) slow_triplet(p, i2.x, o2.x, c0);
                    if (c1 != c1) slow_triplet(p, i2.y, o2.y, c1);
                }
                const uint32_t v = pack_bf2(c0 != c0 ? 0.f : c0, c1 != c1 ? 0.f : c1);
#pragma unroll
                for (int k = 0; k < NP; k++) if (k == u) cc[k] = v;
            }
        }
        uint32_t bin[2 * NP], x[2 * NP], y[2 * NP];
        uint32_t dep = 0;
        auto loads = [&]() {
            const int q = qn + (dep & p.zero);
#pragma unroll
            for (int u = 0; u < NP; u += 2) {
                const int k = !u ? q : q + (half ? 0x40000000 : 32);
                tex2(p.ta, k, va[u], va[u + 1]); tex4(p.to, k, vo[u], vo[u + 1]); tex4(p.ti, k, vi[u], vi[u + 1]);
            }
        };
#pragma unroll
        for (int j = 0; j < 2 * NP; j++) {
            const uint32_t ii = j & 1 ? vi[j >> 1].y : vi[j >> 1].x, oo = j & 1 ? vo[j >> 1].y : vo[j >> 1].x;
            bin[j] = imul(ii, p.i1);
            y[j] = __byte_perm(ifma(bin[j], p.k1, ii), cc[j >> 1], j & 1 ? 0x7610 : 0x5410);
            const uint32_t bo = imul(oo, p.i2);
            x[j] = __byte_perm(ifma(bo, p.k2, imul(oo, 8.f)), bo, 0x0514);
            dep |= x[j] | y[j];
            if (EDGE && pair_of(r, pos0 + (j >> 1) * 32) < 0) bin[j] = NG + (lane & (NDUM - 1));
        }
        if (!EDGE) loads();
        else if (!LATEE) load_edge(r + 1);
        const uint32_t init = h::init(R), lim = init + ((EDGE && r == RT - 1 ? h::S : h::CAP) << h::SH);
        TKS(0)
        mbar_wait(sb + B_OPEN, ~R & 1);
        TKS(1)
        bool freed = false;
        uint32_t over = 0;
#pragma unroll
        for (int g = 0; g < 2 * NP; g += NP) if (!g || EDGE || !half) {
            constexpr int G = NP;
            uint32_t ret[G];
            int mx = 0;
#pragma unroll
            for (int j = 0; j < G; j++) ret[j] = atoms_add<h::CNT>(sb + imul(bin[g + j], 4.f), h::INC);
#pragma unroll
            for (int j = 0; j < G; j++) mx = j ? max(mx, (int)ret[j]) : (int)ret[j];
            if (!freed && __any_sync(0xffffffffu, mx >= (int)(init + 0x10000u))) { TKS(2) mbar_wait(sb + B_FREE, ~R & 1); freed = true; TKS(3) }
            TKS(2)
#pragma unroll
            for (int j = 0; j < G; j++) {
                x[g + j] = and_or<h::TAG>(ret[j], x[g + j]);
                put_rec<h::STG>(ret[j], lim, sb + and_or<0x20000u | h::PM>(ret[j], imul(bin[g + j], 256.f)), x[g + j], y[g + j]);
            }
            if (RARE(mx >= (int)lim)) {
#pragma unroll
                for (int j = 0; j < G; j++) if ((int)ret[j] >= (int)lim) over |= 1u << (g + j);
            }
        }
        __syncwarp();
        if (elect()) mbar_arrive(sb + B_FULL);
        R++;
        TKS(4)
#pragma unroll 1
        while (RARE(over)) {
            TK_CNT(7)
            const int j = __ffs(over) - 1;
            over &= over - 1;
            slow_rec1(p, pick(j, x), pick(j, y), pick(j, bin));
        }
        __syncwarp();
        if (LATEE && EDGE && r < RT - 1) load_edge(r + 1);
    };
#pragma unroll 1
    for (int q = opaque(((NB + blockIdx.x) * NPR + pos0 + lane) >> 1), r = 1; r < p.full; r++, q += NB * NPR / 2) step(r - 1, q, BoolC<false>());
#pragma unroll 1
    for (int r = max(p.full - 1, 0); r < RT; r++) step(r, 0, BoolC<true>());
    TK_OUT
}

__device__ __forceinline__ void stage2(const Params& p, uint32_t sb, int w, int lane, int role, uint32_t base1, uint32_t base) {
    typedef H<2> h;
    const int RT = p.rounds + 1;
    Reader<1> rd;
    rd.init(p, sb, w, lane, role, base1 + 3);
    uint2 rec[J];
#pragma unroll
    for (int j = 0; j < J; j++) rec[j] = null_rec<1>(lane, base1);
    uint32_t kb = sb + 0x10000u, am = 0x10000u | h::PM;
    const float unit = __uint_as_float(__reduce_or_sync(0xffffffffu, lds32(sb + W_UNIT)));
    TK_DECL
#pragma unroll 1
    for (int r = 0; r < RT; r++) {
        rd.check(rec, base1 + r, POLL_NS, lane TK_PASS);
        if (RARE(r == 1)) bar_sync(BAR_TABLE, 2 * NC * 32);
        const uint32_t want = H<1>::tag(base1 + r);
        TKS(0)
        uint2 mv[J];
#pragma unroll
        for (int j = 0; j < J; j++) {
            mv[j] = make_uint2(0u, 0u);
            const uint32_t a = sb + imul(rec[j].y & 0xffffu, 8.f);
            if (!xor_and<0x8e0000u>(rec[j].x, want)) mv[j] = lds64<OFF_M>(a);
        }
        uint32_t fl = 0;
#pragma unroll
        for (int j = 0; j < J; j++) fl |= mv[j].y;
        if (RARE(fl & 0x40000000u)) {
#pragma unroll 1
            for (int j = 0; j < J; j++) {
                const uint2 v = pick(j, mv), w = pick(j, rec);
                if ((v.y & 0x40000000u) && !((w.x ^ want) & 0x8e0000u)) {
                    if (v.x & 0x40000000u) slow_rec1(p, w.x, w.y, lds32(sb + W_ROLE) % NG);
                    else {
                        const float c = bf_hi(w.y), s = __uint_as_float(lds32(sb + W_UNIT)) * 1024.f;
                        side_add(w.x & 0xffu, __byte_perm(w.x, 0u, 0x4413) >> 3, c * (bf_lo(v.x) * s), c * (bf_hi(v.x) * s),
                                 c * (bf_lo(v.y) * s), c * (bf_hi(v.y & 0xbfffffffu) * s));
                    }
                }
            }
#pragma unroll
            for (int j = 0; j < J; j++) if (mv[j].y & 0x40000000u) rec[j].x = 0x800000u;
        }
        uint32_t w0[J], w1[J], bin[J], ret[J];
#pragma unroll
        for (int j = 0; j < J; j++) {
            const float c = bf_hi(rec[j].y), MG = 8194.0f;
            const uint32_t x = rec[j].x;
            const float v[4] = {bf_lo(mv[j].x), bf_hi(mv[j].x), bf_lo(mv[j].y), bf_hi(mv[j].y)};
            w0[j] = and_or<0xf000f000u>(x, __byte_perm(__float_as_uint(fmaf(c, v[0], MG)), __float_as_uint(fmaf(c, v[1], MG)), 0x5410));
            w1[j] = and_or<0xf000f000u>(x << 4, __byte_perm(__float_as_uint(fmaf(c, v[2], MG)), __float_as_uint(fmaf(c, v[3], MG)), 0x5410));
            bin[j] = min(xor_and<0x8e00ffu>(x, want), NB + (lane & (NDUM - 1)));
        }
        const uint32_t lim = h::init(base + r) + (r == RT - 1 ? 0x10000u : 0x20000u);
        rd.load(rec);
        TKS(1)
        mbar_wait(sb + B_OPEN + 8, (r - 1) & 1);
        TKS(2)
#pragma unroll
        for (int j = 0; j < J; j++) ret[j] = atoms_add<h::CNT>(sb + imul(bin[j], 4.f), h::INC);
        uint32_t mx = 0;
#pragma unroll
        for (int j = 0; j < J; j++) {
            w1[j] = and_or<h::TAG>(ret[j], w1[j]);
            put_rec<0>(ret[j], lim, and_xor(ret[j], am, bin[j] * 128 + kb), w0[j], w1[j]);
            mx = __viaddmax_u32(ret[j], 0u - DUMMY, mx);
        }
        __syncwarp();
        if (lane == 0) mbar_arrive(sb + B_FULL + 8);
        TKS(3)
        if (RARE(mx >= lim - DUMMY)) {
            uint32_t over = 0;
#pragma unroll
            for (int j = 0; j < J; j++) if (ret[j] - DUMMY >= lim - DUMMY) over |= 1u << j;
#pragma unroll 1
            do {
                const int j = __ffs(over) - 1;
                over &= over - 1;
                const uint32_t b = pick(j, bin), v = pick(j, ret) - lim, e = v >> h::SH, at = ((v - e * h::INC - (b & 7u) * 16u - h::CAP * 8) >> 7) + e;
                if (max(at, e) < BOXN && r < RT - LATE) g_box[(b * NB + role) * BOX + at] = make_uint2(pick(j, w0), pick(j, w1) | h::TAG);
                else slow_rec2(p, pick(j, w0), pick(j, w1), b, unit);
            } while (over);
        }
        __syncwarp();
        am = am >= 0x30000u ? 0x10000u | h::PM : am + 0x10000u;
        kb ^= am & 0x30000u;
        TKS(4)
    }
    rd.finish();
    TK_OUT
}

__device__ __forceinline__ void add_recs(uint32_t sb, int lane, const uint2 (&rec)[J], uint32_t want) {
    const uint32_t t = 0u - (lane & 1u), k = (t & 1u << 26) - (want >> 4);
    uint32_t o0[J], o1[J], g = 0;
#pragma unroll
    for (int j = 0; j < J; j++) {
        o0[j] = 0; o1[j] = 0;
        if (xor_and<0x7fffffffu>(rec[j].y, want) < 0x0ffc0000u) {
            const uint32_t a = aux_of(rec[j].x, rec[j].y, k);
            const uint32_t v0 = (rec[j].x & 0x0fff0fffu) - 0x08000800u, v1 = (rec[j].y & 0x0fff0fffu) - 0x08000800u;
            o0[j] = atoms_add<OFF_ACC>(sb + a, mux(v0, v1, t));
            o1[j] = atoms_add<OFF_ACC>(sb + (a ^ 4u), mux(v1, v0, t));
        }
    }
#pragma unroll
    for (int j = 0; j < J; j++) g |= o0[j] | o1[j];
    if (RARE(__any_sync(0xffffffffu, g & 0x80008000u))) {
#pragma unroll 1
        for (int j = 0; j < J; j++) {
            const uint2 w = pick(j, rec);
            const uint32_t aux = aux_of(w.x, w.y), p0 = pick(j, o0), p1 = pick(j, o1);
            const float2 a = acc_fix(t ? p1 : p0, w.x & 0x0fff0fffu), b = acc_fix(t ? p0 : p1, w.y & 0x0fff0fffu);
            const float unit = __uint_as_float(lds32(sb + W_UNIT));
            if (xor_and<0x7fffffffu>(w.y, want) < 0x0ffc0000u && (a.x != 0.f || a.y != 0.f || b.x != 0.f || b.y != 0.f)) {
                side_add(lds32(sb + W_ROLE), aux >> 3, a.x * unit, a.y * unit, b.x * unit, b.y * unit);
                sts32(sb + W_WRAP, 1u);
            }
            __syncwarp();
        }
    }
}
__device__ __forceinline__ void stage3(const Params& p, uint32_t sb, int w, int lane, int role, uint32_t base) {
    const int RT = p.rounds + 1;
    Reader<2> rd;
    rd.init(p, sb, w, lane, role, base);
    uint2 rec[J];
    TK_DECL
#pragma unroll 1
    for (int r = 0; r < RT; r++) {
        rd.load(rec);
        rd.check(rec, base + r, r < RT - 2 ? POLL_NS3 : 100, lane TK_PASS);
        RTS((r & 127) == 41 && w == 0, 1 + (r >> 7))
        TK(0)
        add_recs(sb, lane, rec, H<2>::tag(base + r));
        TK(1)
        if (RARE((uint32_t)(r - (RT - LATE + 1)) < 2u)) {
            static_assert(BOX == 32, "box");
            float4* box = reinterpret_cast<float4*>(g_box) + (lds32(sb + W_ROLE) * NB + (w * 2 + r - (RT - LATE + 1)) * J) * (BOX / 2) + lane;
            TKY(0)
#pragma unroll
            for (int j = 0; j < J / 2; j++) {
                const float4 v = ld_rlx128f(box + j * 32);
                rec[2 * j] = make_uint2(__float_as_uint(v.x), __float_as_uint(v.y)); rec[2 * j + 1] = make_uint2(__float_as_uint(v.z), __float_as_uint(v.w));
            }
#pragma unroll
            for (int j = 0; j < J / 2; j++) if (rec[2 * j].x) box[j * 32] = make_float4(0.f, 0.f, 0.f, 0.f);
            add_recs(sb, lane, rec, H<2>::TAG);
            TKY(1)
        }
    }
    rd.finish();
    TK_OUT
}

__device__ __forceinline__ uint32_t row_max(uint32_t x, uint32_t y) {
    const uint32_t mx = __vmaxu2(x & 0x7fff7fffu, y & 0x7fff7fffu);
    return max(mx & 0xffffu, mx >> 16);
}
__device__ __forceinline__ uint32_t amax2(uint32_t a, uint32_t b) {
    uint32_t r; asm("max.NaN.xorsign.abs.bf16x2 %0, %1, %2;" : "=r"(r) : "r"(a), "r"(b)); return r;
}
constexpr int NTAB = 9, TABC = 2 * NC * 32 * 16;
__device__ __forceinline__ void load_piece(const Params& p, uint32_t sb, int role, int i) {
    const int r0 = (role >= NG ? role - NG : role) * p.R1, n = max(min(min(p.R1, p.E - r0) * 8 - i * TABC, TABC), 0);
    asm volatile("mbarrier.arrive.expect_tx.shared::cta.b64 _, [%0], %1;" ::"r"(sb + B_TAB + i * 8), "r"(n) : "memory");
    if (n) asm volatile("cp.async.bulk.shared::cluster.global.mbarrier::complete_tx::bytes [%0], [%1], %2, [%3];"
                        ::"r"(sb + OFF_M + i * TABC), "l"(p.m + r0 + i * (TABC / 8)), "r"(n), "r"(sb + B_TAB + i * 8) : "memory");
}
static_assert(NTAB * TABC >= R1MAX * 8 && NTAB * TABC - TABC / 2 <= R1MAX * 8, "table");
constexpr int EWIN = 5;

__global__ void __launch_bounds__(NTHR, 1) fused_kernel(const Params p) {
    const int tid = threadIdx.x, lane = tid & 31;
    const int hw = __reduce_max_sync(0xffffffffu, tid >> 5);
    const uint32_t sb = __reduce_or_sync(0xffffffffu, (uint32_t)__cvta_generic_to_shared(smem));
    TKX(0)
    RTS(tid == 0, 0)
    uint32_t cta;
    asm volatile("mov.u32 %0, %%ctaid.x;" : "=r"(cta));
    if (hw != W_M1 && hw != W_M2) {
        const int job = hw < W_M1 ? hw : hw - 1;
        if (lane == 0 && job < 2 * NPAGE + 2)
            sts32(sb + OFF_PROBE + job * 4, probe(p.ring + (size_t)max(job / 2 - 1, 0) * PAGE + PROBE + (cta & 31) * 128 + (cta >> 5 & 3) * 16384 + (cta >> 7 << 20) +
                                                  ((job & 1) << 12 ^ (job < 2 ? 0x3000 : 0)), p.zero));
        if (job < 4) bar_arrive(BAR_SIDE, 5 * 32); else bar_arrive(BAR_PROBE, 27 * 32);
        TKX(1)
    }
    if (hw < NS1) {
        stage1(p, sb, hw * 128 + lane, lane, hw == NS1 - 1);
    } else if (hw == W_M1) {
        const uint32_t epoch = ld_rlx32(reinterpret_cast<const uint32_t*>(p.ring + M_BASE)) ^ 33u;
        if (lane == 0) {
            if (sb & 255u) __trap();
            mbar_init(sb + B_FULL, NS1); mbar_init(sb + B_OPEN, 1); mbar_init(sb + B_FREE, 1); mbar_init(sb + B_TFREE, NC); mbar_init(sb + B_FLAG, 32); mbar_init(sb + B_INIT, 1); sts32(sb + W_ITEM, NS1);
            for (int i = 0; i < NTAB; i++) mbar_init(sb + B_TAB + i * 8, 1);
            asm volatile("fence.proxy.async.shared::cta;" ::: "memory");
        }
        const uint32_t base = __reduce_or_sync(0xffffffffu, epoch) & 31u;
        if (lane == 0) { sts32(sb + W_BASE, epoch); sts64(sb + W_NLIST, 0u, 0u); }
        if (lane == 0 && (base & 1u)) { mbar_arrive(sb + B_OPEN); mbar_arrive(sb + B_FREE); }
        bar_arrive(BAR_BASE, (NC + 1) * 32);
        TKY(5)
        bar_sync(BAR_SIDE, 5 * 32);
        TKY(6)
        {
            const uint2 la = lds64<OFF_PROBE>(sb), lb = lds64<OFF_PROBE + 8>(sb);
            const uint32_t side = min(la.y, lb.y) < min(la.x, lb.x);
            uint32_t v = 0;
            if (lane == 0) {
                asm volatile("atom.relaxed.gpu.global.add.u32 %0, [%1], %2;" : "=r"(v) : "l"(p.ring + M_CNT), "r"(side ? 0x10000u : 1u) : "memory");
                asm volatile("red.relaxed.gpu.global.add.u32 [%0], %1;" ::"l"(p.ring + M_CNT + 4096), "r"(side ? 0x10000u : 1u) : "memory");
            }
            bar_sync(BAR_PROBE, 27 * 32);
            const uint2 l = lds64<OFF_PROBE + 8>(sb + min(lane, NPAGE - 1) * 8);
            const uint32_t mine = (__ballot_sync(0xffffffffu, (l.y < l.x) != side) & ~1u) | 0x80000000u;
            if (lane == 0) {
                uint32_t par;
                asm volatile("atom.relaxed.gpu.global.cas.b32 %0, [%1], 0, %2;" : "=r"(par) : "l"(p.ring + M_PAR), "r"(mine) : "memory");
                const uint32_t role = side ? NB - 1 - (v >> 16) : v & 0xffffu;
#pragma unroll 1
                for (int i = 0; i < AHEAD; i++) load_piece(p, sb, role, i);
                sts32(sb + W_ROLE, role); sts32(sb + W_SIDE, role < NLO ? 0u : role >= NHI ? 1u : side);
                sts32(sb + W_END, (epoch | 1023u) + 1u + (base + p.rounds) % 24u + ((epoch >> 5 & 31u) + p.rounds + 1) % 24u * 32u);
                sts32(sb + W_PAR, par ? par : mine);
            }
            TKX(2)
        }
        bar_arrive(BAR_PAR, (2 * NC + 2) * 32);
        manager<1>(p, sb, opaque(lane), __reduce_max_sync(0xffffffffu, lds32(sb + W_ROLE)), base);
        asm volatile("cp.async.bulk.wait_group 0;" ::: "memory");
        bar_arrive(BAR_H1, (NS1 + 1) * 32);
        TKX(4)
        {
            const int role = lds32(sb + W_ROLE);
#pragma unroll 1
            for (int i = lane * 16; i < DROW; i += NPF * 512) {
                float4 f[NPF];
#pragma unroll
                for (int u = 0; u < NPF; u++) f[u] = ld_rlx128f(reinterpret_cast<const float4*>(g_dirty + role * DROW + i + u * 512));
#pragma unroll
                for (int u = 0; u < NPF; u++) {
                    if (__float_as_uint(f[u].x) | __float_as_uint(f[u].y)) prefetch_l2(g_ovf + role * RPAD + i + u * 512);
                    if (__float_as_uint(f[u].z) | __float_as_uint(f[u].w)) prefetch_l2(g_ovf + role * RPAD + i + u * 512 + 8);
                }
            }
        }
        bar_sync(BAR_DONE, (NE + 1) * 32);
        TKY(0)
        if (lane < 2) { fence_gpu(); st_rlx32(reinterpret_cast<uint32_t*>(p.ring + M_FLAG + lane * 4096) + blockIdx.x, lds32(sb + W_END)); }
        TKY(1)
        __syncwarp();
        bar_arrive(BAR_ROWS, 64);
        wait_flags(p, sb, lane, lds32(sb + W_END));
        TKX(5)
        mbar_arrive(sb + B_FLAG);
        if (blockIdx.x == 0) {
            if (lane == 0) *reinterpret_cast<uint32_t*>(p.ring + M_BASE) = lds32(sb + W_END) ^ 33u;
            if (lane < 3) *reinterpret_cast<uint32_t*>(p.ring + (lane & 2 ? M_PAR : M_CNT + (lane & 1) * 4096)) = 0;
        }
    } else if (hw == W_M2) {
        uint2 sm[16];
#pragma unroll
        for (int i = 0; i < 8; i++) ld_in4(p.m + 2 * min((i * 8 + (lane >> 2)) * (p.E >> 7) + (lane & 3), (p.E >> 1) - 1), sm[2 * i], sm[2 * i + 1]);
        const float wd = __bfloat162float(lane & 16 ? p.w_up[lane & 15] : p.w_down[lane & 15]);
        const uint16_t* wg = reinterpret_cast<const uint16_t*>(lane & 16 ? p.w_rbf : p.w_sbf) + (lane & 3) * 8 + (lane >> 2 & 3);
        const uint16_t* cp = reinterpret_cast<const uint16_t*>(p.centers) + (lane & 3) * 2;
        const uint32_t w0 = __ldg(wg), w1 = __ldg(wg + 4), c0 = __ldg(cp), c1 = __ldg(cp + 1);
        if (lane == 0) { mbar_init(sb + B_FULL + 8, NC); mbar_init(sb + B_OPEN + 8, 1); mbar_init(sb + B_ROWS, 1); }
        sts128<OFF_HIST>(sb + lane * 16, make_uint4(0u, 0u, 0u, 0u)); sts128<OFF_HIST + 512>(sb + lane * 16, make_uint4(0u, 0u, 0u, 0u));
        __syncwarp();
#pragma unroll
        for (int i = 0; i < 16; i++) atoms_add<OFF_HIST>(sb + (row_max(sm[i].x, sm[i].y) >> 7) * 4, 1u);
        __syncwarp();
        uint32_t best = 0;
#pragma unroll 1
        for (int e = 11 + lane; e <= 230; e += 32) {
            uint32_t c = 0;
#pragma unroll
            for (int i = 0; i < EWIN; i++) c += lds32(sb + OFF_HIST + (e - i) * 4);
            best = max(best, c << 8 | (255 - e));
        }
        const uint32_t e = 255 - (__reduce_max_sync(0xffffffffu, best) & 255u);
        if (lane == 0) { sts32(sb + W_EXP, e); sts32(sb + W_UNIT, (e - 10) << 23); }
        reinterpret_cast<float*>(smem + OFF_WSM)[lane] = wd;
        const int wi = (lane & 4) * 4 + (lane & 1) * 8 + (lane & 2) + (lane >> 3 & 1);
        const uint32_t fr = __byte_perm(__float_as_uint(__shfl_sync(0xffffffffu, wd, wi)), __float_as_uint(__shfl_sync(0xffffffffu, wd, wi + 4)), 0x7632);
        if (lane < 16) sts32(sb + OFF_WB + lane * 4, fr);
        sts64(sb + OFF_WG + lane * 8, w0 | w1 << 16, c0 | c1 << 16);
        TKY(5)
        bar_sync(BAR_PAR, (2 * NC + 2) * 32);
        if (lane == 0) mbar_arrive(sb + B_INIT);
        manager<2>(p, sb, opaque(lane), __reduce_max_sync(0xffffffffu, lds32(sb + W_ROLE)), __reduce_or_sync(0xffffffffu, lds32(sb + W_BASE)) >> 5 & 31u);
        TKX(4)
        asm volatile("cp.async.bulk.wait_group.read 0;" ::: "memory");
        bar_sync(BAR_ROWS, 64);
        if (lane == 0) {
            const int row0 = lds32(sb + W_ROLE) * p.R2, np = min(p.R2, p.E - row0) >> 1, off = row0 * 8 & 127;
            asm volatile("mbarrier.arrive.expect_tx.shared::cta.b64 _, [%0], %1;" ::"r"(sb + B_ROWS), "r"(max(np, 0) * 16 + (max(np, 0) + NG0 - 1) / NG0 * off) : "memory");
#pragma unroll 1
            for (int k = 0; k < np; k += NG0)
                asm volatile("cp.async.bulk.shared::cluster.global.mbarrier::complete_tx::bytes [%0], [%1], %2, [%3];"
                             ::"r"(sb + H<2>::win(k / NG0)), "l"(p.m + (row0 - off / 8 + 2 * k)), "r"(min(np - k, NG0) * 16 + off), "r"(sb + B_ROWS) : "memory");
        }
        asm volatile("cp.async.bulk.wait_group 0;" ::: "memory");
    } else {
        const int w = __reduce_max_sync(0xffffffffu, hw < W_M1 ? hw - NS1 : hw - W_M1 - 1), ct = w * 32 + lane;
        if (hw < W_M1) {
            bar_sync(BAR_BASE, (NC + 1) * 32);
            const uint32_t b1 = lds32(sb + W_BASE) & 31u, b2 = lds32(sb + W_BASE) >> 5 & 31u;
            if (ct < NG + NDUM) sts32(sb + OFF_CNT1 + ct * 4, ct < NG ? H<1>::init(b1) + (ct & 7) * 16 : DUMMY);
            if (ct <= NB + NDUM) sts32(sb + OFF_CNT2 + ct * 4, ct < NB ? H<2>::init(b2) + (ct & 7) * 16 : DUMMY);
            fill<1>(sb + OFF_H1 + H<1>::win(b1), ct, b1); fill<1>(sb + OFF_H1 + H<1>::win(b1 + 1), ct, b1 + 1);
            bar_arrive(BAR_S1, (NS1 + NC) * 32);
#pragma unroll
            for (int i = 0; i < 3; i++) fill<2>(sb + H<2>::win(i), ct, b2 + i);
        }
        bar_sync(BAR_PAR, (2 * NC + 2) * 32);
        TKY(4)
        const int role = __reduce_max_sync(0xffffffffu, lds32(sb + W_ROLE));
        const uint32_t epoch = __reduce_or_sync(0xffffffffu, lds32(sb + W_BASE));
        if (hw < W_M1) {
            for (int i = ct; i < R2MAX / 2; i += NC * 32) reinterpret_cast<uint4*>(smem + OFF_ACC)[i] = make_uint4(0x40004000u, 0x40004000u, 0x40004000u, 0x40004000u);
            mbar_wait(sb + B_TAB + KDRY * 8, 0);
            stage2(p, sb, w, opaque(lane), role, (epoch & 31u) - 1u, epoch >> 5 & 31u);
        } else {
            const int e = lds32(sb + W_EXP);
            const uint32_t sc = (uint32_t)(254 - e) * 0x800080u, top = (e << 7 | 0x807fu) * 0x10001u;
            auto conv = [&](uint32_t& x, uint32_t& y) {
                const uint32_t mx = row_max(x, y);
                const int d = e - (int)(mx >> 7);
                x = hmul_bf2(x, sc); y = hmul_bf2(y, sc);
                if (d >= EWIN) y |= 0x40000000u;
                if (d < 0 || (d >= EWIN && e > 127)) { x = 0x40000000u; y = x; }
                if (mx == 0) { x = 0; y = 0; }
            };
#pragma unroll 1
            for (int i = 0; i < NTAB; i++) {
                mbar_wait(sb + B_TAB + i * 8, 0);
                if (ct == 0 && i < NTAB - AHEAD) load_piece(p, sb, role, i + AHEAD);
                const uint32_t t = sb + OFF_M + i * TABC + ct * 16, t1 = t + TABC / 2 < sb + OFF_M + R1MAX * 8 ? t + TABC / 2 : t;
                uint4 v[2] = {lds128(t), lds128(t1)};
                uint32_t ok = ~0u;
#pragma unroll
                for (int u = 0; u < 2; u++) {
                    const uint32_t a = amax2(v[u].x, v[u].y), b = amax2(v[u].z, v[u].w), mx = amax2(__byte_perm(a, b, 0x5410), __byte_perm(a, b, 0x7632)) & 0x7fff7fffu;
                    ok &= (top - mx) ^ (top - EWIN * 0x800080u - mx);
                }
                if (RARE(~ok & 0x80008000u)) {
#pragma unroll 1
                    for (int u = 0; u < 4; u++) {
                        conv(v[0].x, v[0].y);
                        const uint2 f = make_uint2(v[0].x, v[0].y);
                        v[0] = make_uint4(v[0].z, v[0].w, v[1].x, v[1].y); v[1] = make_uint4(v[1].z, v[1].w, f.x, f.y);
                    }
                } else {
#pragma unroll
                    for (int u = 0; u < 2; u++) v[u] = make_uint4(hmul_bf2(v[u].x, sc), hmul_bf2(v[u].y, sc), hmul_bf2(v[u].z, sc), hmul_bf2(v[u].w, sc));
                }
                sts128<0>(t, v[0]); sts128<0>(t1, v[1]);
                __syncwarp();
            }
            TKX(3)
            bar_sync(BAR_TABLE, 2 * NC * 32);
            stage3(p, sb, w, opaque(lane), role, epoch >> 5 & 31u);
            TKX(4)
            bar_sync(BAR_ACC, (NE + NC) * 32);
            if (!lds32(sb + W_WRAP)) {
                int i;
                asm volatile("mov.u32 %0, %%tid.x;" : "=r"(i));
                const int ro = lds32(sb + W_ROLE);
#pragma unroll 1
                for (i -= (W_M1 + 1) * 32; i < DROW / 16; i += NC * 32) {
                    float4* f = reinterpret_cast<float4*>(g_dirty + ro * DROW) + i;
                    const float4 v = ld_rlx128f(f);
                    uint32_t m = __float_as_uint(v.x) | __float_as_uint(v.y) << 1 | __float_as_uint(v.z) << 2 | __float_as_uint(v.w) << 3;
                    if (m) *f = make_float4(0.f, 0.f, 0.f, 0.f);
#pragma unroll 1
                    for (; m; m &= m - 1) {
                        const int b = __ffs(m) - 1;
                        g_ovf[ro * RPAD + i * 16 + (b & 3) * 4 + (b >> 3)] = make_float4(0.f, 0.f, 0.f, 0.f);
                    }
                }
            }
        }
    }
    if (hw < W_M1) {
        bar_arrive(BAR_DONE, (NE + 1) * 32);
        __syncwarp();
        TKX(4)
        finish_rows(p, sb, hw < NS1);
    }
}

__global__ void fb_scatter(const uint2* __restrict__ m, const int* __restrict__ idx_in, const int* __restrict__ idx_out,
                           const uint16_t* __restrict__ angle, const __nv_bfloat16* __restrict__ ang_freq, int T, int e0, int e1) {
    const uint32_t fb = *reinterpret_cast<const uint16_t*>(ang_freq);
    for (long long t = blockIdx.x * (long long)blockDim.x + threadIdx.x; t < T; t += (long long)gridDim.x * blockDim.x) {
        int o = idx_out[t];
        if (o < e0 || o >= e1) continue;
        float c = bf16r(cos_bf(hmul_bf2(angle[t], fb) & 0xffffu));
        uint2 v = __ldg(m + idx_in[t]);
        red4(&g_ovf[o - e0], c * bf_lo(v.x), c * bf_hi(v.x), c * bf_lo(v.y), c * bf_hi(v.y));
    }
}
__global__ void fb_final(const Params p, int e0, int e1) {
    int e = e0 + blockIdx.x * blockDim.x + threadIdx.x;
    if (e >= e1) return;
    float4 a4 = g_ovf[e - e0];
    g_ovf[e - e0] = make_float4(0.f, 0.f, 0.f, 0.f);
    float a[4] = {a4.x, a4.y, a4.z, a4.w};
    float d = __bfloat162float(p.dist[e]);
    float g[4] = {0, 0, 0, 0}, h[4] = {0, 0, 0, 0};
    for (int r = 0; r < 8; r++) {
        float df = bf16r(d - __bfloat162float(p.centers[r]));
        float rb = bf16r(expf(bf16r(-10.0f * bf16r(df * df))));
        for (int k = 0; k < 4; k++) {
            g[k] += rb * __bfloat162float(p.w_sbf[r * 4 + k]);
            h[k] += rb * __bfloat162float(p.w_rbf[r * 4 + k]);
        }
    }
    float ag[4];
    for (int k = 0; k < 4; k++) {
        float s = 0.f;
        for (int j = 0; j < 4; j++) s += a[j] * __bfloat162float(p.w_down[j * 4 + k]);
        ag[k] = bf16r(s * g[k]);
    }
    uint2 mv = p.m[e];
    float mm[4] = {bf_lo(mv.x), bf_hi(mv.x), bf_lo(mv.y), bf_hi(mv.y)};
    __nv_bfloat16 o[4];
    for (int k = 0; k < 4; k++) {
        float u = 0.f;
        for (int j = 0; j < 4; j++) u += ag[j] * __bfloat162float(p.w_up[j * 4 + k]);
        o[k] = __float2bfloat16_rn(mm[k] + bf16r(bf16r(u) * bf16r(h[k])));
    }
    p.out[e] = *reinterpret_cast<uint2*>(o);
}

}

static cudaTextureObject_t make_tex(const void* ptr, size_t bytes, int words) {
    cudaResourceDesc rd = {}; cudaTextureDesc td = {};
    rd.resType = cudaResourceTypeLinear; rd.res.linear.devPtr = const_cast<void*>(ptr); rd.res.linear.sizeInBytes = bytes;
    rd.res.linear.desc = cudaCreateChannelDesc(32, words > 1 ? 32 : 0, words > 2 ? 32 : 0, words > 2 ? 32 : 0, cudaChannelFormatKindUnsigned);
    td.readMode = cudaReadModeElementType;
    cudaTextureObject_t t = 0;
    if (cudaCreateTextureObject(&t, &rd, &td, nullptr) != cudaSuccess) { t = 0; (void)cudaGetLastError(); }
    return t;
}

extern "C" void kernel_launch(void* const* d_in, const int* in_sizes, int n_in, void* d_out, int out_size) {
    typedef const __nv_bfloat16* B;
    Params p;
    p.m = (const uint2*)d_in[0]; p.idx_in = (const uint2*)d_in[1]; p.idx_out = (const uint2*)d_in[2]; p.dist = (B)d_in[3];
    p.angle = (const uint32_t*)d_in[4]; p.centers = (B)d_in[5]; p.ang_freq = (B)d_in[6]; p.w_rbf = (B)d_in[7]; p.w_sbf = (B)d_in[8];
    p.w_down = (B)d_in[9]; p.w_up = (B)d_in[10]; p.out = (uint2*)d_out;
    p.E = in_sizes[3]; p.T = in_sizes[1]; p.T2 = p.T >> 1; p.zero = 0;
    p.R1 = p.R2 = p.rounds = p.lastn = p.full = 0; p.i1 = p.i2 = p.k1 = p.k2 = 0.f;
    static int ok = -1;
    static unsigned char* ring = nullptr;
    if (ok < 0) {
        void* ra = nullptr;
        cudaGetSymbolAddress(&ra, g_ring);
        ring = reinterpret_cast<unsigned char*>(((uintptr_t)ra + PAGE - 1) & ~(uintptr_t)(PAGE - 1));
        int dev = 0, sms = 0, occ = 0;
        cudaGetDevice(&dev);
        cudaDeviceGetAttribute(&sms, cudaDevAttrMultiProcessorCount, dev);
        cudaError_t e = cudaFuncSetAttribute(fused_kernel, cudaFuncAttributeMaxDynamicSharedMemorySize, SMEM_BYTES);
        if (e == cudaSuccess) e = cudaOccupancyMaxActiveBlocksPerMultiprocessor(&occ, fused_kernel, NTHR, SMEM_BYTES);
        ok = (e == cudaSuccess && occ >= 1 && sms >= NB) ? 1 : 0;
        (void)cudaGetLastError();
    }
    p.ring = ring;
    static cudaTextureObject_t tx[3];
    static const void* of[3];
    static int of_t = -1;
    if (of[0] != d_in[1] || of[1] != d_in[2] || of[2] != d_in[4] || of_t != p.T) {
        tx[0] = make_tex(p.idx_in, (size_t)(p.T >> 2) * 16, 4); tx[1] = make_tex(p.idx_out, (size_t)(p.T >> 2) * 16, 4); tx[2] = make_tex(p.angle, (size_t)(p.T >> 2) * 8, 2);
        of[0] = d_in[1]; of[1] = d_in[2]; of[2] = d_in[4]; of_t = p.T;
    }
    p.ti = tx[0]; p.to = tx[1]; p.ta = tx[2];
    const bool fused = ok == 1 && p.E <= EMAX && p.E >= 2 * NB && p.E % 2 == 0 && p.T >= 2;
    if (fused) {
        p.R1 = ((p.E + NG - 1) / NG + 1) & ~1;
        if (p.R1 > 1024) p.R1 = (p.R1 + 15) & ~15;
        p.R2 = ((p.E + NB - 1) / NB + 1) & ~1;
        p.i1 = nextafterf(1.f / p.R1, 2.f); p.i2 = nextafterf(1.f / p.R2, 2.f); p.k1 = -(float)p.R1; p.k2 = -8.f * p.R2;
        const int per = NB * NPR;
        int full = p.T2 / per, rest = p.T2 - full * per;
        p.full = p.ti && p.to && p.ta ? full : 0;
        p.lastn = (rest + NB - 1) / NB;
        if (p.lastn > NPR / 2) { full++; p.lastn = 0; }
        if (full < D) { full = D; p.lastn = 0; }
        p.rounds = full + 1;
        fused_kernel<<<NB, NTHR, SMEM_BYTES>>>(p);
    } else {
        for (int e0 = 0; e0 < p.E; e0 += EMAX) {
            int e1 = p.E - e0 < EMAX ? p.E : e0 + EMAX;
            fb_scatter<<<1056, 256>>>(p.m, (const int*)d_in[1], (const int*)d_in[2], (const uint16_t*)d_in[4], p.ang_freq, p.T, e0, e1);
            fb_final<<<(e1 - e0 + 255) / 256, 256>>>(p, e0, e1);
        }
    }
}
```

```cpp
#include <cuda_runtime.h>
#include <cuda_bf16.h>
#include <stdint.h>
#include <math.h>

#define LATEE 0
#define AHEAD 3
#define RSPLIT (D - 1)
#define TEX0 1
#define KDRY 4
#define SMP1 0
#define SMP2 1
#define FUNR 1
#define DRY2 1
#define PFH 1
#define NPF 6
#define GU 16
#define MBF 1
#define FNS 50
#define RARE(x) __builtin_expect(!!(x), 0)
namespace {

constexpr int NB = 132, NG = 66;
constexpr int R2MAX = 6062, R1MAX = 12128;
constexpr int EMAX = NB * R2MAX;
constexpr int NTHR = 1024;
constexpr int NS1 = 8, NC = 11, J = 6;
constexpr int NPR = 960;
constexpr int D = 3;
constexpr int WIN = 16896;
constexpr int NDUM = 16;
constexpr uint32_t DUMMY = 0xc0000000u;

constexpr int OFF_ACC = WIN, OFF_BAR = OFF_ACC + R2MAX * 8;
constexpr int OFF_H1 = 0x10000 + WIN, OFF_M = OFF_H1 + WIN, OFF_PROBE = OFF_M + R1MAX * 8;
constexpr int OFF_CNT1 = OFF_H1 + 0x20000 + WIN, OFF_CNT2 = OFF_CNT1 + (NG + NDUM + 2) * 4;
constexpr int OFF_HIST = OFF_ACC;
constexpr int OFF_WSM = OFF_CNT2 + (NB + NDUM) * 4 + 16;
constexpr int OFF_WB = OFF_WSM + 128, OFF_WG = OFF_WB + 64;
constexpr int SMEM_BYTES = OFF_WG + 256;
static_assert(SMEM_BYTES <= 232448 && OFF_BAR + 64 <= 0x10000 && OFF_PROBE + 256 <= 0x30000, "smem");
static_assert(OFF_BAR % 8 == 0 && OFF_WSM % 16 == 0 && OFF_CNT2 % 16 == 0, "align");
static_assert(NC * J == NG && NC * 32 * 6 * 16 == 2 * WIN, "shape");

template <int HOP> struct H {
    static constexpr int S = HOP == 1 ? 32 : 16, NBIN = HOP == 1 ? NG : NB, CAP = 2 * S, SH = HOP == 1 ? 11 : 12;
    static constexpr int TB = HOP == 1 ? 17 : 28, CNT = HOP == 1 ? OFF_CNT1 : OFF_CNT2, STG = HOP == 1 ? OFF_H1 : 0;
    static constexpr uint32_t INC = (1u << SH) + 8u, PM = (S - 1) * 8, TAG = 7u << TB;
    static __device__ __forceinline__ uint32_t tag(uint32_t R) { return R << TB & TAG; }
    static __device__ __forceinline__ uint32_t init(uint32_t R) { return tag(R) | ((1u << TB) - 0x10000u); }
    static __device__ __forceinline__ uint32_t mark(uint32_t R, uint32_t line) { return ((HOP == 1 ? R >> 1 : R) + line) & 3u; }
    static __device__ __forceinline__ uint32_t win(int r) { return HOP == 1 ? (r & 1) << 17 : (0x310u >> (r % 3 * 4) & 3u) << 16; }
};

constexpr uint32_t PAGE = 1u << 21;
constexpr int NPAGE = NC + 2;
__device__ __align__(256) unsigned char g_ring[(size_t)(NPAGE + 1) * PAGE];
constexpr int MISC = 0xa0000;
constexpr int M_CNT = MISC + 1024, M_PAR = M_CNT + 4;
constexpr int M_BASE = M_CNT + 8;
constexpr int M_FLAG = MISC + 2048;
constexpr int PROBE = MISC + 0x40000;
__device__ __forceinline__ uint32_t cred_off(uint32_t role) { return role * 4 + min(role >> 5, 3u) * (16384 - 128); }
struct Ring {
    uint64_t main, mid;
    uint32_t par;
    __device__ __forceinline__ Ring(const unsigned char* ring, uint32_t pars, int k) {
        main = reinterpret_cast<uint64_t>(ring) + ((uint64_t)k << 20);
        par = pars >> (k >> 1) & 1u;
        mid = reinterpret_cast<uint64_t>(ring) + (uint64_t)NC * PAGE + (((k >> 3 << 20) + (k >> 2 & 1) * 0x11000u + (k & 1) * 2048) ^ (k >> 1 & 1) * 0x3000u ^ (pars >> (NC + (k >> 4)) & 1u) << 12);
    }
};
constexpr int NLO = 60, NHI = 72;
__host__ __device__ constexpr uint32_t src_off(int j) { return (j % 3) << 14 | (j / 3) << 18; }
__device__ __forceinline__ uint32_t slot_off(uint32_t s) { return (0xa930u >> s * 4 & 15u) << 16; }
__device__ __forceinline__ uint32_t slot_steps(uint32_t R) { return (uint32_t)(0x30a09030aull >> (2 - R % 3) * 8) & 0xffffffu; }
__device__ __forceinline__ void slot_next(uint32_t& a, uint32_t st) { a ^= st & 0xf0000u; }
__device__ __forceinline__ uint32_t slot_rot(uint32_t st) { return __byte_perm(st, 0u, 0x4102); }
constexpr int RPAD = 6064, DROW = 6144;
__device__ __align__(128) uint8_t g_dirty[NB * DROW];
constexpr int BOX = 32, BOXN = 24, LATE = 8;
__device__ __align__(128) uint2 g_box[NB * NB * BOX];
__device__ __align__(128) float4 g_ovf[NB * RPAD];

struct Params {
    const uint2* m; const uint2* idx_in; const uint2* idx_out; const __nv_bfloat16* dist; const uint32_t* angle;
    const __nv_bfloat16* centers; const __nv_bfloat16* ang_freq; const __nv_bfloat16* w_rbf; const __nv_bfloat16* w_sbf;
    const __nv_bfloat16* w_down; const __nv_bfloat16* w_up; uint2* out; unsigned char* ring;
    cudaTextureObject_t ti, to, ta;
    int E, T, T2, R1, R2, rounds, lastn, full; uint32_t zero; float i1, i2, k1, k2;
};

__device__ __forceinline__ float bf16r(float x) { return __bfloat162float(__float2bfloat16_rn(x)); }
__device__ __forceinline__ float bf_lo(uint32_t v) { return __uint_as_float(v << 16); }
__device__ __forceinline__ float bf_hi(uint32_t v) { return __uint_as_float(v & 0xffff0000u); }
__device__ __forceinline__ void red4(float4* a, float x, float y, float z, float w) {
    asm volatile("red.global.add.v4.f32 [%0], {%1,%2,%3,%4};" ::"l"(a), "f"(x), "f"(y), "f"(z), "f"(w) : "memory");
}
__device__ __forceinline__ void bar_sync(int id, int n) { __syncwarp(); asm volatile("bar.sync %0, %1;" ::"r"(id), "r"(n) : "memory"); }
__device__ __forceinline__ void bar_arrive(int id, int n) { __syncwarp(); asm volatile("bar.arrive %0, %1;" ::"r"(id), "r"(n) : "memory"); }
template <int OFF> __device__ __forceinline__ uint32_t atoms_add(uint32_t addr, uint32_t v) {
    uint32_t r; asm volatile("atom.shared.add.u32 %0, [%1+%3], %2;" : "=r"(r) : "r"(addr), "r"(v), "n"(OFF) : "memory"); return r;
}
__device__ __forceinline__ void sts64(uint32_t addr, uint32_t x, uint32_t y) {
    asm volatile("st.shared.v2.u32 [%0], {%1,%2};" ::"r"(addr), "r"(x), "r"(y) : "memory");
}
__device__ __forceinline__ void sts32(uint32_t addr, uint32_t x) { asm volatile("st.shared.u32 [%0], %1;" ::"r"(addr), "r"(x) : "memory"); }
template <int OFF = 0> __device__ __forceinline__ uint2 lds64(uint32_t addr) {
    uint2 v; asm volatile("ld.shared.v2.u32 {%0,%1}, [%2+%3];" : "=r"(v.x), "=r"(v.y) : "r"(addr), "n"(OFF) : "memory"); return v;
}
__device__ __forceinline__ uint32_t lds32(uint32_t addr) {
    uint32_t v; asm volatile("ld.shared.u32 %0, [%1];" : "=r"(v) : "r"(addr) : "memory"); return v;
}
template <int OFF> __device__ __forceinline__ void sts128(uint32_t a, const uint4& v) {
    asm volatile("st.shared.v4.u32 [%0+%5], {%1,%2,%3,%4};" ::"r"(a), "r"(v.x), "r"(v.y), "r"(v.z), "r"(v.w), "n"(OFF) : "memory");
}
__device__ __forceinline__ uint4 lds128(uint32_t a) {
    uint4 v; asm volatile("ld.shared.v4.u32 {%0,%1,%2,%3}, [%4];" : "=r"(v.x), "=r"(v.y), "=r"(v.z), "=r"(v.w) : "r"(a) : "memory"); return v;
}
__device__ __forceinline__ uint32_t ld_rlx32(const uint32_t* p) {
    uint32_t v; asm volatile("ld.relaxed.gpu.global.u32 %0, [%1];" : "=r"(v) : "l"(p) : "memory"); return v;
}
__device__ __forceinline__ uint2 ld_rlx64(const void* p) {
    uint2 v; asm volatile("ld.relaxed.gpu.global.v2.u32 {%0,%1}, [%2];" : "=r"(v.x), "=r"(v.y) : "l"(p) : "memory"); return v;
}
__device__ __forceinline__ float4 ld_rlx128f(const float4* p) {
    float4 v; asm volatile("ld.relaxed.gpu.global.v4.f32 {%0,%1,%2,%3}, [%4];" : "=f"(v.x), "=f"(v.y), "=f"(v.z), "=f"(v.w) : "l"(p) : "memory"); return v;
}
__device__ __forceinline__ float4 take(float4* p, bool q) {
    float4 v;
    asm volatile("{ .reg .b128 a; .reg .b64 x, y; .reg .pred q; mov.b64 x, 0; mov.b128 a, {x, x}; setp.ne.u32 q, %5, 0;\n"
                 "@q atom.relaxed.gpu.global.exch.b128 a, [%4], a; mov.b128 {x, y}, a; mov.b64 {%0,%1}, x; mov.b64 {%2,%3}, y; }"
                 : "=f"(v.x), "=f"(v.y), "=f"(v.z), "=f"(v.w) : "l"(p), "r"((uint32_t)q) : "memory");
    return v;
}
__device__ __forceinline__ void fence_gpu() { asm volatile("fence.acq_rel.gpu;" ::: "memory"); }
__device__ __forceinline__ void st_rlx32(uint32_t* p, uint32_t v) { asm volatile("st.relaxed.gpu.global.u32 [%0], %1;" ::"l"(p), "r"(v) : "memory"); }
__device__ __forceinline__ uint32_t hmul_bf2(uint32_t a, uint32_t b) {
    uint32_t r; asm("mul.rn.bf16x2 %0, %1, %2;" : "=r"(r) : "r"(a), "r"(b)); return r;
}
__device__ __forceinline__ uint32_t hsub_bf2(uint32_t a, uint32_t b) {
    uint32_t r; asm("sub.rn.bf16x2 %0, %1, %2;" : "=r"(r) : "r"(a), "r"(b)); return r;
}
__device__ __forceinline__ uint32_t hadd_bf2(uint32_t a, uint32_t b) {
    uint32_t r; asm("add.rn.bf16x2 %0, %1, %2;" : "=r"(r) : "r"(a), "r"(b)); return r;
}
__device__ __forceinline__ int opaque(int v) { return __shfl_sync(0xffffffffu, v, threadIdx.x); }
constexpr int SPIN_LIMIT = 1 << 22;

__constant__ uint32_t c_inv2pi[8] = {0u, 0x28be60dbu, 0x9391054au, 0x7f09d5f4u, 0x7d4d3770u, 0x36d8a566u, 0x4f10e410u, 0x7f9458eau};
constexpr uint32_t BIGX = 0x4280u;
__device__ __forceinline__ float cos_big(uint32_t xb) {
    uint32_t e = (xb >> 7) & 0xffu, M = (xb & 0x7fu) | 0x80u;
    uint32_t pp = e - 102u;
    uint32_t wi = pp >> 5;
    uint32_t t0 = c_inv2pi[wi], t1 = c_inv2pi[wi + 1], t2 = c_inv2pi[wi + 2];
    uint32_t f = M * __funnelshift_l(t1, t0, pp) + __umulhi(M, __funnelshift_l(t2, t1, pp));
    float c = __cosf((float)(int)f * 1.4629180792671596e-9f);
    return e == 255u ? __uint_as_float(0x7fc00000u) : c;
}
__device__ __forceinline__ float cos_bf(uint32_t xb) {
    return (xb & 0x7fffu) > BIGX ? cos_big(xb) : __cosf(__uint_as_float(xb << 16));
}
__device__ __forceinline__ uint32_t pack_bf2(float lo, float hi) {
    uint32_t r; asm("cvt.rn.bf16x2.f32 %0, %1, %2;" : "=r"(r) : "f"(hi), "f"(lo)); return r;
}
template <int N> __device__ __forceinline__ uint32_t pick(int k, const uint32_t (&a)[N]) {
    uint32_t v = a[0];
#pragma unroll
    for (int i = 1; i < N; i++) if (k == i) v = a[i];
    return v;
}
template <int N> __device__ __forceinline__ uint2 pick(int k, const uint2 (&a)[N]) {
    uint2 v = a[0];
#pragma unroll
    for (int i = 1; i < N; i++) if (k == i) v = a[i];
    return v;
}
__device__ __forceinline__ uint32_t imul(uint32_t a, float s) { uint32_t r; asm("mul.rz.f32 %0, %1, %2;" : "=r"(r) : "r"(a), "f"(s)); return r; }
__device__ __forceinline__ uint32_t ifma(uint32_t a, float s, uint32_t c) { uint32_t r; asm("fma.rn.f32 %0, %1, %2, %3;" : "=r"(r) : "r"(a), "f"(s), "r"(c)); return r; }
extern __shared__ __align__(1024) unsigned char smem[];
__device__ __forceinline__ void side_add(uint32_t bin, uint32_t row, float a, float b, float c, float d) {
    red4(&g_ovf[bin * RPAD + row], a, b, c, d);
    g_dirty[bin * DROW + row] = 1;
}
__device__ __forceinline__ void slow_triplet(const Params& p, uint32_t ii, uint32_t oo, float c) {
    const uint2 v = __ldg(p.m + ii);
    const uint32_t bo = imul(oo, p.i2);
    side_add(bo, oo - bo * p.R2, c * bf_lo(v.x), c * bf_hi(v.x), c * bf_lo(v.y), c * bf_hi(v.y));
}
__device__ __forceinline__ void slow_rec1(const Params& p, uint32_t x, uint32_t y, uint32_t bin) {
    const uint2 v = __ldg(p.m + bin * p.R1 + (y & 0xffffu));
    const float c = bf_hi(y);
    side_add(x & 0xffu, __byte_perm(x, 0u, 0x4413) >> 3, c * bf_lo(v.x), c * bf_hi(v.x), c * bf_lo(v.y), c * bf_hi(v.y));
}
__device__ __forceinline__ uint32_t aux_of(uint32_t w0, uint32_t w1, uint32_t k = 0) {
    uint32_t u; asm("lop3.b32 %0, %1, %2, 0xf000f000, 0xe4;" : "=r"(u) : "r"(w0), "r"((w1 >> 4) + k));
    return __byte_perm(u, 0u, 0x4413);
}
__device__ __forceinline__ void slow_rec2(const Params& p, uint32_t w0, uint32_t w1, uint32_t bin, float unit) {
    side_add(bin, aux_of(w0, w1) >> 3, (float)((int)(w0 & 0xfffu) - 2048) * unit, (float)((int)(w0 >> 16 & 0xfffu) - 2048) * unit,
             (float)((int)(w1 & 0xfffu) - 2048) * unit, (float)((int)(w1 >> 16 & 0xfffu) - 2048) * unit);
}
template <uint32_t M> __device__ __forceinline__ uint32_t and_or(uint32_t a, uint32_t c) {
    uint32_t r; asm("lop3.b32 %0, %1, %2, %3, 0xea;" : "=r"(r) : "r"(a), "n"(M), "r"(c)); return r;
}
template <uint32_t M> __device__ __forceinline__ uint32_t xor_and(uint32_t a, uint32_t c) {
    uint32_t r; asm("lop3.b32 %0, %1, %2, %3, 0x48;" : "=r"(r) : "r"(a), "n"(M), "r"(c)); return r;
}
__device__ __forceinline__ uint32_t mux(uint32_t a, uint32_t b, uint32_t m) {
    uint32_t r; asm("lop3.b32 %0, %1, %2, %3, 0xd8;" : "=r"(r) : "r"(a), "r"(b), "r"(m)); return r;
}
__device__ __forceinline__ uint32_t and_xor(uint32_t a, uint32_t m, uint32_t c) {
    uint32_t r; asm("lop3.b32 %0, %1, %2, %3, 0x6a;" : "=r"(r) : "r"(a), "r"(m), "r"(c)); return r;
}
__device__ __forceinline__ uint2 ld_in(const uint2* a) {
    uint2 v; asm volatile("ld.global.nc.L1::no_allocate.v2.u32 {%0,%1}, [%2];" : "=r"(v.x), "=r"(v.y) : "l"(a)); return v;
}
__device__ __forceinline__ uint32_t ld_in(const uint32_t* a) {
    uint32_t v; asm volatile("ld.global.nc.L1::no_allocate.u32 %0, [%1];" : "=r"(v) : "l"(a)); return v;
}
__device__ __forceinline__ void ld_in4(const uint2* p, uint2& a, uint2& b) {
    asm volatile("ld.global.nc.L1::no_allocate.v4.u32 {%0,%1,%2,%3}, [%4];" : "=r"(a.x), "=r"(a.y), "=r"(b.x), "=r"(b.y) : "l"(p));
}
__device__ __forceinline__ void tex4(cudaTextureObject_t t, int i, uint2& a, uint2& b) {
    asm volatile("tex.1d.v4.u32.s32 {%0,%1,%2,%3}, [%4, {%5}];" : "=r"(a.x), "=r"(a.y), "=r"(b.x), "=r"(b.y) : "l"(t), "r"(i));
}
__device__ __forceinline__ void tex2(cudaTextureObject_t t, int i, uint32_t& a, uint32_t& b) {
    asm volatile("{ .reg .b32 z, w; tex.1d.v4.u32.s32 {%0,%1,z,w}, [%2, {%3}]; }" : "=r"(a), "=r"(b) : "l"(t), "r"(i) : "memory");
}
template <int OFF> __device__ __forceinline__ void put_rec(uint32_t ret, uint32_t lim, uint32_t addr, uint32_t x, uint32_t y) {
    asm volatile("{ .reg .pred q; setp.lt.u32 q, %0, %1; @q st.shared.v2.u32 [%2+%5], {%3,%4}; }" ::"r"(ret), "r"(lim), "r"(addr), "r"(x), "r"(y), "n"(OFF) : "memory");
}
__device__ __forceinline__ uint32_t mbar_try(uint32_t mb, uint32_t parity) {
    uint32_t ok;
    asm volatile("{ .reg .pred q; mbarrier.try_wait.parity.shared::cta.b64 q, [%1], %2; selp.u32 %0, 1, 0, q; }" : "=r"(ok) : "r"(mb), "r"(parity) : "memory");
    return ok;
}
__device__ __forceinline__ void mbar_wait(uint32_t mb, uint32_t parity) {
    if (!mbar_try(mb, parity)) {
        int it = 0;
        while (!mbar_try(mb, parity)) if (++it > SPIN_LIMIT) __trap();
    }
}
__device__ __forceinline__ void mbar_init(uint32_t mb, uint32_t n) { asm volatile("mbarrier.init.shared::cta.b64 [%0], %1;" ::"r"(mb), "r"(n) : "memory"); }
__device__ __forceinline__ void mbar_arrive(uint32_t mb) { asm volatile("mbarrier.arrive.shared::cta.b64 _, [%0];" ::"r"(mb) : "memory"); }
constexpr int B_FULL = OFF_BAR, B_OPEN = OFF_BAR + 16, B_FREE = OFF_BAR + 32;
constexpr int W_END = OFF_BAR + 40, W_SIDE = OFF_BAR + 44, W_PAR = OFF_BAR + 48, W_ROLE = OFF_BAR + 52, W_EXP = OFF_BAR + 56, W_UNIT = OFF_BAR + 60, W_NLIST = OFF_PROBE + 112, W_WRAP = OFF_PROBE + 116, W_BASE = OFF_PROBE + 120, B_TAB = OFF_PROBE + 128, B_ROWS = OFF_PROBE + 248, B_TFREE = OFF_PROBE + 240, B_FLAG = OFF_PROBE + 232, B_INIT = OFF_PROBE + 224, W_ITEM = OFF_PROBE + 124;
enum { BAR_S1 = 1, BAR_SIDE, BAR_PROBE, BAR_PAR, BAR_TABLE, BAR_DONE, BAR_ACC, BAR_FLAG, BAR_FLAG1, BAR_H1, BAR_BASE, BAR_ROWS };
constexpr int W_M1 = NS1 + NC, W_M2 = 31;

#define RTS(c, i)
#define TK_DECL
#define TK(i)
#define TK_CNT(i)
#define TK_OUT
#define TK_ARG
#define TK_PASS
#define TKS(i) TK(i)
#define TKX(i)
#define TKY(i) {}
#define TKZ(i, d)

__device__ __forceinline__ void prefetch_l2(const void* a) { asm volatile("prefetch.global.L2 [%0];" ::"l"(a)); }
__device__ __forceinline__ void wait_flags(const Params& p, uint32_t sb, int lane, uint32_t need) {
    const unsigned char* f = p.ring + M_FLAG + (lds32(sb + W_SIDE) << 12);
    int it = 0;
    while (true) {
        uint32_t a[4];
        asm volatile("ld.acquire.gpu.global.v4.u32 {%0,%1,%2,%3}, [%4];" : "=r"(a[0]), "=r"(a[1]), "=r"(a[2]), "=r"(a[3]) : "l"(f + min(lane, 16) * 16) : "memory");
        const uint32_t d = (a[0] ^ need) | (a[1] ^ need) | (lane < 16 ? (a[2] ^ need) | (a[3] ^ need) : 0u);
        if (__all_sync(0xffffffffu, d == 0)) break;
        __nanosleep(FNS);
        if (++it > SPIN_LIMIT) __trap();
    }
}
__device__ __forceinline__ float exp_fast(float x) { float r; asm("ex2.approx.ftz.f32 %0, %1;" : "=f"(r) : "f"(x * 1.4426950408889634f)); return r; }
constexpr uint32_t BIAS = 0x3d803d80u, ZERO = 0x7d80u;
__device__ __forceinline__ float2 acc_fix(uint32_t old, uint32_t q) {
    const uint32_t u = old + BIAS, n = u + q - 0x08000800u;
    return make_float2((float)((int)(u & 0xffffu) + (int)(q & 0xffffu) - 2048 - (int)(n & 0xffffu)), (float)((int)(u >> 16) + (int)(q >> 16) - 2048 - (int)(n >> 16)));
}
constexpr int NE = NS1 + NC, NPAIR = (R2MAX / 2 + NE * 32 - 1) / (NE * 32), NTILE = 16, NG0 = NS1 * 8 * NTILE;
constexpr int OFF_G = OFF_M, GH = R2MAX * 8, OFF_LIST = OFF_G;
static_assert(2 * R2MAX <= R1MAX && NG0 * 16 + 112 <= WIN && 3 * NG0 >= NPAIR * NE * 32 && NPAIR * NE * 64 <= DROW, "gates");
__device__ __forceinline__ int gate_g(int k) { return (k < NG0 ? OFF_H1 : OFF_G) + k * 16; }
__device__ __forceinline__ int gate_h(int k) { return (k < NG0 ? OFF_H1 + 0x20000 : OFF_G + GH) + k * 16; }
__device__ __forceinline__ uint2 out_row(int row, const float4& o, const float4& add, const uint2& mv) {
    const float* w = reinterpret_cast<const float*>(smem + OFF_WSM);
    const float unit = *reinterpret_cast<const float*>(smem + W_UNIT), K = 8388608.f + ZERO;
    const uint2 ac = reinterpret_cast<const uint2*>(smem + OFF_ACC)[row];
    const uint32_t* g = reinterpret_cast<const uint32_t*>(smem + gate_g(row >> 1)) + (row & 1), *h = reinterpret_cast<const uint32_t*>(smem + gate_h(row >> 1)) + (row & 1);
    const uint32_t c0 = ac.x + BIAS, c1 = ac.y + BIAS;
    const float a[4] = {fmaf(__uint_as_float(__byte_perm(c0, 0x4b00u, 0x5410)) - K, unit, o.x), fmaf(__uint_as_float(__byte_perm(c0, 0x4b00u, 0x5432)) - K, unit, o.y),
                        fmaf(__uint_as_float(__byte_perm(c1, 0x4b00u, 0x5410)) - K, unit, o.z), fmaf(__uint_as_float(__byte_perm(c1, 0x4b00u, 0x5432)) - K, unit, o.w)};
    float sd[4], uu[4];
#pragma unroll
    for (int k = 0; k < 4; k++) sd[k] = fmaf(a[3], w[12 + k], fmaf(a[2], w[8 + k], fmaf(a[1], w[4 + k], a[0] * w[k])));
    const uint32_t a01 = hmul_bf2(pack_bf2(sd[0] + add.x, sd[1] + add.y), g[0]), a23 = hmul_bf2(pack_bf2(sd[2] + add.z, sd[3] + add.w), g[2]);
#pragma unroll
    for (int k = 0; k < 4; k++) uu[k] = fmaf(bf_hi(a23), w[28 + k], fmaf(bf_lo(a23), w[24 + k], fmaf(bf_hi(a01), w[20 + k], bf_lo(a01) * w[16 + k])));
    return make_uint2(hadd_bf2(mv.x, hmul_bf2(pack_bf2(uu[0], uu[1]), h[0])), hadd_bf2(mv.y, hmul_bf2(pack_bf2(uu[2], uu[3]), h[2])));
}
__device__ __forceinline__ void mma16(float (&c)[4], const uint32_t (&a)[4], uint32_t b0, uint32_t b1) {
    asm volatile("mma.sync.aligned.m16n8k16.row.col.f32.bf16.bf16.f32 {%0,%1,%2,%3}, {%4,%5,%6,%7}, {%8,%9}, {%0,%1,%2,%3};"
                 : "+f"(c[0]), "+f"(c[1]), "+f"(c[2]), "+f"(c[3]) : "r"(a[0]), "r"(a[1]), "r"(a[2]), "r"(a[3]), "r"(b0), "r"(b1));
}
__device__ __forceinline__ void finish_rows(const Params& p, uint32_t sb, bool s1) {
    int tid;
    bool wet = !DRY2;
    {
        asm volatile("mov.u32 %0, %%tid.x;" : "=r"(tid));
        const int lane = tid & 31;
        if (s1) mbar_wait(sb + B_INIT, 0); else if (lane == 0) mbar_arrive(sb + B_TFREE);
#pragma unroll 1
        for (bool own = s1;; own = false, wet = true) {
            asm volatile("mov.u32 %0, %%tid.x;" : "=r"(tid));
            uint32_t item = tid >> 5;
            if (!own) item = tid & 31 ? 0u : atoms_add<W_ITEM>(sb, 1u);
            item = __reduce_max_sync(0xffffffffu, item);
            if (item >= 3 * NS1) break;
            const int kb = item / NS1 * NG0 + item % NS1 * 8, q = (lds32(sb + W_ROLE) * p.R2 >> 1) + kb + (tid >> 2 & 7) + (tid & 3) * NS1 * 8;
            uint32_t ds[NTILE / 4];
            TKY(7)
#pragma unroll
            for (int j = 0; j < NTILE / 4; j++) ds[j] = ld_in(reinterpret_cast<const uint32_t*>(p.dist) + min(q + j * NS1 * 32, (p.E >> 1) - 1));
            const uint2 wc = lds64<OFF_WG>(sb + (tid & 31) * 8);
            const uint32_t wb = wc.x, cen = wc.y;
            TKZ(4, (ds[0] ^ ds[1] ^ ds[2] ^ ds[3] ^ wb ^ cen))
            uint2 v[NTILE];
#pragma unroll 1
            for (int t = 0; t < NTILE; t += GU) {
#pragma unroll
            for (int i = 0; i < NTILE - GU; i++) v[i] = v[i + GU];
#pragma unroll
            for (int i = 0; i < GU; i++) {
                const uint32_t x = __shfl_sync(0xffffffffu, ds[i >> 2], i & 3, 4);
                uint32_t rb[2];
#pragma unroll
                for (int u = 0; u < 2; u++) {
                    const uint32_t df = hsub_bf2(__byte_perm(x, 0u, u ? 0x3232 : 0x1010), cen);
                    const uint32_t ar = hmul_bf2(hmul_bf2(df, df), 0xc120c120u);
                    rb[u] = pack_bf2(exp_fast(bf_lo(ar)), exp_fast(bf_hi(ar)));
                }
                float c[4];
                asm volatile("mma.sync.aligned.m16n8k8.row.col.f32.bf16.bf16.f32 {%0,%1,%2,%3}, {%4,%5}, {%6}, {%7,%7,%7,%7};"
                             : "=f"(c[0]), "=f"(c[1]), "=f"(c[2]), "=f"(c[3]) : "r"(rb[0]), "r"(rb[1]), "r"(wb), "f"(0.f));
                v[NTILE - GU + i] = make_uint2(pack_bf2(c[0], c[1]), pack_bf2(c[2], c[3]));
            }
#pragma unroll
            for (int j = 0; j < (NTILE - GU) / 4; j++) ds[j] = ds[j + GU / 4];
            }
            TKZ(5, (v[15].x ^ v[9].y))
            if (own) bar_sync(BAR_H1, (NS1 + 1) * 32); else mbar_wait(sb + B_TFREE, 0);
            asm volatile("mov.u32 %0, %%tid.x;" : "=r"(tid));
            const int k0 = kb + (tid >> 2 & 7);
            const uint32_t a = sb + (tid & 2 ? gate_h(k0) : gate_g(k0)) + (tid & 1) * 8;
#pragma unroll
            for (int i = 0; i < NTILE; i++) if (i < NTILE - 1 || k0 + i * NS1 * 8 < R2MAX / 2) sts64(a + i * NS1 * 8 * 16, v[i].x, v[i].y);
            static_assert(2 * NG0 + (NTILE - 1) * NS1 * 8 <= R2MAX / 2, "gates");
            TKY(1)
        }
    }
    asm volatile("mov.u32 %0, %%tid.x;" : "=r"(tid));
    const int role = lds32(sb + W_ROLE), row0 = role * p.R2, np = min(p.R2, p.E - row0) >> 1, lane = tid & 31;
    uint4 wd = make_uint4(0u, 0u, 0u, 0u), wu = wd;
    if ((lane & 3) == lane >> 3) { wd = lds128(sb + OFF_WB + (lane & 4) * 8); wu = lds128(sb + OFF_WB + 16 + (lane & 4) * 8); }
    const uint32_t wb[8] = {wd.x, wd.y, wd.z, wd.w, wu.x, wu.y, wu.z, wu.w};
    const uint32_t k0 = (lds32(sb + W_UNIT) >> 16) * 0x10001u + 0x03800380u;
    uint8_t* dirty = g_dirty + role * DROW + tid * 2;
    auto flags = [&](uint32_t on) {
        uint32_t f[NPAIR], m = 0;
#pragma unroll
        for (int i = 0; i < NPAIR; i++) asm volatile("{ .reg .pred q; setp.ne.u32 q, %2, 0; mov.u32 %0, 0; @q ld.relaxed.gpu.global.u16 %0, [%1]; }" : "=r"(f[i]) : "l"(dirty + i * NE * 64), "r"(on) : "memory");
#pragma unroll
        for (int i = 0; i < NPAIR; i++) m |= ((f[i] | f[i] >> 7) & 3u) << 2 * i;
        return m;
    };
    auto row_of = [&](int j) { return 2 * tid + (j >> 1) * NE * 64 + (j & 1); };
    uint32_t kept, left = 0, bad = 0, at;
#pragma unroll 1
    for (;; wet = true) {
    if (wet) mbar_wait(sb + B_FLAG, 0);
    TKY(2)
    kept = flags(wet);
    at = __popc(kept);
    TKZ(3, kept)
#pragma unroll
    for (int i = 1; i < 32; i *= 2) { const uint32_t t = __shfl_up_sync(0xffffffffu, at, i); if (lane >= i) at += t; }
    const uint32_t n = __shfl_sync(0xffffffffu, at, 31);
    if (n || !wet) {
        uint32_t q = 0;
        if (lane == 0) q = atoms_add<W_NLIST>(sb, n);
        q = __shfl_sync(0xffffffffu, q, 0);
        if (q + n > NG0) { sts32(sb + W_WRAP, 1u); kept = 0; }
        else {
            q = sb + OFF_LIST + q * 16;
            at = q + (at - __popc(kept)) * 16;
            uint32_t to = at;
            uint32_t m = kept;
#pragma unroll 1
            do {
                if (m) sts32(to, row_of(__ffs(m) - 1));
                m &= m - 1; to += 16;
            } while (m);
            __syncwarp();
            to = q + lane * 16;
#pragma unroll 1
            do {
                const bool on = to < q + n * 16;
                float4 o = make_float4(0.f, 0.f, 0.f, 0.f);
                asm volatile("{ .reg .pred q; setp.ne.u32 q, %5, 0; @q ld.relaxed.gpu.global.v4.f32 {%0,%1,%2,%3}, [%4]; }"
                             : "+f"(o.x), "+f"(o.y), "+f"(o.z), "+f"(o.w) : "l"(&g_ovf[role * RPAD + lds32(to)]), "r"((uint32_t)on) : "memory");
                const float4* w = reinterpret_cast<const float4*>(smem + OFF_WSM);
                const uint4 v = make_uint4(__float_as_uint(fmaf(o.w, w[3].x, fmaf(o.z, w[2].x, fmaf(o.y, w[1].x, o.x * w[0].x)))),
                                           __float_as_uint(fmaf(o.w, w[3].y, fmaf(o.z, w[2].y, fmaf(o.y, w[1].y, o.x * w[0].y)))),
                                           __float_as_uint(fmaf(o.w, w[3].z, fmaf(o.z, w[2].z, fmaf(o.y, w[1].z, o.x * w[0].z)))),
                                           __float_as_uint(fmaf(o.w, w[3].w, fmaf(o.z, w[2].w, fmaf(o.y, w[1].w, o.x * w[0].w)))));
                if (on) sts128<0>(to, v);
                to += 512;
            } while (to < q + n * 16);
        }
    }
    TKY(6)
    if (wet) {
        mbar_wait(sb + B_ROWS, 0);
        TKX(5)
        bar_sync(BAR_ACC, (NE + NC) * 32);
    }
    const int lim = wet ? np : 0;
    uint32_t from = at, bit = wet ? 1u : 1u << (2 * NPAIR - 2);
    uint4* out = reinterpret_cast<uint4*>(p.out + row0) + tid;
constexpr int FU = FUNR;
#pragma unroll FU
    for (int k = tid; bit < 1u << 2 * NPAIR; k += NE * 32, bit *= 4, out += NE * 32) {
        const uint4 ac = lds128(sb + OFF_ACC + k * 16), g = lds128(sb + gate_g(k)), h = lds128(sb + gate_h(k));
        const uint4 mv = lds128(sb + (row0 * 8 & 127) + k * 16 + (k < NG0 ? 0 : k < 2 * NG0 ? 0x10000 - NG0 * 16 : 0x30000 - NG0 * 32));
        const uint32_t u[4] = {ac.x + BIAS, ac.z + BIAS, ac.y + BIAS, ac.w + BIAS};
        uint32_t a[4];
        float c[4] = {0.f, 0.f, 0.f, 0.f}, d[4] = {0.f, 0.f, 0.f, 0.f};
#pragma unroll
        for (int j = 0; j < 2; j++)
            asm volatile("{ .reg .pred q; setp.ne.u32 q, %5, 0; @q ld.shared.v2.f32 {%0,%1}, [%4]; @q ld.shared.v2.f32 {%2,%3}, [%4+8]; @q add.u32 %4, %4, 16; }"
                         : "+f"(c[2 * j]), "+f"(c[2 * j + 1]), "+f"(d[2 * j]), "+f"(d[2 * j + 1]), "+r"(from) : "r"(kept & bit << j) : "memory");
#pragma unroll
        for (int j = 0; j < 4; j++) a[j] = hsub_bf2(and_or<0x007f007fu>(u[j] >> 9, k0 + 0x04800480u), k0 + 0x04c004c0u);
        mma16(c, a, wb[0], wb[1]); mma16(d, a, wb[2], wb[3]);
#pragma unroll
        for (int j = 0; j < 4; j++) a[j] = and_or<0x007f007fu>(u[j] >> 2, k0 + 0x01000100u);
        mma16(c, a, wb[0], wb[1]); mma16(d, a, wb[2], wb[3]);
#pragma unroll
        for (int j = 0; j < 4; j++) a[j] = and_or<0x00030003u>(u[j], k0);
        mma16(c, a, wb[0], wb[1]); mma16(d, a, wb[2], wb[3]);
        a[0] = hmul_bf2(pack_bf2(c[0], c[1]), g.x); a[1] = hmul_bf2(pack_bf2(c[2], c[3]), g.y);
        a[2] = hmul_bf2(pack_bf2(d[0], d[1]), g.z); a[3] = hmul_bf2(pack_bf2(d[2], d[3]), g.w);
#pragma unroll
        for (int j = 0; j < 4; j++) c[j] = d[j] = 0.f;
        mma16(c, a, wb[4], wb[5]); mma16(d, a, wb[6], wb[7]);
        if (k < lim) {
            *out = make_uint4(hadd_bf2(mv.x, hmul_bf2(pack_bf2(c[0], c[1]), h.x)), hadd_bf2(mv.y, hmul_bf2(pack_bf2(d[0], d[1]), h.z)),
                              hadd_bf2(mv.z, hmul_bf2(pack_bf2(c[2], c[3]), h.y)), hadd_bf2(mv.w, hmul_bf2(pack_bf2(d[2], d[3]), h.w)));
            if (c[0] != c[0] || c[2] != c[2]) bad |= 3u * bit;
        }
    }
    if (wet) break;
    }
    const bool wrap = lds32(sb + W_WRAP);
    if (RARE(wrap)) { left = flags(1u); kept = 0; }
#pragma unroll 1
    for (uint32_t m = left | bad; RARE(m); m &= m - 1) {
        const int j = __ffs(m) - 1, row = row_of(j);
        uint4 v = make_uint4(0u, 0u, 0u, 0u);
        if (kept >> j & 1u) v = lds128(at + __popc(kept & ((1u << j) - 1u)) * 16);
        p.out[row0 + row] = out_row(row, take(&g_ovf[role * RPAD + row], left >> j & 1u),
                                    make_float4(__uint_as_float(v.x), __uint_as_float(v.y), __uint_as_float(v.z), __uint_as_float(v.w)), p.m[row0 + row]);
        if (wrap) g_dirty[role * DROW + row] = 0;
    }
}

template <int HOP> __device__ __forceinline__ uint2 null_rec(int lane, uint32_t R) {
    if (HOP == 1) return make_uint2(0x800000u | H<1>::tag(R), (OFF_CNT1 - OFF_M) / 8);
    return make_uint2(0x08000800u | lane << 28, 0x0fff0000u | H<2>::tag(R));
}
template <int HOP> __device__ __forceinline__ void fill(uint32_t win, int ct, uint32_t R) {
    const uint2 v = null_rec<HOP>(ct, R);
#pragma unroll
    for (int i = 0; i < WIN / (NC * 512); i++) sts128<0>(win + ct * 16 + i * NC * 512, make_uint4(v.x, v.y, v.x, v.y));
}
template <int HOP> __device__ __forceinline__ void reset(uint32_t win, int lane, uint32_t R) {
    const uint2 v = null_rec<HOP>(lane, R);
    const uint32_t a = win + lane * 32 + H<HOP>::mark(R, lane >> 2) * 8;
#pragma unroll
    for (int i = 0; i < 16; i++) sts64(a + i * 1024, v.x, v.y);
    if (lane < 16) sts64(a + 16384, v.x, v.y);
}
__device__ __forceinline__ bool elect() {
    uint32_t q; asm volatile("{ .reg .pred q; elect.sync _|q, 0xffffffff; selp.u32 %0, 1, 0, q; }" : "=r"(q)); return q;
}
__device__ __forceinline__ const unsigned char* mk_ptr(uint32_t lo, uint32_t hi) { return reinterpret_cast<const unsigned char*>((uint64_t)hi << 32 | lo); }
__device__ __forceinline__ void bulk_store(uint32_t lo, uint32_t hi, uint32_t src, uint32_t n) {
    asm volatile("cp.async.bulk.global.shared::cta.bulk_group [%0], [%1], %2;" ::"l"(mk_ptr(lo, hi)), "r"(src), "r"(n) : "memory");
}
template <int HOP>
__device__ __forceinline__ void manager(const Params& p, uint32_t sb, int lane, int role, uint32_t base) {
    typedef H<HOP> h;
    constexpr int SMP = HOP == 1 ? SMP1 : SMP2;
    constexpr int V = h::NBIN / 32, PB = h::S * 8;
    const int RT = p.rounds + HOP - 1, lo = HOP == 1 && role >= NG ? NG : 0, hi = lo + h::NBIN;
    const int w = (role - lo) / (HOP * J), j = (role - lo - w * HOP * J) / HOP;
    const Ring rg(p.ring, __reduce_or_sync(0xffffffffu, lds32(sb + W_PAR)), 2 * w + HOP - 1);
    const uint32_t side = lds32(sb + W_SIDE), dhi = rg.main >> 32, mhi = rg.mid >> 32;
    const uint32_t c0 = HOP == 2 ? role & 1 : 0, up = (HOP == 1 && lo) ^ rg.par ^ c0;
    uint32_t dA = ((uint32_t)rg.main + src_off(j) + (c0 << 16) + (up ? 4096 : 12288)) ^ slot_off(base % 3);
    uint32_t dM = ((uint32_t)rg.mid + src_off(j) + c0 * 1024) ^ slot_off(base % 3);
    const int a0 = max(64, lo), b1 = min(68, hi);
    int n0 = (min(NHI, hi) - a0) * PB, a1 = (max(NLO, lo) - lo) * PB;
    const unsigned char* cr = reinterpret_cast<const unsigned char*>(rg.main) + MISC + ((side ^ rg.par) << 12);
    const unsigned char* cr0 = cr + cred_off(lo + lane * V), *cr1 = cr + cred_off(lo + 32 * V + min(lane, V - 1));
    const uint32_t ca0 = sb + h::CNT + lane * V * 4, ca1 = sb + h::CNT + (32 * V + min(lane, V + NDUM)) * 4;
    const uint32_t rot0 = (lane * V & 7) * 16, rot1 = lane * 16;
    uint32_t st = slot_steps(base);
    uint32_t init = h::init(base), prim = sb + h::STG + (HOP == 1 ? h::win(base) : 0u);
    uint32_t cs[5] = {0, 0, 0, 0, 0};
    auto sample = [&]() {
        if (V == 2) asm volatile("ld.relaxed.gpu.global.v2.u32 {%0,%1}, [%2];" : "=r"(cs[0]), "=r"(cs[1]) : "l"(cr0) : "memory");
        else asm volatile("ld.relaxed.gpu.global.v4.u32 {%0,%1,%2,%3}, [%4];" : "=r"(cs[0]), "=r"(cs[1]), "=r"(cs[2]), "=r"(cs[3]) : "l"(cr0) : "memory");
        cs[V] = ld_rlx32(reinterpret_cast<const uint32_t*>(cr1));
    };
    uint32_t low[5] = {rot0, rot0 + 16, rot0 + 32, rot0 + 48, rot1};
    TK_DECL
#pragma unroll 1
    for (int r = 0;; r++) {
        const uint32_t R = base + r, ninit = h::init(R + 1), done = prim;
        TK(5)
        mbar_wait(sb + B_FULL + (HOP - 1) * 8, r & 1);
        TK(0)
        if (SMP == 1) sample();
        uint32_t c[5];
        if (V == 2) asm volatile("ld.shared.v2.u32 {%0,%1}, [%2];" : "=r"(c[0]), "=r"(c[1]) : "r"(ca0) : "memory");
        else asm volatile("ld.shared.v4.u32 {%0,%1,%2,%3}, [%4];" : "=r"(c[0]), "=r"(c[1]), "=r"(c[2]), "=r"(c[3]) : "r"(ca0) : "memory");
        c[V] = lds32(ca1);
        uint32_t nc[5];
#pragma unroll
        for (int k = 0; k <= V; k++) {
            const uint32_t rot = k < V ? rot0 + k * 16 : rot1, z = ninit + (HOP == 1 ? rot : low[k]);
            if (HOP == 2) low[k] = min((max((int)(c[k] - low[k] - init - h::CAP * h::INC), 0) >> h::SH) * 128u + low[k], rot + BOXN * 128u);
            nc[k] = min(max(c[k] + (ninit - init - h::S * h::INC), z), (HOP == 1 ? z : ninit + low[k]) + (h::CAP - h::S) * h::INC);
        }
        if (V == 2) sts64(ca0, nc[0], nc[1]); else sts128<0>(ca0, make_uint4(nc[0], nc[1], nc[2], nc[3]));
        sts32(ca1, lane < V ? nc[V] : lane < V + NDUM ? DUMMY : r);
        __syncwarp();
        if (lane == 0) mbar_arrive(sb + B_OPEN + (HOP - 1) * 8);
        TK(1)
        TK(2)
        asm volatile("fence.proxy.async.shared::cta;" ::: "memory");
        TK(6)
        if (r >= D) {
            int it = 0;
            while (true) {
                uint32_t bad = 0;
#pragma unroll
                for (int k = 0; k <= V; k++) bad |= cs[k] - (R - D + 1);
                if (!__any_sync(0xffffffffu, bad >> 20)) break;
                if (++it > SPIN_LIMIT) __trap();
                if (it > 1) __nanosleep(100);
                sample();
            }
        }
        TK(3)
        if (SMP == 2) sample();
        if (elect()) {
            const uint32_t dB = (HOP == 1 ? dA ^ 0x10000u : dA) + (up ? 8192 : -8192), sm = prim + (lo ? 2 * PB : 0);
            bulk_store(dA, dhi, sm, 8192);
            bulk_store(dB, dhi, HOP == 1 ? sm + 8192 : prim + 68 * PB, 8192);
            if (n0 > 0) bulk_store(dM + (a0 - 64) * PB, mhi, prim + (a0 - lo) * PB, n0);
            if (a1 < (b1 - lo) * PB) bulk_store((dM ^ 4096u) + (uint32_t)((lo - NLO) * PB + a1), mhi, prim + a1, (b1 - lo) * PB - a1);
            asm volatile("cp.async.bulk.commit_group;" ::: "memory");
            if (r != RT - 1) asm volatile("cp.async.bulk.wait_group.read 0;" ::: "memory");
        }
        __syncwarp();
        TK(4)
        prim = HOP == 1 ? prim ^ 0x20000u : prim >= sb + 0x30000u ? sb : prim + (prim - sb) + 0x10000u;
        if (r == RT - 1) break;
        if (SMP == 3) sample();
        reset<HOP>(done, lane, R + HOP + 1);
        if (HOP == 1) {
            __syncwarp();
            if (lane == 0) mbar_arrive(sb + B_FREE);
        }
        if (RARE(r == RSPLIT || r == RT - D - 1)) {
            uint32_t n = NHI, m = NLO;
            if (HOP == PFH && r == RT - D - 1 && lane < 2) {
                const int row0 = role * p.R2, nr = min(p.R2, p.E - row0) & ~7;
                const uint64_t a = lane ? reinterpret_cast<uint64_t>(p.dist + row0) + 15 & ~15ull : reinterpret_cast<uint64_t>(p.m + row0);
                if (nr > 8) asm volatile("cp.async.bulk.prefetch.L2.global [%0], %1;" ::"l"(a), "r"(lane ? nr * 2 - 16 : nr * 8) : "memory");
            }
            if (r < RT - D - 1) {
                int it = 0;
                while (true) {
                    n = ld_rlx32(reinterpret_cast<const uint32_t*>(p.ring + M_CNT + (side << 12)));
                    if ((n & 0xffffu) + (n >> 16) == NB) break;
                    if (++it > SPIN_LIMIT) __trap();
                }
                m = n = min(max(__reduce_or_sync(0xffffffffu, n) & 0xffffu, (uint32_t)NLO), (uint32_t)NHI);
            }
            n0 = (min((int)n, hi) - a0) * PB;
            a1 = (max((int)m, lo) - lo) * PB;
        }
        if (HOP == 2 && RARE(r == RT - LATE)) fence_gpu();
        if (SMP == 0) sample();
        slot_next(dA, st); slot_next(dM, st);
        st = slot_rot(st);
        init = ninit;
    }
    TK_OUT
}

#define POLL_NS 200
#define POLL_NS3 400
template <int HOP> struct Reader {
    uint32_t lo, hi, st, line;
    uint32_t* cred;
    __device__ __forceinline__ void init(const Params& p, uint32_t sb, int w, int lane, int role, uint32_t base) {
        constexpr int PB = H<HOP>::S * 8;
        const int first = HOP == 1 ? (role >= NG ? NG : 0) + w * J : w * 2 * J;
        const Ring rg(p.ring, lds32(sb + W_PAR), 2 * w + HOP - 1);
        const uint32_t side = lds32(sb + W_SIDE);
        const bool mid = side ? role < 68 : role >= 64;
        const uint32_t i = role - (side ? (mid ? NLO : 68) : (mid ? 64 : 0));
        const uint32_t c = HOP == 1 ? i >> 5 : lane >> 3 & 1, in = (HOP == 1 ? (i & 31) * PB + (lane & 15) * 16 : i * PB + (lane & 7) * 16) + (lane >> 4) * src_off(3);
        lo = (in + (mid ? ((uint32_t)rg.mid ^ side << 12) + c * 1024 : (uint32_t)rg.main + (c << 16) + (side ^ rg.par ^ c ? 4096 : 12288))) ^ slot_off(base % 3);
        hi = __reduce_or_sync(0xffffffffu, (uint32_t)((mid ? rg.mid : rg.main) >> 32));
        st = slot_steps(base);
        line = opaque((HOP == 1 ? 2 * (role % NG) + (lane >> 3 & 1) : role) + (lane & 1) * 2);
        const bool both = first >= NLO && first < NHI;
        cred = lane < 1 + both ? reinterpret_cast<uint32_t*>(rg.main + MISC + (((both ? lane : first >= NG) ^ rg.par) << 12) + cred_off(role)) : nullptr;
    }
    template <int K> __device__ __forceinline__ void load1(uint2 (&v)[J]) const {
        asm volatile("ld.relaxed.gpu.global.v4.u32 {%0,%1,%2,%3}, [%4+%5];" : "=r"(v[2 * K].x), "=r"(v[2 * K].y), "=r"(v[2 * K + 1].x), "=r"(v[2 * K + 1].y)
                     : "l"(mk_ptr(lo, hi)), "n"(src_off(K)) : "memory");
    }
    static __device__ __forceinline__ uint32_t word(const uint2& v) { return HOP == 1 ? v.x : v.y; }
    template <int K> __device__ __forceinline__ void again(uint2 (&v)[J], uint32_t want, uint32_t m0, uint32_t m1, uint32_t grp) const {
        if (__ballot_sync(0xffffffffu, ((word(v[2 * K]) ^ want) & m0) | ((word(v[2 * K + 1]) ^ want) & m1)) & grp) load1<K>(v);
    }
    __device__ __forceinline__ void load(uint2 (&rec)[J]) const { load1<0>(rec); load1<1>(rec); load1<2>(rec); }
    __device__ __forceinline__ void check(uint2 (&rec)[J], uint32_t R, uint32_t ns, int lane TK_ARG) {
        const uint32_t want = H<HOP>::tag(R), mk = H<HOP>::mark(R, line);
        const uint32_t m0 = mk == 0 ? H<HOP>::TAG : 0u, m1 = mk == 1 ? H<HOP>::TAG : 0u;
        int it = 0;
        while (true) {
            uint32_t b0 = 0, b1 = 0;
#pragma unroll
            for (int j = 0; j < J; j += 2) { b0 |= word(rec[j]) ^ want; b1 |= word(rec[j + 1]) ^ want; }
            if (!__any_sync(0xffffffffu, (b0 & m0) | (b1 & m1))) break;
            if (++it > SPIN_LIMIT) __trap();
            __nanosleep(ns);
            TK_CNT(7)
            const uint32_t grp = 0xffu << (lane & 24u);
            again<0>(rec, want, m0, m1, grp); again<1>(rec, want, m0, m1, grp); again<2>(rec, want, m0, m1, grp);
        }
        if (cred) st_rlx32(cred, R + 1);
        __syncwarp();
        slot_next(lo, st);
        st = slot_rot(st);
    }
    __device__ __forceinline__ void finish() const { if (cred) st_rlx32(cred, 0u); }
};

#define NPROBE 2
__device__ __forceinline__ uint32_t probe(unsigned char* a, uint32_t zero) {
    *reinterpret_cast<uint4*>(a) = make_uint4(0u, 0u, 0u, 0u);
    *reinterpret_cast<uint4*>(a + 16) = make_uint4(0u, 0u, 0u, 0u);
    uint32_t best = ~0u, v = threadIdx.x, prev = 0;
#pragma unroll
    for (int t = 0; t <= NPROBE + 1; t++) {
        uint32_t now;
        if (t <= NPROBE) asm volatile("atom.relaxed.gpu.global.add.u32 %0, [%1], 1;" : "=r"(v) : "l"(a + (v & zero)) : "memory");
        else asm volatile("red.relaxed.gpu.global.add.u32 [%0], 1;" ::"l"(a + (v & zero)) : "memory");
        asm volatile("mov.u32 %0, %%clock;" : "=r"(now) :: "memory");
        if (t > 1) best = min(best, now - prev);
        prev = now;
    }
    return best;
}
template <bool B> struct BoolC { static constexpr bool value = B; };

__device__ __forceinline__ void stage1(const Params& p, uint32_t sb, const int pos0, int lane, const bool half) {
    typedef H<1> h;
    constexpr int NP = 4;
    static_assert(NPR == NS1 * NP * 32 - NP * 16, "tiles");
    const int RT = p.rounds;
    uint32_t ff = *reinterpret_cast<const uint16_t*>(p.ang_freq) * 0x10001u;
    auto pair_of = [&](int r, int pos) {
        const int q = r < RT - 1 ? (r * NB + blockIdx.x) * NPR + pos : (RT - 1) * NB * NPR + blockIdx.x * p.lastn + pos;
        return pos < (r < RT - 1 ? NPR : r == RT - 1 ? p.lastn : 0) && q < p.T2 ? q : -1;
    };
    uint2 vi[NP], vo[NP]; uint32_t va[NP];
    auto load_edge = [&](int r) {
#pragma unroll
        for (int u = 0; u < NP; u++) {
            const int q = max(pair_of(r, pos0 + u * 32), 0);
            vi[u] = ld_in(p.idx_in + q); vo[u] = ld_in(p.idx_out + q); va[u] = ld_in(p.angle + q);
        }
    };
    if (TEX0 && p.full) {
#pragma unroll
        for (int u = 0; u < NP; u += 2) {
            const int k = ((blockIdx.x * NPR + pos0 + lane) >> 1) + (!u ? 0 : half ? 0x40000000 : 32);
            tex2(p.ta, k, va[u], va[u + 1]); tex4(p.to, k, vo[u], vo[u + 1]); tex4(p.ti, k, vi[u], vi[u + 1]);
        }
    } else load_edge(0);
    if (blockIdx.x == 0 && pos0 == 0 && (p.T & 1)) {
        const int t = p.T - 1;
        slow_triplet(p, reinterpret_cast<const uint32_t*>(p.idx_in)[t], reinterpret_cast<const uint32_t*>(p.idx_out)[t],
                     bf16r(cos_bf(hmul_bf2(reinterpret_cast<const uint16_t*>(p.angle)[t], ff) & 0xffffu)));
    }
    ff = __reduce_or_sync(0xffffffffu, ff);
    bar_sync(BAR_S1, (NS1 + NC) * 32);
    uint32_t R = __reduce_or_sync(0xffffffffu, lds32(sb + W_BASE) & 31u);
    TK_DECL
    auto step = [&](const int r, const int qn, auto edge) {
        constexpr bool EDGE = decltype(edge)::value;
        uint32_t cc[NP], big = 0;
#pragma unroll
        for (int u = 0; u < NP; u++) {
            va[u] = hmul_bf2(va[u], ff);
            cc[u] = pack_bf2(__cosf(bf_lo(va[u])), __cosf(bf_hi(va[u])));
            big |= hmul_bf2(va[u], 0x3d003d00u);
        }
        if (RARE(big & 0x40004000u)) {
#pragma unroll 1
            for (int u = 0; u < NP; u++) {
                const uint32_t a = pick(u, va);
                float c0 = cos_bf(a & 0xffffu), c1 = cos_bf(a >> 16);
                if ((c0 != c0 || c1 != c1) && (EDGE ? pair_of(r, pos0 + u * 32) >= 0 : !half || u < 2)) {
                    const uint2 i2 = pick(u, vi), o2 = pick(u, vo);
                    if (c0 != c0) slow_triplet(p, i2.x, o2.x, c0);
                    if (c1 != c1) slow_triplet(p, i2.y, o2.y, c1);
                }
                const uint32_t v = pack_bf2(c0 != c0 ? 0.f : c0, c1 != c1 ? 0.f : c1);
#pragma unroll
                for (int k = 0; k < NP; k++) if (k == u) cc[k] = v;
            }
        }
        uint32_t bin[2 * NP], x[2 * NP], y[2 * NP];
        uint32_t dep = 0;
        auto loads = [&]() {
            const int q = qn + (dep & p.zero);
#pragma unroll
            for (int u = 0; u < NP; u += 2) {
                const int k = !u ? q : q + (half ? 0x40000000 : 32);
                tex2(p.ta, k, va[u], va[u + 1]); tex4(p.to, k, vo[u], vo[u + 1]); tex4(p.ti, k, vi[u], vi[u + 1]);
            }
        };
#pragma unroll
        for (int j = 0; j < 2 * NP; j++) {
            const uint32_t ii = j & 1 ? vi[j >> 1].y : vi[j >> 1].x, oo = j & 1 ? vo[j >> 1].y : vo[j >> 1].x;
            bin[j] = imul(ii, p.i1);
            y[j] = __byte_perm(ifma(bin[j], p.k1, ii), cc[j >> 1], j & 1 ? 0x7610 : 0x5410);
            const uint32_t bo = imul(oo, p.i2);
            x[j] = __byte_perm(ifma(bo, p.k2, imul(oo, 8.f)), bo, 0x0514);
            dep |= x[j] | y[j];
            if (EDGE && pair_of(r, pos0 + (j >> 1) * 32) < 0) bin[j] = NG + (lane & (NDUM - 1));
        }
        if (!EDGE) loads();
        else if (!LATEE) load_edge(r + 1);
        const uint32_t init = h::init(R), lim = init + ((EDGE && r == RT - 1 ? h::S : h::CAP) << h::SH);
        TKS(0)
        mbar_wait(sb + B_OPEN, ~R & 1);
        TKS(1)
        bool freed = false;
        uint32_t over = 0;
#pragma unroll
        for (int g = 0; g < 2 * NP; g += NP) if (!g || EDGE || !half) {
            constexpr int G = NP;
            uint32_t ret[G];
            int mx = 0;
#pragma unroll
            for (int j = 0; j < G; j++) ret[j] = atoms_add<h::CNT>(sb + imul(bin[g + j], 4.f), h::INC);
#pragma unroll
            for (int j = 0; j < G; j++) mx = j ? max(mx, (int)ret[j]) : (int)ret[j];
            if (!freed && __any_sync(0xffffffffu, mx >= (int)(init + 0x10000u))) { TKS(2) mbar_wait(sb + B_FREE, ~R & 1); freed = true; TKS(3) }
            TKS(2)
#pragma unroll
            for (int j = 0; j < G; j++) {
                x[g + j] = and_or<h::TAG>(ret[j], x[g + j]);
                put_rec<h::STG>(ret[j], lim, sb + and_or<0x20000u | h::PM>(ret[j], imul(bin[g + j], 256.f)), x[g + j], y[g + j]);
            }
            if (RARE(mx >= (int)lim)) {
#pragma unroll
                for (int j = 0; j < G; j++) if ((int)ret[j] >= (int)lim) over |= 1u << (g + j);
            }
        }
        __syncwarp();
        if (elect()) mbar_arrive(sb + B_FULL);
        R++;
        TKS(4)
#pragma unroll 1
        while (RARE(over)) {
            TK_CNT(7)
            const int j = __ffs(over) - 1;
            over &= over - 1;
            slow_rec1(p, pick(j, x), pick(j, y), pick(j, bin));
        }
        __syncwarp();
        if (LATEE && EDGE && r < RT - 1) load_edge(r + 1);
    };
#pragma unroll 1
    for (int q = opaque(((NB + blockIdx.x) * NPR + pos0 + lane) >> 1), r = 1; r < p.full; r++, q += NB * NPR / 2) step(r - 1, q, BoolC<false>());
#pragma unroll 1
    for (int r = max(p.full - 1, 0); r < RT; r++) step(r, 0, BoolC<true>());
    TK_OUT
}

__device__ __forceinline__ void stage2(const Params& p, uint32_t sb, int w, int lane, int role, uint32_t base1, uint32_t base) {
    typedef H<2> h;
    const int RT = p.rounds + 1;
    Reader<1> rd;
    rd.init(p, sb, w, lane, role, base1 + 3);
    uint2 rec[J];
#pragma unroll
    for (int j = 0; j < J; j++) rec[j] = null_rec<1>(lane, base1);
    uint32_t kb = sb + 0x10000u, am = 0x10000u | h::PM;
    const float unit = __uint_as_float(__reduce_or_sync(0xffffffffu, lds32(sb + W_UNIT)));
    TK_DECL
#pragma unroll 1
    for (int r = 0; r < RT; r++) {
        rd.check(rec, base1 + r, POLL_NS, lane TK_PASS);
        if (RARE(r == 1)) bar_sync(BAR_TABLE, 2 * NC * 32);
        const uint32_t want = H<1>::tag(base1 + r);
        TKS(0)
        uint2 mv[J];
#pragma unroll
        for (int j = 0; j < J; j++) {
            mv[j] = make_uint2(0u, 0u);
            const uint32_t a = sb + imul(rec[j].y & 0xffffu, 8.f);
            if (!xor_and<0x8e0000u>(rec[j].x, want)) mv[j] = lds64<OFF_M>(a);
        }
        uint32_t fl = 0;
#pragma unroll
        for (int j = 0; j < J; j++) fl |= mv[j].y;
        if (RARE(fl & 0x40000000u)) {
#pragma unroll 1
            for (int j = 0; j < J; j++) {
                const uint2 v = pick(j, mv), w = pick(j, rec);
                if ((v.y & 0x40000000u) && !((w.x ^ want) & 0x8e0000u)) {
                    if (v.x & 0x40000000u) slow_rec1(p, w.x, w.y, lds32(sb + W_ROLE) % NG);
                    else {
                        const float c = bf_hi(w.y), s = __uint_as_float(lds32(sb + W_UNIT)) * 1024.f;
                        side_add(w.x & 0xffu, __byte_perm(w.x, 0u, 0x4413) >> 3, c * (bf_lo(v.x) * s), c * (bf_hi(v.x) * s),
                                 c * (bf_lo(v.y) * s), c * (bf_hi(v.y & 0xbfffffffu) * s));
                    }
                }
            }
#pragma unroll
            for (int j = 0; j < J; j++) if (mv[j].y & 0x40000000u) rec[j].x = 0x800000u;
        }
        uint32_t w0[J], w1[J], bin[J], ret[J];
#pragma unroll
        for (int j = 0; j < J; j++) {
            const float c = bf_hi(rec[j].y), MG = 8194.0f;
            const uint32_t x = rec[j].x;
            const float v[4] = {bf_lo(mv[j].x), bf_hi(mv[j].x), bf_lo(mv[j].y), bf_hi(mv[j].y)};
            w0[j] = and_or<0xf000f000u>(x, __byte_perm(__float_as_uint(fmaf(c, v[0], MG)), __float_as_uint(fmaf(c, v[1], MG)), 0x5410));
            w1[j] = and_or<0xf000f000u>(x << 4, __byte_perm(__float_as_uint(fmaf(c, v[2], MG)), __float_as_uint(fmaf(c, v[3], MG)), 0x5410));
            bin[j] = min(xor_and<0x8e00ffu>(x, want), NB + (lane & (NDUM - 1)));
        }
        const uint32_t lim = h::init(base + r) + (r == RT - 1 ? 0x10000u : 0x20000u);
        rd.load(rec);
        TKS(1)
        mbar_wait(sb + B_OPEN + 8, (r - 1) & 1);
        TKS(2)
#pragma unroll
        for (int j = 0; j < J; j++) ret[j] = atoms_add<h::CNT>(sb + imul(bin[j], 4.f), h::INC);
        uint32_t mx = 0;
#pragma unroll
        for (int j = 0; j < J; j++) {
            w1[j] = and_or<h::TAG>(ret[j], w1[j]);
            put_rec<0>(ret[j], lim, and_xor(ret[j], am, bin[j] * 128 + kb), w0[j], w1[j]);
            mx = __viaddmax_u32(ret[j], 0u - DUMMY, mx);
        }
        __syncwarp();
        if (lane == 0) mbar_arrive(sb + B_FULL + 8);
        TKS(3)
        if (RARE(mx >= lim - DUMMY)) {
            uint32_t over = 0;
#pragma unroll
            for (int j = 0; j < J; j++) if (ret[j] - DUMMY >= lim - DUMMY) over |= 1u << j;
#pragma unroll 1
            do {
                const int j = __ffs(over) - 1;
                over &= over - 1;
                const uint32_t b = pick(j, bin), v = pick(j, ret) - lim, e = v >> h::SH, at = ((v - e * h::INC - (b & 7u) * 16u - h::CAP * 8) >> 7) + e;
                if (max(at, e) < BOXN && r < RT - LATE) g_box[(b * NB + role) * BOX + at] = make_uint2(pick(j, w0), pick(j, w1) | h::TAG);
                else slow_rec2(p, pick(j, w0), pick(j, w1), b, unit);
            } while (over);
        }
        __syncwarp();
        am = am >= 0x30000u ? 0x10000u | h::PM : am + 0x10000u;
        kb ^= am & 0x30000u;
        TKS(4)
    }
    rd.finish();
    TK_OUT
}

__device__ __forceinline__ void add_recs(uint32_t sb, int lane, const uint2 (&rec)[J], uint32_t want) {
    const uint32_t t = 0u - (lane & 1u), k = (t & 1u << 26) - (want >> 4);
    uint32_t o0[J], o1[J], g = 0;
#pragma unroll
    for (int j = 0; j < J; j++) {
        o0[j] = 0; o1[j] = 0;
        if (xor_and<0x7fffffffu>(rec[j].y, want) < 0x0ffc0000u) {
            const uint32_t a = aux_of(rec[j].x, rec[j].y, k);
            const uint32_t v0 = (rec[j].x & 0x0fff0fffu) - 0x08000800u, v1 = (rec[j].y & 0x0fff0fffu) - 0x08000800u;
            o0[j] = atoms_add<OFF_ACC>(sb + a, mux(v0, v1, t));
            o1[j] = atoms_add<OFF_ACC>(sb + (a ^ 4u), mux(v1, v0, t));
        }
    }
#pragma unroll
    for (int j = 0; j < J; j++) g |= o0[j] | o1[j];
    if (RARE(__any_sync(0xffffffffu, g & 0x80008000u))) {
#pragma unroll 1
        for (int j = 0; j < J; j++) {
            const uint2 w = pick(j, rec);
            const uint32_t aux = aux_of(w.x, w.y), p0 = pick(j, o0), p1 = pick(j, o1);
            const float2 a = acc_fix(t ? p1 : p0, w.x & 0x0fff0fffu), b = acc_fix(t ? p0 : p1, w.y & 0x0fff0fffu);
            const float unit = __uint_as_float(lds32(sb + W_UNIT));
            if (xor_and<0x7fffffffu>(w.y, want) < 0x0ffc0000u && (a.x != 0.f || a.y != 0.f || b.x != 0.f || b.y != 0.f)) {
                side_add(lds32(sb + W_ROLE), aux >> 3, a.x * unit, a.y * unit, b.x * unit, b.y * unit);
                sts32(sb + W_WRAP, 1u);
            }
            __syncwarp();
        }
    }
}
__device__ __forceinline__ void stage3(const Params& p, uint32_t sb, int w, int lane, int role, uint32_t base) {
    const int RT = p.rounds + 1;
    Reader<2> rd;
    rd.init(p, sb, w, lane, role, base);
    uint2 rec[J];
    TK_DECL
#pragma unroll 1
    for (int r = 0; r < RT; r++) {
        rd.load(rec);
        rd.check(rec, base + r, r < RT - 2 ? POLL_NS3 : 100, lane TK_PASS);
        RTS((r & 127) == 41 && w == 0, 1 + (r >> 7))
        TK(0)
        add_recs(sb, lane, rec, H<2>::tag(base + r));
        TK(1)
        if (RARE((uint32_t)(r - (RT - LATE + 1)) < 2u)) {
            static_assert(BOX == 32, "box");
            float4* box = reinterpret_cast<float4*>(g_box) + (lds32(sb + W_ROLE) * NB + (w * 2 + r - (RT - LATE + 1)) * J) * (BOX / 2) + lane;
            TKY(0)
#pragma unroll
            for (int j = 0; j < J / 2; j++) {
                const float4 v = ld_rlx128f(box + j * 32);
                rec[2 * j] = make_uint2(__float_as_uint(v.x), __float_as_uint(v.y)); rec[2 * j + 1] = make_uint2(__float_as_uint(v.z), __float_as_uint(v.w));
            }
#pragma unroll
            for (int j = 0; j < J / 2; j++) if (rec[2 * j].x) box[j * 32] = make_float4(0.f, 0.f, 0.f, 0.f);
            add_recs(sb, lane, rec, H<2>::TAG);
            TKY(1)
        }
    }
    rd.finish();
    TK_OUT
}

__device__ __forceinline__ uint32_t row_max(uint32_t x, uint32_t y) {
    const uint32_t mx = __vmaxu2(x & 0x7fff7fffu, y & 0x7fff7fffu);
    return max(mx & 0xffffu, mx >> 16);
}
__device__ __forceinline__ uint32_t amax2(uint32_t a, uint32_t b) {
    uint32_t r; asm("max.NaN.xorsign.abs.bf16x2 %0, %1, %2;" : "=r"(r) : "r"(a), "r"(b)); return r;
}
constexpr int NTAB = 9, TABC = 2 * NC * 32 * 16;
__device__ __forceinline__ void load_piece(const Params& p, uint32_t sb, int role, int i) {
    const int r0 = (role >= NG ? role - NG : role) * p.R1, n = max(min(min(p.R1, p.E - r0) * 8 - i * TABC, TABC), 0);
    asm volatile("mbarrier.arrive.expect_tx.shared::cta.b64 _, [%0], %1;" ::"r"(sb + B_TAB + i * 8), "r"(n) : "memory");
    if (n) asm volatile("cp.async.bulk.shared::cluster.global.mbarrier::complete_tx::bytes [%0], [%1], %2, [%3];"
                        ::"r"(sb + OFF_M + i * TABC), "l"(p.m + r0 + i * (TABC / 8)), "r"(n), "r"(sb + B_TAB + i * 8) : "memory");
}
static_assert(NTAB * TABC >= R1MAX * 8 && NTAB * TABC - TABC / 2 <= R1MAX * 8, "table");
constexpr int EWIN = 5;

__global__ void __launch_bounds__(NTHR, 1) fused_kernel(const Params p) {
    const int tid = threadIdx.x, lane = tid & 31;
    const int hw = __reduce_max_sync(0xffffffffu, tid >> 5);
    const uint32_t sb = __reduce_or_sync(0xffffffffu, (uint32_t)__cvta_generic_to_shared(smem));
    TKX(0)
    RTS(tid == 0, 0)
    uint32_t cta;
    asm volatile("mov.u32 %0, %%ctaid.x;" : "=r"(cta));
    if (hw != W_M1 && hw != W_M2) {
        const int job = hw < W_M1 ? hw : hw - 1;
        if (lane == 0 && job < 2 * NPAGE + 2)
            sts32(sb + OFF_PROBE + job * 4, probe(p.ring + (size_t)max(job / 2 - 1, 0) * PAGE + PROBE + (cta & 31) * 128 + (cta >> 5 & 3) * 16384 + (cta >> 7 << 20) +
                                                  ((job & 1) << 12 ^ (job < 2 ? 0x3000 : 0)), p.zero));
        if (job < 4) bar_arrive(BAR_SIDE, 5 * 32); else bar_arrive(BAR_PROBE, 27 * 32);
        TKX(1)
    }
    if (hw < NS1) {
        stage1(p, sb, hw * 128 + lane, lane, hw == NS1 - 1);
    } else if (hw == W_M1) {
        const uint32_t epoch = ld_rlx32(reinterpret_cast<const uint32_t*>(p.ring + M_BASE)) ^ 33u;
        if (lane == 0) {
            if (sb & 255u) __trap();
            mbar_init(sb + B_FULL, NS1); mbar_init(sb + B_OPEN, 1); mbar_init(sb + B_FREE, 1); mbar_init(sb + B_TFREE, NC); mbar_init(sb + B_FLAG, 32); mbar_init(sb + B_INIT, 1); sts32(sb + W_ITEM, NS1);
            for (int i = 0; i < NTAB; i++) mbar_init(sb + B_TAB + i * 8, 1);
            asm volatile("fence.proxy.async.shared::cta;" ::: "memory");
        }
        const uint32_t base = __reduce_or_sync(0xffffffffu, epoch) & 31u;
        if (lane == 0) { sts32(sb + W_BASE, epoch); sts64(sb + W_NLIST, 0u, 0u); }
        if (lane == 0 && (base & 1u)) { mbar_arrive(sb + B_OPEN); mbar_arrive(sb + B_FREE); }
        bar_arrive(BAR_BASE, (NC + 1) * 32);
        TKY(5)
        bar_sync(BAR_SIDE, 5 * 32);
        TKY(6)
        {
            const uint2 la = lds64<OFF_PROBE>(sb), lb = lds64<OFF_PROBE + 8>(sb);
            const uint32_t side = min(la.y, lb.y) < min(la.x, lb.x);
            uint32_t v = 0;
            if (lane == 0) {
                asm volatile("atom.relaxed.gpu.global.add.u32 %0, [%1], %2;" : "=r"(v) : "l"(p.ring + M_CNT), "r"(side ? 0x10000u : 1u) : "memory");
                asm volatile("red.relaxed.gpu.global.add.u32 [%0], %1;" ::"l"(p.ring + M_CNT + 4096), "r"(side ? 0x10000u : 1u) : "memory");
            }
            bar_sync(BAR_PROBE, 27 * 32);
            const uint2 l = lds64<OFF_PROBE + 8>(sb + min(lane, NPAGE - 1) * 8);
            const uint32_t mine = (__ballot_sync(0xffffffffu, (l.y < l.x) != side) & ~1u) | 0x80000000u;
            if (lane == 0) {
                uint32_t par;
                asm volatile("atom.relaxed.gpu.global.cas.b32 %0, [%1], 0, %2;" : "=r"(par) : "l"(p.ring + M_PAR), "r"(mine) : "memory");
                const uint32_t role = side ? NB - 1 - (v >> 16) : v & 0xffffu;
#pragma unroll 1
                for (int i = 0; i < AHEAD; i++) load_piece(p, sb, role, i);
                sts32(sb + W_ROLE, role); sts32(sb + W_SIDE, role < NLO ? 0u : role >= NHI ? 1u : side);
                sts32(sb + W_END, (epoch | 1023u) + 1u + (base + p.rounds) % 24u + ((epoch >> 5 & 31u) + p.rounds + 1) % 24u * 32u);
                sts32(sb + W_PAR, par ? par : mine);
            }
            TKX(2)
        }
        bar_arrive(BAR_PAR, (2 * NC + 2) * 32);
        manager<1>(p, sb, opaque(lane), __reduce_max_sync(0xffffffffu, lds32(sb + W_ROLE)), base);
        asm volatile("cp.async.bulk.wait_group 0;" ::: "memory");
        bar_arrive(BAR_H1, (NS1 + 1) * 32);
        TKX(4)
        {
            const int role = lds32(sb + W_ROLE);
#pragma unroll 1
            for (int i = lane * 16; i < DROW; i += NPF * 512) {
                float4 f[NPF];
#pragma unroll
                for (int u = 0; u < NPF; u++) f[u] = ld_rlx128f(reinterpret_cast<const float4*>(g_dirty + role * DROW + i + u * 512));
#pragma unroll
                for (int u = 0; u < NPF; u++) {
                    if (__float_as_uint(f[u].x) | __float_as_uint(f[u].y)) prefetch_l2(g_ovf + role * RPAD + i + u * 512);
                    if (__float_as_uint(f[u].z) | __float_as_uint(f[u].w)) prefetch_l2(g_ovf + role * RPAD + i + u * 512 + 8);
                }
            }
        }
        bar_sync(BAR_DONE, (NE + 1) * 32);
        TKY(0)
        const uint32_t flag = lds32(sb + W_END) >> 10 & 0xffffu;
        if (lane < 2) {
            fence_gpu();
            asm volatile("st.relaxed.gpu.global.u16 [%0], %1;" ::"l"(p.ring + M_FLAG + lane * 4096 + blockIdx.x * 2), "h"((uint16_t)flag) : "memory");
        }
        TKY(1)
        __syncwarp();
        bar_arrive(BAR_ROWS, 64);
        wait_flags(p, sb, lane, flag * 0x10001u);
        TKX(5)
        mbar_arrive(sb + B_FLAG);
        if (blockIdx.x == 0) {
            if (lane == 0) *reinterpret_cast<uint32_t*>(p.ring + M_BASE) = lds32(sb + W_END) ^ 33u;
            if (lane < 3) *reinterpret_cast<uint32_t*>(p.ring + (lane & 2 ? M_PAR : M_CNT + (lane & 1) * 4096)) = 0;
        }
    } else if (hw == W_M2) {
        uint2 sm[16];
#pragma unroll
        for (int i = 0; i < 8; i++) ld_in4(p.m + 2 * min((i * 8 + (lane >> 2)) * (p.E >> 7) + (lane & 3), (p.E >> 1) - 1), sm[2 * i], sm[2 * i + 1]);
        const float wd = __bfloat162float(lane & 16 ? p.w_up[lane & 15] : p.w_down[lane & 15]);
        const uint16_t* wg = reinterpret_cast<const uint16_t*>(lane & 16 ? p.w_rbf : p.w_sbf) + (lane & 3) * 8 + (lane >> 2 & 3);
        const uint16_t* cp = reinterpret_cast<const uint16_t*>(p.centers) + (lane & 3) * 2;
        const uint32_t w0 = __ldg(wg), w1 = __ldg(wg + 4), c0 = __ldg(cp), c1 = __ldg(cp + 1);
        if (lane == 0) { mbar_init(sb + B_FULL + 8, NC); mbar_init(sb + B_OPEN + 8, 1); mbar_init(sb + B_ROWS, 1); }
        sts128<OFF_HIST>(sb + lane * 16, make_uint4(0u, 0u, 0u, 0u)); sts128<OFF_HIST + 512>(sb + lane * 16, make_uint4(0u, 0u, 0u, 0u));
        __syncwarp();
#pragma unroll
        for (int i = 0; i < 16; i++) atoms_add<OFF_HIST>(sb + (row_max(sm[i].x, sm[i].y) >> 7) * 4, 1u);
        __syncwarp();
        uint32_t best = 0;
#pragma unroll 1
        for (int e = 11 + lane; e <= 230; e += 32) {
            uint32_t c = 0;
#pragma unroll
            for (int i = 0; i < EWIN; i++) c += lds32(sb + OFF_HIST + (e - i) * 4);
            best = max(best, c << 8 | (255 - e));
        }
        const uint32_t e = 255 - (__reduce_max_sync(0xffffffffu, best) & 255u);
        if (lane == 0) { sts32(sb + W_EXP, e); sts32(sb + W_UNIT, (e - 10) << 23); }
        reinterpret_cast<float*>(smem + OFF_WSM)[lane] = wd;
        const int wi = (lane & 4) * 4 + (lane & 1) * 8 + (lane & 2) + (lane >> 3 & 1);
        const uint32_t fr = __byte_perm(__float_as_uint(__shfl_sync(0xffffffffu, wd, wi)), __float_as_uint(__shfl_sync(0xffffffffu, wd, wi + 4)), 0x7632);
        if (lane < 16) sts32(sb + OFF_WB + lane * 4, fr);
        sts64(sb + OFF_WG + lane * 8, w0 | w1 << 16, c0 | c1 << 16);
        TKY(5)
        bar_sync(BAR_PAR, (2 * NC + 2) * 32);
        if (lane == 0) mbar_arrive(sb + B_INIT);
        manager<2>(p, sb, opaque(lane), __reduce_max_sync(0xffffffffu, lds32(sb + W_ROLE)), __reduce_or_sync(0xffffffffu, lds32(sb + W_BASE)) >> 5 & 31u);
        TKX(4)
        asm volatile("cp.async.bulk.wait_group.read 0;" ::: "memory");
        bar_sync(BAR_ROWS, 64);
        if (lane == 0) {
            const int row0 = lds32(sb + W_ROLE) * p.R2, np = min(p.R2, p.E - row0) >> 1, off = row0 * 8 & 127;
            asm volatile("mbarrier.arrive.expect_tx.shared::cta.b64 _, [%0], %1;" ::"r"(sb + B_ROWS), "r"(max(np, 0) * 16 + (max(np, 0) + NG0 - 1) / NG0 * off) : "memory");
#pragma unroll 1
            for (int k = 0; k < np; k += NG0)
                asm volatile("cp.async.bulk.shared::cluster.global.mbarrier::complete_tx::bytes [%0], [%1], %2, [%3];"
                             ::"r"(sb + H<2>::win(k / NG0)), "l"(p.m + (row0 - off / 8 + 2 * k)), "r"(min(np - k, NG0) * 16 + off), "r"(sb + B_ROWS) : "memory");
        }
        asm volatile("cp.async.bulk.wait_group 0;" ::: "memory");
    } else {
        const int w = __reduce_max_sync(0xffffffffu, hw < W_M1 ? hw - NS1 : hw - W_M1 - 1), ct = w * 32 + lane;
        if (hw < W_M1) {
            bar_sync(BAR_BASE, (NC + 1) * 32);
            const uint32_t b1 = lds32(sb + W_BASE) & 31u, b2 = lds32(sb + W_BASE) >> 5 & 31u;
            if (ct < NG + NDUM) sts32(sb + OFF_CNT1 + ct * 4, ct < NG ? H<1>::init(b1) + (ct & 7) * 16 : DUMMY);
            if (ct <= NB + NDUM) sts32(sb + OFF_CNT2 + ct * 4, ct < NB ? H<2>::init(b2) + (ct & 7) * 16 : DUMMY);
            fill<1>(sb + OFF_H1 + H<1>::win(b1), ct, b1); fill<1>(sb + OFF_H1 + H<1>::win(b1 + 1), ct, b1 + 1);
            bar_arrive(BAR_S1, (NS1 + NC) * 32);
#pragma unroll
            for (int i = 0; i < 3; i++) fill<2>(sb + H<2>::win(i), ct, b2 + i);
        }
        bar_sync(BAR_PAR, (2 * NC + 2) * 32);
        TKY(4)
        const int role = __reduce_max_sync(0xffffffffu, lds32(sb + W_ROLE));
        const uint32_t epoch = __reduce_or_sync(0xffffffffu, lds32(sb + W_BASE));
        if (hw < W_M1) {
            for (int i = ct; i < R2MAX / 2; i += NC * 32) reinterpret_cast<uint4*>(smem + OFF_ACC)[i] = make_uint4(0x40004000u, 0x40004000u, 0x40004000u, 0x40004000u);
            mbar_wait(sb + B_TAB + KDRY * 8, 0);
            stage2(p, sb, w, opaque(lane), role, (epoch & 31u) - 1u, epoch >> 5 & 31u);
        } else {
            const int e = lds32(sb + W_EXP);
            const uint32_t sc = (uint32_t)(254 - e) * 0x800080u, top = (e << 7 | 0x807fu) * 0x10001u;
            auto conv = [&](uint32_t& x, uint32_t& y) {
                const uint32_t mx = row_max(x, y);
                const int d = e - (int)(mx >> 7);
                x = hmul_bf2(x, sc); y = hmul_bf2(y, sc);
                if (d >= EWIN) y |= 0x40000000u;
                if (d < 0 || (d >= EWIN && e > 127)) { x = 0x40000000u; y = x; }
                if (mx == 0) { x = 0; y = 0; }
            };
#pragma unroll 1
            for (int i = 0; i < NTAB; i++) {
                mbar_wait(sb + B_TAB + i * 8, 0);
                if (ct == 0 && i < NTAB - AHEAD) load_piece(p, sb, role, i + AHEAD);
                const uint32_t t = sb + OFF_M + i * TABC + ct * 16, t1 = t + TABC / 2 < sb + OFF_M + R1MAX * 8 ? t + TABC / 2 : t;
                uint4 v[2] = {lds128(t), lds128(t1)};
                uint32_t ok = ~0u;
#pragma unroll
                for (int u = 0; u < 2; u++) {
                    const uint32_t a = amax2(v[u].x, v[u].y), b = amax2(v[u].z, v[u].w), mx = amax2(__byte_perm(a, b, 0x5410), __byte_perm(a, b, 0x7632)) & 0x7fff7fffu;
                    ok &= (top - mx) ^ (top - EWIN * 0x800080u - mx);
                }
                if (RARE(~ok & 0x80008000u)) {
#pragma unroll 1
                    for (int u = 0; u < 4; u++) {
                        conv(v[0].x, v[0].y);
                        const uint2 f = make_uint2(v[0].x, v[0].y);
                        v[0] = make_uint4(v[0].z, v[0].w, v[1].x, v[1].y); v[1] = make_uint4(v[1].z, v[1].w, f.x, f.y);
                    }
                } else {
#pragma unroll
                    for (int u = 0; u < 2; u++) v[u] = make_uint4(hmul_bf2(v[u].x, sc), hmul_bf2(v[u].y, sc), hmul_bf2(v[u].z, sc), hmul_bf2(v[u].w, sc));
                }
                sts128<0>(t, v[0]); sts128<0>(t1, v[1]);
                __syncwarp();
            }
            TKX(3)
            bar_sync(BAR_TABLE, 2 * NC * 32);
            stage3(p, sb, w, opaque(lane), role, epoch >> 5 & 31u);
            TKX(4)
            bar_sync(BAR_ACC, (NE + NC) * 32);
            if (!lds32(sb + W_WRAP)) {
                int i;
                asm volatile("mov.u32 %0, %%tid.x;" : "=r"(i));
                const int ro = lds32(sb + W_ROLE);
#pragma unroll 1
                for (i -= (W_M1 + 1) * 32; i < DROW / 16; i += NC * 32) {
                    float4* f = reinterpret_cast<float4*>(g_dirty + ro * DROW) + i;
                    const float4 v = ld_rlx128f(f);
                    uint32_t m = __float_as_uint(v.x) | __float_as_uint(v.y) << 1 | __float_as_uint(v.z) << 2 | __float_as_uint(v.w) << 3;
                    if (m) *f = make_float4(0.f, 0.f, 0.f, 0.f);
#pragma unroll 1
                    for (; m; m &= m - 1) {
                        const int b = __ffs(m) - 1;
                        g_ovf[ro * RPAD + i * 16 + (b & 3) * 4 + (b >> 3)] = make_float4(0.f, 0.f, 0.f, 0.f);
                    }
                }
            }
        }
    }
    if (hw < W_M1) {
        bar_arrive(BAR_DONE, (NE + 1) * 32);
        __syncwarp();
        TKX(4)
        finish_rows(p, sb, hw < NS1);
    }
}

__global__ void fb_scatter(const uint2* __restrict__ m, const int* __restrict__ idx_in, const int* __restrict__ idx_out,
                           const uint16_t* __restrict__ angle, const __nv_bfloat16* __restrict__ ang_freq, int T, int e0, int e1) {
    const uint32_t fb = *reinterpret_cast<const uint16_t*>(ang_freq);
    for (long long t = blockIdx.x * (long long)blockDim.x + threadIdx.x; t < T; t += (long long)gridDim.x * blockDim.x) {
        int o = idx_out[t];
        if (o < e0 || o >= e1) continue;
        float c = bf16r(cos_bf(hmul_bf2(angle[t], fb) & 0xffffu));
        uint2 v = __ldg(m + idx_in[t]);
        red4(&g_ovf[o - e0], c * bf_lo(v.x), c * bf_hi(v.x), c * bf_lo(v.y), c * bf_hi(v.y));
    }
}
__global__ void fb_final(const Params p, int e0, int e1) {
    int e = e0 + blockIdx.x * blockDim.x + threadIdx.x;
    if (e >= e1) return;
    float4 a4 = g_ovf[e - e0];
    g_ovf[e - e0] = make_float4(0.f, 0.f, 0.f, 0.f);
    float a[4] = {a4.x, a4.y, a4.z, a4.w};
    float d = __bfloat162float(p.dist[e]);
    float g[4] = {0, 0, 0, 0}, h[4] = {0, 0, 0, 0};
    for (int r = 0; r < 8; r++) {
        float df = bf16r(d - __bfloat162float(p.centers[r]));
        float rb = bf16r(expf(bf16r(-10.0f * bf16r(df * df))));
        for (int k = 0; k < 4; k++) {
            g[k] += rb * __bfloat162float(p.w_sbf[r * 4 + k]);
            h[k] += rb * __bfloat162float(p.w_rbf[r * 4 + k]);
        }
    }
    float ag[4];
    for (int k = 0; k < 4; k++) {
        float s = 0.f;
        for (int j = 0; j < 4; j++) s += a[j] * __bfloat162float(p.w_down[j * 4 + k]);
        ag[k] = bf16r(s * g[k]);
    }
    uint2 mv = p.m[e];
    float mm[4] = {bf_lo(mv.x), bf_hi(mv.x), bf_lo(mv.y), bf_hi(mv.y)};
    __nv_bfloat16 o[4];
    for (int k = 0; k < 4; k++) {
        float u = 0.f;
        for (int j = 0; j < 4; j++) u += ag[j] * __bfloat162float(p.w_up[j * 4 + k]);
        o[k] = __float2bfloat16_rn(mm[k] + bf16r(bf16r(u) * bf16r(h[k])));
    }
    p.out[e] = *reinterpret_cast<uint2*>(o);
}

}

static cudaTextureObject_t make_tex(const void* ptr, size_t bytes, int words) {
    cudaResourceDesc rd = {}; cudaTextureDesc td = {};
    rd.resType = cudaResourceTypeLinear; rd.res.linear.devPtr = const_cast<void*>(ptr); rd.res.linear.sizeInBytes = bytes;
    rd.res.linear.desc = cudaCreateChannelDesc(32, words > 1 ? 32 : 0, words > 2 ? 32 : 0, words > 2 ? 32 : 0, cudaChannelFormatKindUnsigned);
    td.readMode = cudaReadModeElementType;
    cudaTextureObject_t t = 0;
    if (cudaCreateTextureObject(&t, &rd, &td, nullptr) != cudaSuccess) { t = 0; (void)cudaGetLastError(); }
    return t;
}

extern "C" void kernel_launch(void* const* d_in, const int* in_sizes, int n_in, void* d_out, int out_size) {
    typedef const __nv_bfloat16* B;
    Params p;
    p.m = (const uint2*)d_in[0]; p.idx_in = (const uint2*)d_in[1]; p.idx_out = (const uint2*)d_in[2]; p.dist = (B)d_in[3];
    p.angle = (const uint32_t*)d_in[4]; p.centers = (B)d_in[5]; p.ang_freq = (B)d_in[6]; p.w_rbf = (B)d_in[7]; p.w_sbf = (B)d_in[8];
    p.w_down = (B)d_in[9]; p.w_up = (B)d_in[10]; p.out = (uint2*)d_out;
    p.E = in_sizes[3]; p.T = in_sizes[1]; p.T2 = p.T >> 1; p.zero = 0;
    p.R1 = p.R2 = p.rounds = p.lastn = p.full = 0; p.i1 = p.i2 = p.k1 = p.k2 = 0.f;
    static int ok = -1;
    static unsigned char* ring = nullptr;
    if (ok < 0) {
        void* ra = nullptr;
        cudaGetSymbolAddress(&ra, g_ring);
        ring = reinterpret_cast<unsigned char*>(((uintptr_t)ra + PAGE - 1) & ~(uintptr_t)(PAGE - 1));
        int dev = 0, sms = 0, occ = 0;
        cudaGetDevice(&dev);
        cudaDeviceGetAttribute(&sms, cudaDevAttrMultiProcessorCount, dev);
        cudaError_t e = cudaFuncSetAttribute(fused_kernel, cudaFuncAttributeMaxDynamicSharedMemorySize, SMEM_BYTES);
        if (e == cudaSuccess) e = cudaOccupancyMaxActiveBlocksPerMultiprocessor(&occ, fused_kernel, NTHR, SMEM_BYTES);
        ok = (e == cudaSuccess && occ >= 1 && sms >= NB) ? 1 : 0;
        (void)cudaGetLastError();
    }
    p.ring = ring;
    static cudaTextureObject_t tx[3];
    static const void* of[3];
    static int of_t = -1;
    if (of[0] != d_in[1] || of[1] != d_in[2] || of[2] != d_in[4] || of_t != p.T) {
        tx[0] = make_tex(p.idx_in, (size_t)(p.T >> 2) * 16, 4); tx[1] = make_tex(p.idx_out, (size_t)(p.T >> 2) * 16, 4); tx[2] = make_tex(p.angle, (size_t)(p.T >> 2) * 8, 2);
        of[0] = d_in[1]; of[1] = d_in[2]; of[2] = d_in[4]; of_t = p.T;
    }
    p.ti = tx[0]; p.to = tx[1]; p.ta = tx[2];
    const bool fused = ok == 1 && p.E <= EMAX && p.E >= 2 * NB && p.E % 2 == 0 && p.T >= 2;
    if (fused) {
        p.R1 = ((p.E + NG - 1) / NG + 1) & ~1;
        if (p.R1 > 1024) p.R1 = (p.R1 + 15) & ~15;
        p.R2 = ((p.E + NB - 1) / NB + 1) & ~1;
        p.i1 = nextafterf(1.f / p.R1, 2.f); p.i2 = nextafterf(1.f / p.R2, 2.f); p.k1 = -(float)p.R1; p.k2 = -8.f * p.R2;
        const int per = NB * NPR;
        int full = p.T2 / per, rest = p.T2 - full * per;
        p.full = p.ti && p.to && p.ta ? full : 0;
        p.lastn = (rest + NB - 1) / NB;
        if (p.lastn > NPR / 2) { full++; p.lastn = 0; }
        if (full < D) { full = D; p.lastn = 0; }
        p.rounds = full + 1;
        fused_kernel<<<NB, NTHR, SMEM_BYTES>>>(p);
    } else {
        for (int e0 = 0; e0 < p.E; e0 += EMAX) {
            int e1 = p.E - e0 < EMAX ? p.E : e0 + EMAX;
            fb_scatter<<<1056, 256>>>(p.m, (const int*)d_in[1], (const int*)d_in[2], (const uint16_t*)d_in[4], p.ang_freq, p.T, e0, e1);
            fb_final<<<(e1 - e0 + 255) / 256, 256>>>(p, e0, e1);
        }
    }
}
```

```cpp
#include <cuda_runtime.h>
#include <cuda_bf16.h>
#include <stdint.h>
#include <math.h>

#define RARE(x) __builtin_expect(!!(x), 0)
namespace {

constexpr int NB = 132, NG = 66;
constexpr int R2MAX = 6062, R1MAX = 12128;
constexpr int EMAX = NB * R2MAX;
constexpr int NTHR = 1024;
constexpr int NS1 = 8, NC = 11, J = 6;
constexpr int NPR = 960;
constexpr int D = 3;
constexpr int WIN = 16896;
constexpr int NDUM = 16;
constexpr uint32_t DUMMY = 0xc0000000u;
constexpr int AHEAD = 3, KDRY = 4, NPF = 6, NPROBE = 2, POLL_NS = 200, POLL_NS3 = 400;

constexpr int OFF_ACC = WIN, OFF_BAR = OFF_ACC + R2MAX * 8;
constexpr int OFF_H1 = 0x10000 + WIN, OFF_M = OFF_H1 + WIN, OFF_PROBE = OFF_M + R1MAX * 8;
constexpr int OFF_CNT1 = OFF_H1 + 0x20000 + WIN, OFF_CNT2 = OFF_CNT1 + (NG + NDUM + 2) * 4;
constexpr int OFF_HIST = OFF_ACC;
constexpr int OFF_WSM = OFF_CNT2 + (NB + NDUM) * 4 + 16;
constexpr int OFF_WB = OFF_WSM + 128, OFF_WG = OFF_WB + 64;
constexpr int SMEM_BYTES = OFF_WG + 256;
static_assert(SMEM_BYTES <= 232448 && OFF_BAR + 64 <= 0x10000 && OFF_PROBE + 256 <= 0x30000, "smem");
static_assert(OFF_BAR % 8 == 0 && OFF_WSM % 16 == 0 && OFF_CNT2 % 16 == 0, "align");
static_assert(NC * J == NG && NC * 32 * 6 * 16 == 2 * WIN, "shape");

template <int HOP> struct H {
    static constexpr int S = HOP == 1 ? 32 : 16, NBIN = HOP == 1 ? NG : NB, CAP = 2 * S, SH = HOP == 1 ? 11 : 12;
    static constexpr int TB = HOP == 1 ? 17 : 28, CNT = HOP == 1 ? OFF_CNT1 : OFF_CNT2, STG = HOP == 1 ? OFF_H1 : 0;
    static constexpr uint32_t INC = (1u << SH) + 8u, PM = (S - 1) * 8, TAG = 7u << TB;
    static __device__ __forceinline__ uint32_t tag(uint32_t R) { return R << TB & TAG; }
    static __device__ __forceinline__ uint32_t init(uint32_t R) { return tag(R) | ((1u << TB) - 0x10000u); }
    static __device__ __forceinline__ uint32_t mark(uint32_t R, uint32_t line) { return ((HOP == 1 ? R >> 1 : R) + line) & 3u; }
    static __device__ __forceinline__ uint32_t win(int r) { return HOP == 1 ? (r & 1) << 17 : (0x310u >> (r % 3 * 4) & 3u) << 16; }
};

constexpr uint32_t PAGE = 1u << 21;
constexpr int NPAGE = NC + 2;
__device__ __align__(256) unsigned char g_ring[(size_t)(NPAGE + 1) * PAGE];
constexpr int MISC = 0xa0000;
constexpr int M_CNT = MISC + 1024, M_PAR = M_CNT + 4;
constexpr int M_BASE = M_CNT + 8;
constexpr int M_FLAG = MISC + 2048;
constexpr int PROBE = MISC + 0x40000;
__device__ __forceinline__ uint32_t cred_off(uint32_t role) { return role * 4 + min(role >> 5, 3u) * (16384 - 128); }
struct Ring {
    uint64_t main, mid;
    uint32_t par;
    __device__ __forceinline__ Ring(const unsigned char* ring, uint32_t pars, int k) {
        main = reinterpret_cast<uint64_t>(ring) + ((uint64_t)k << 20);
        par = pars >> (k >> 1) & 1u;
        mid = reinterpret_cast<uint64_t>(ring) + (uint64_t)NC * PAGE + (((k >> 3 << 20) + (k >> 2 & 1) * 0x11000u + (k & 1) * 2048) ^ (k >> 1 & 1) * 0x3000u ^ (pars >> (NC + (k >> 4)) & 1u) << 12);
    }
};
constexpr int NLO = 60, NHI = 72;
__host__ __device__ constexpr uint32_t src_off(int j) { return (j % 3) << 14 | (j / 3) << 18; }
__device__ __forceinline__ uint32_t slot_off(uint32_t s) { return (0xa930u >> s * 4 & 15u) << 16; }
__device__ __forceinline__ uint32_t slot_steps(uint32_t R) { return (uint32_t)(0x30a09030aull >> (2 - R % 3) * 8) & 0xffffffu; }
__device__ __forceinline__ void slot_next(uint32_t& a, uint32_t st) { a ^= st & 0xf0000u; }
__device__ __forceinline__ uint32_t slot_rot(uint32_t st) { return __byte_perm(st, 0u, 0x4102); }
constexpr int RPAD = 6064, DROW = 6144;
__device__ __align__(128) uint8_t g_dirty[NB * DROW];
constexpr int BOX = 32, BOXN = 24, LATE = 8;
__device__ __align__(128) uint2 g_box[NB * NB * BOX];
__device__ __align__(128) float4 g_ovf[NB * RPAD];

struct Params {
    const uint2* m; const uint2* idx_in; const uint2* idx_out; const __nv_bfloat16* dist; const uint32_t* angle;
    const __nv_bfloat16* centers; const __nv_bfloat16* ang_freq; const __nv_bfloat16* w_rbf; const __nv_bfloat16* w_sbf;
    const __nv_bfloat16* w_down; const __nv_bfloat16* w_up; uint2* out; unsigned char* ring;
    cudaTextureObject_t ti, to, ta;
    int E, T, T2, R1, R2, rounds, lastn, full; uint32_t zero; float i1, i2, k1, k2;
};

__device__ __forceinline__ float bf16r(float x) { return __bfloat162float(__float2bfloat16_rn(x)); }
__device__ __forceinline__ float bf_lo(uint32_t v) { return __uint_as_float(v << 16); }
__device__ __forceinline__ float bf_hi(uint32_t v) { return __uint_as_float(v & 0xffff0000u); }
__device__ __forceinline__ void red4(float4* a, float x, float y, float z, float w) {
    asm volatile("red.global.add.v4.f32 [%0], {%1,%2,%3,%4};" ::"l"(a), "f"(x), "f"(y), "f"(z), "f"(w) : "memory");
}
__device__ __forceinline__ void bar_sync(int id, int n) { __syncwarp(); asm volatile("bar.sync %0, %1;" ::"r"(id), "r"(n) : "memory"); }
__device__ __forceinline__ void bar_arrive(int id, int n) { __syncwarp(); asm volatile("bar.arrive %0, %1;" ::"r"(id), "r"(n) : "memory"); }
template <int OFF> __device__ __forceinline__ uint32_t atoms_add(uint32_t addr, uint32_t v) {
    uint32_t r; asm volatile("atom.shared.add.u32 %0, [%1+%3], %2;" : "=r"(r) : "r"(addr), "r"(v), "n"(OFF) : "memory"); return r;
}
__device__ __forceinline__ void sts64(uint32_t addr, uint32_t x, uint32_t y) {
    asm volatile("st.shared.v2.u32 [%0], {%1,%2};" ::"r"(addr), "r"(x), "r"(y) : "memory");
}
__device__ __forceinline__ void sts32(uint32_t addr, uint32_t x) { asm volatile("st.shared.u32 [%0], %1;" ::"r"(addr), "r"(x) : "memory"); }
template <int OFF = 0> __device__ __forceinline__ uint2 lds64(uint32_t addr) {
    uint2 v; asm volatile("ld.shared.v2.u32 {%0,%1}, [%2+%3];" : "=r"(v.x), "=r"(v.y) : "r"(addr), "n"(OFF) : "memory"); return v;
}
__device__ __forceinline__ uint32_t lds32(uint32_t addr) {
    uint32_t v; asm volatile("ld.shared.u32 %0, [%1];" : "=r"(v) : "r"(addr) : "memory"); return v;
}
template <int OFF> __device__ __forceinline__ void sts128(uint32_t a, const uint4& v) {
    asm volatile("st.shared.v4.u32 [%0+%5], {%1,%2,%3,%4};" ::"r"(a), "r"(v.x), "r"(v.y), "r"(v.z), "r"(v.w), "n"(OFF) : "memory");
}
__device__ __forceinline__ uint4 lds128(uint32_t a) {
    uint4 v; asm volatile("ld.shared.v4.u32 {%0,%1,%2,%3}, [%4];" : "=r"(v.x), "=r"(v.y), "=r"(v.z), "=r"(v.w) : "r"(a) : "memory"); return v;
}
__device__ __forceinline__ uint32_t ld_rlx32(const uint32_t* p) {
    uint32_t v; asm volatile("ld.relaxed.gpu.global.u32 %0, [%1];" : "=r"(v) : "l"(p) : "memory"); return v;
}
__device__ __forceinline__ uint2 ld_rlx64(const void* p) {
    uint2 v; asm volatile("ld.relaxed.gpu.global.v2.u32 {%0,%1}, [%2];" : "=r"(v.x), "=r"(v.y) : "l"(p) : "memory"); return v;
}
__device__ __forceinline__ float4 ld_rlx128f(const float4* p) {
    float4 v; asm volatile("ld.relaxed.gpu.global.v4.f32 {%0,%1,%2,%3}, [%4];" : "=f"(v.x), "=f"(v.y), "=f"(v.z), "=f"(v.w) : "l"(p) : "memory"); return v;
}
__device__ __forceinline__ float4 take(float4* p, bool q) {
    float4 v;
    asm volatile("{ .reg .b128 a; .reg .b64 x, y; .reg .pred q; mov.b64 x, 0; mov.b128 a, {x, x}; setp.ne.u32 q, %5, 0;\n"
                 "@q atom.relaxed.gpu.global.exch.b128 a, [%4], a; mov.b128 {x, y}, a; mov.b64 {%0,%1}, x; mov.b64 {%2,%3}, y; }"
                 : "=f"(v.x), "=f"(v.y), "=f"(v.z), "=f"(v.w) : "l"(p), "r"((uint32_t)q) : "memory");
    return v;
}
__device__ __forceinline__ void fence_gpu() { asm volatile("fence.acq_rel.gpu;" ::: "memory"); }
__device__ __forceinline__ void st_rlx32(uint32_t* p, uint32_t v) { asm volatile("st.relaxed.gpu.global.u32 [%0], %1;" ::"l"(p), "r"(v) : "memory"); }
__device__ __forceinline__ uint32_t hmul_bf2(uint32_t a, uint32_t b) {
    uint32_t r; asm("mul.rn.bf16x2 %0, %1, %2;" : "=r"(r) : "r"(a), "r"(b)); return r;
}
__device__ __forceinline__ uint32_t hsub_bf2(uint32_t a, uint32_t b) {
    uint32_t r; asm("sub.rn.bf16x2 %0, %1, %2;" : "=r"(r) : "r"(a), "r"(b)); return r;
}
__device__ __forceinline__ uint32_t hadd_bf2(uint32_t a, uint32_t b) {
    uint32_t r; asm("add.rn.bf16x2 %0, %1, %2;" : "=r"(r) : "r"(a), "r"(b)); return r;
}
__device__ __forceinline__ int opaque(int v) { return __shfl_sync(0xffffffffu, v, threadIdx.x); }
constexpr int SPIN_LIMIT = 1 << 22;

__constant__ uint32_t c_inv2pi[8] = {0u, 0x28be60dbu, 0x9391054au, 0x7f09d5f4u, 0x7d4d3770u, 0x36d8a566u, 0x4f10e410u, 0x7f9458eau};
constexpr uint32_t BIGX = 0x4280u;
__device__ __forceinline__ float cos_big(uint32_t xb) {
    uint32_t e = (xb >> 7) & 0xffu, M = (xb & 0x7fu) | 0x80u;
    uint32_t pp = e - 102u;
    uint32_t wi = pp >> 5;
    uint32_t t0 = c_inv2pi[wi], t1 = c_inv2pi[wi + 1], t2 = c_inv2pi[wi + 2];
    uint32_t f = M * __funnelshift_l(t1, t0, pp) + __umulhi(M, __funnelshift_l(t2, t1, pp));
    float c = __cosf((float)(int)f * 1.4629180792671596e-9f);
    return e == 255u ? __uint_as_float(0x7fc00000u) : c;
}
__device__ __forceinline__ float cos_bf(uint32_t xb) {
    return (xb & 0x7fffu) > BIGX ? cos_big(xb) : __cosf(__uint_as_float(xb << 16));
}
__device__ __forceinline__ uint32_t pack_bf2(float lo, float hi) {
    uint32_t r; asm("cvt.rn.bf16x2.f32 %0, %1, %2;" : "=r"(r) : "f"(hi), "f"(lo)); return r;
}
template <int N> __device__ __forceinline__ uint32_t pick(int k, const uint32_t (&a)[N]) {
    uint32_t v = a[0];
#pragma unroll
    for (int i = 1; i < N; i++) if (k == i) v = a[i];
    return v;
}
template <int N> __device__ __forceinline__ uint2 pick(int k, const uint2 (&a)[N]) {
    uint2 v = a[0];
#pragma unroll
    for (int i = 1; i < N; i++) if (k == i) v = a[i];
    return v;
}
__device__ __forceinline__ uint32_t imul(uint32_t a, float s) { uint32_t r; asm("mul.rz.f32 %0, %1, %2;" : "=r"(r) : "r"(a), "f"(s)); return r; }
__device__ __forceinline__ uint32_t ifma(uint32_t a, float s, uint32_t c) { uint32_t r; asm("fma.rn.f32 %0, %1, %2, %3;" : "=r"(r) : "r"(a), "f"(s), "r"(c)); return r; }
extern __shared__ __align__(1024) unsigned char smem[];
__device__ __forceinline__ void side_add(uint32_t bin, uint32_t row, float a, float b, float c, float d) {
    red4(&g_ovf[bin * RPAD + row], a, b, c, d);
    g_dirty[bin * DROW + row] = 1;
}
__device__ __forceinline__ void slow_triplet(const Params& p, uint32_t ii, uint32_t oo, float c) {
    const uint2 v = __ldg(p.m + ii);
    const uint32_t bo = imul(oo, p.i2);
    side_add(bo, oo - bo * p.R2, c * bf_lo(v.x), c * bf_hi(v.x), c * bf_lo(v.y), c * bf_hi(v.y));
}
__device__ __forceinline__ void slow_rec1(const Params& p, uint32_t x, uint32_t y, uint32_t bin) {
    const uint2 v = __ldg(p.m + bin * p.R1 + (y & 0xffffu));
    const float c = bf_hi(y);
    side_add(x & 0xffu, __byte_perm(x, 0u, 0x4413) >> 3, c * bf_lo(v.x), c * bf_hi(v.x), c * bf_lo(v.y), c * bf_hi(v.y));
}
__device__ __forceinline__ uint32_t aux_of(uint32_t w0, uint32_t w1, uint32_t k = 0) {
    uint32_t u; asm("lop3.b32 %0, %1, %2, 0xf000f000, 0xe4;" : "=r"(u) : "r"(w0), "r"((w1 >> 4) + k));
    return __byte_perm(u, 0u, 0x4413);
}
__device__ __forceinline__ void slow_rec2(const Params& p, uint32_t w0, uint32_t w1, uint32_t bin, float unit) {
    side_add(bin, aux_of(w0, w1) >> 3, (float)((int)(w0 & 0xfffu) - 2048) * unit, (float)((int)(w0 >> 16 & 0xfffu) - 2048) * unit,
             (float)((int)(w1 & 0xfffu) - 2048) * unit, (float)((int)(w1 >> 16 & 0xfffu) - 2048) * unit);
}
template <uint32_t M> __device__ __forceinline__ uint32_t and_or(uint32_t a, uint32_t c) {
    uint32_t r; asm("lop3.b32 %0, %1, %2, %3, 0xea;" : "=r"(r) : "r"(a), "n"(M), "r"(c)); return r;
}
template <uint32_t M> __device__ __forceinline__ uint32_t xor_and(uint32_t a, uint32_t c) {
    uint32_t r; asm("lop3.b32 %0, %1, %2, %3, 0x48;" : "=r"(r) : "r"(a), "n"(M), "r"(c)); return r;
}
__device__ __forceinline__ uint32_t mux(uint32_t a, uint32_t b, uint32_t m) {
    uint32_t r; asm("lop3.b32 %0, %1, %2, %3, 0xd8;" : "=r"(r) : "r"(a), "r"(b), "r"(m)); return r;
}
__device__ __forceinline__ uint32_t and_xor(uint32_t a, uint32_t m, uint32_t c) {
    uint32_t r; asm("lop3.b32 %0, %1, %2, %3, 0x6a;" : "=r"(r) : "r"(a), "r"(m), "r"(c)); return r;
}
__device__ __forceinline__ uint2 ld_in(const uint2* a) {
    uint2 v; asm volatile("ld.global.nc.L1::no_allocate.v2.u32 {%0,%1}, [%2];" : "=r"(v.x), "=r"(v.y) : "l"(a)); return v;
}
__device__ __forceinline__ uint32_t ld_in(const uint32_t* a) {
    uint32_t v; asm volatile("ld.global.nc.L1::no_allocate.u32 %0, [%1];" : "=r"(v) : "l"(a)); return v;
}
__device__ __forceinline__ void ld_in4(const uint2* p, uint2& a, uint2& b) {
    asm volatile("ld.global.nc.L1::no_allocate.v4.u32 {%0,%1,%2,%3}, [%4];" : "=r"(a.x), "=r"(a.y), "=r"(b.x), "=r"(b.y) : "l"(p));
}
__device__ __forceinline__ void tex4(cudaTextureObject_t t, int i, uint2& a, uint2& b) {
    asm volatile("tex.1d.v4.u32.s32 {%0,%1,%2,%3}, [%4, {%5}];" : "=r"(a.x), "=r"(a.y), "=r"(b.x), "=r"(b.y) : "l"(t), "r"(i));
}
__device__ __forceinline__ void tex2(cudaTextureObject_t t, int i, uint32_t& a, uint32_t& b) {
    asm volatile("{ .reg .b32 z, w; tex.1d.v4.u32.s32 {%0,%1,z,w}, [%2, {%3}]; }" : "=r"(a), "=r"(b) : "l"(t), "r"(i) : "memory");
}
template <int OFF> __device__ __forceinline__ void put_rec(uint32_t ret, uint32_t lim, uint32_t addr, uint32_t x, uint32_t y) {
    asm volatile("{ .reg .pred q; setp.lt.u32 q, %0, %1; @q st.shared.v2.u32 [%2+%5], {%3,%4}; }" ::"r"(ret), "r"(lim), "r"(addr), "r"(x), "r"(y), "n"(OFF) : "memory");
}
__device__ __forceinline__ uint32_t mbar_try(uint32_t mb, uint32_t parity) {
    uint32_t ok;
    asm volatile("{ .reg .pred q; mbarrier.try_wait.parity.shared::cta.b64 q, [%1], %2; selp.u32 %0, 1, 0, q; }" : "=r"(ok) : "r"(mb), "r"(parity) : "memory");
    return ok;
}
__device__ __forceinline__ void mbar_wait(uint32_t mb, uint32_t parity) {
    if (!mbar_try(mb, parity)) {
        int it = 0;
        while (!mbar_try(mb, parity)) if (++it > SPIN_LIMIT) __trap();
    }
}
__device__ __forceinline__ void mbar_init(uint32_t mb, uint32_t n) { asm volatile("mbarrier.init.shared::cta.b64 [%0], %1;" ::"r"(mb), "r"(n) : "memory"); }
__device__ __forceinline__ void mbar_arrive(uint32_t mb) { asm volatile("mbarrier.arrive.shared::cta.b64 _, [%0];" ::"r"(mb) : "memory"); }
constexpr int B_FULL = OFF_BAR, B_OPEN = OFF_BAR + 16, B_FREE = OFF_BAR + 32;
constexpr int W_END = OFF_BAR + 40, W_SIDE = OFF_BAR + 44, W_PAR = OFF_BAR + 48, W_ROLE = OFF_BAR + 52, W_EXP = OFF_BAR + 56, W_UNIT = OFF_BAR + 60, W_NLIST = OFF_PROBE + 112, W_WRAP = OFF_PROBE + 116, W_BASE = OFF_PROBE + 120, B_TAB = OFF_PROBE + 128, B_ROWS = OFF_PROBE + 248, B_TFREE = OFF_PROBE + 240, B_FLAG = OFF_PROBE + 232, B_INIT = OFF_PROBE + 224, W_ITEM = OFF_PROBE + 124;
enum { BAR_S1 = 1, BAR_SIDE, BAR_PROBE, BAR_PAR, BAR_TABLE, BAR_DONE, BAR_ACC, BAR_H1, BAR_BASE, BAR_ROWS };
constexpr int W_M1 = NS1 + NC, W_M2 = 31;

#define RTS(c, i)
#define TK_DECL
#define TK(i)
#define TK_CNT(i)
#define TK_OUT
#define TK_ARG
#define TK_PASS
#define TKS(i) TK(i)
#define TKX(i)
#define TKY(i) {}
#define TKZ(i, d)

__device__ __forceinline__ void prefetch_l2(const void* a) { asm volatile("prefetch.global.L2 [%0];" ::"l"(a)); }
__device__ __forceinline__ void wait_flags(const Params& p, uint32_t sb, int lane, uint32_t need) {
    const unsigned char* f = p.ring + M_FLAG + (lds32(sb + W_SIDE) << 12);
    int it = 0;
    while (true) {
        uint32_t a[4];
        asm volatile("ld.acquire.gpu.global.v4.u32 {%0,%1,%2,%3}, [%4];" : "=r"(a[0]), "=r"(a[1]), "=r"(a[2]), "=r"(a[3]) : "l"(f + min(lane, 16) * 16) : "memory");
        const uint32_t d = (a[0] ^ need) | (a[1] ^ need) | (lane < 16 ? (a[2] ^ need) | (a[3] ^ need) : 0u);
        if (__all_sync(0xffffffffu, d == 0)) break;
        __nanosleep(50);
        if (++it > SPIN_LIMIT) __trap();
    }
}
__device__ __forceinline__ float exp_fast(float x) { float r; asm("ex2.approx.ftz.f32 %0, %1;" : "=f"(r) : "f"(x * 1.4426950408889634f)); return r; }
constexpr uint32_t BIAS = 0x3d803d80u, ZERO = 0x7d80u;
__device__ __forceinline__ float2 acc_fix(uint32_t old, uint32_t q) {
    const uint32_t u = old + BIAS, n = u + q - 0x08000800u;
    return make_float2((float)((int)(u & 0xffffu) + (int)(q & 0xffffu) - 2048 - (int)(n & 0xffffu)), (float)((int)(u >> 16) + (int)(q >> 16) - 2048 - (int)(n >> 16)));
}
constexpr int NE = NS1 + NC, NPAIR = (R2MAX / 2 + NE * 32 - 1) / (NE * 32), NTILE = 16, NG0 = NS1 * 8 * NTILE;
constexpr int OFF_G = OFF_M, GH = R2MAX * 8, OFF_LIST = OFF_G;
static_assert(2 * R2MAX <= R1MAX && NG0 * 16 + 112 <= WIN && 3 * NG0 >= NPAIR * NE * 32 && NPAIR * NE * 64 <= DROW, "gates");
__device__ __forceinline__ int gate_g(int k) { return (k < NG0 ? OFF_H1 : OFF_G) + k * 16; }
__device__ __forceinline__ int gate_h(int k) { return (k < NG0 ? OFF_H1 + 0x20000 : OFF_G + GH) + k * 16; }
__device__ __forceinline__ uint2 out_row(int row, const float4& o, const float4& add, const uint2& mv) {
    const float* w = reinterpret_cast<const float*>(smem + OFF_WSM);
    const float unit = *reinterpret_cast<const float*>(smem + W_UNIT), K = 8388608.f + ZERO;
    const uint2 ac = reinterpret_cast<const uint2*>(smem + OFF_ACC)[row];
    const uint32_t* g = reinterpret_cast<const uint32_t*>(smem + gate_g(row >> 1)) + (row & 1), *h = reinterpret_cast<const uint32_t*>(smem + gate_h(row >> 1)) + (row & 1);
    const uint32_t c0 = ac.x + BIAS, c1 = ac.y + BIAS;
    const float a[4] = {fmaf(__uint_as_float(__byte_perm(c0, 0x4b00u, 0x5410)) - K, unit, o.x), fmaf(__uint_as_float(__byte_perm(c0, 0x4b00u, 0x5432)) - K, unit, o.y),
                        fmaf(__uint_as_float(__byte_perm(c1, 0x4b00u, 0x5410)) - K, unit, o.z), fmaf(__uint_as_float(__byte_perm(c1, 0x4b00u, 0x5432)) - K, unit, o.w)};
    float sd[4], uu[4];
#pragma unroll
    for (int k = 0; k < 4; k++) sd[k] = fmaf(a[3], w[12 + k], fmaf(a[2], w[8 + k], fmaf(a[1], w[4 + k], a[0] * w[k])));
    const uint32_t a01 = hmul_bf2(pack_bf2(sd[0] + add.x, sd[1] + add.y), g[0]), a23 = hmul_bf2(pack_bf2(sd[2] + add.z, sd[3] + add.w), g[2]);
#pragma unroll
    for (int k = 0; k < 4; k++) uu[k] = fmaf(bf_hi(a23), w[28 + k], fmaf(bf_lo(a23), w[24 + k], fmaf(bf_hi(a01), w[20 + k], bf_lo(a01) * w[16 + k])));
    return make_uint2(hadd_bf2(mv.x, hmul_bf2(pack_bf2(uu[0], uu[1]), h[0])), hadd_bf2(mv.y, hmul_bf2(pack_bf2(uu[2], uu[3]), h[2])));
}
__device__ __forceinline__ void mma16(float (&c)[4], const uint32_t (&a)[4], uint32_t b0, uint32_t b1) {
    asm volatile("mma.sync.aligned.m16n8k16.row.col.f32.bf16.bf16.f32 {%0,%1,%2,%3}, {%4,%5,%6,%7}, {%8,%9}, {%0,%1,%2,%3};"
                 : "+f"(c[0]), "+f"(c[1]), "+f"(c[2]), "+f"(c[3]) : "r"(a[0]), "r"(a[1]), "r"(a[2]), "r"(a[3]), "r"(b0), "r"(b1));
}
__device__ __forceinline__ void finish_rows(const Params& p, uint32_t sb, bool s1) {
    int tid;
    bool wet = false;
    {
        asm volatile("mov.u32 %0, %%tid.x;" : "=r"(tid));
        const int lane = tid & 31;
        if (s1) mbar_wait(sb + B_INIT, 0); else if (lane == 0) mbar_arrive(sb + B_TFREE);
#pragma unroll 1
        for (bool own = s1;; own = false, wet = true) {
            asm volatile("mov.u32 %0, %%tid.x;" : "=r"(tid));
            uint32_t item = tid >> 5;
            if (!own) item = tid & 31 ? 0u : atoms_add<W_ITEM>(sb, 1u);
            item = __reduce_max_sync(0xffffffffu, item);
            if (item >= 3 * NS1) break;
            const int kb = item / NS1 * NG0 + item % NS1 * 8, q = (lds32(sb + W_ROLE) * p.R2 >> 1) + kb + (tid >> 2 & 7) + (tid & 3) * NS1 * 8;
            uint32_t ds[NTILE / 4];
#pragma unroll
            for (int j = 0; j < NTILE / 4; j++) ds[j] = ld_in(reinterpret_cast<const uint32_t*>(p.dist) + min(q + j * NS1 * 32, (p.E >> 1) - 1));
            const uint2 wc = lds64<OFF_WG>(sb + (tid & 31) * 8);
            const uint32_t wb = wc.x, cen = wc.y;
            TKZ(4, (ds[0] ^ ds[1] ^ ds[2] ^ ds[3] ^ wb ^ cen))
            uint2 v[NTILE];
#pragma unroll
            for (int i = 0; i < NTILE; i++) {
                const uint32_t x = __shfl_sync(0xffffffffu, ds[i >> 2], i & 3, 4);
                uint32_t rb[2];
#pragma unroll
                for (int u = 0; u < 2; u++) {
                    const uint32_t df = hsub_bf2(__byte_perm(x, 0u, u ? 0x3232 : 0x1010), cen);
                    const uint32_t ar = hmul_bf2(hmul_bf2(df, df), 0xc120c120u);
                    rb[u] = pack_bf2(exp_fast(bf_lo(ar)), exp_fast(bf_hi(ar)));
                }
                float c[4];
                asm volatile("mma.sync.aligned.m16n8k8.row.col.f32.bf16.bf16.f32 {%0,%1,%2,%3}, {%4,%5}, {%6}, {%7,%7,%7,%7};"
                             : "=f"(c[0]), "=f"(c[1]), "=f"(c[2]), "=f"(c[3]) : "r"(rb[0]), "r"(rb[1]), "r"(wb), "f"(0.f));
                v[i] = make_uint2(pack_bf2(c[0], c[1]), pack_bf2(c[2], c[3]));
            }
            TKZ(5, (v[15].x ^ v[9].y))
            if (own) bar_sync(BAR_H1, (NS1 + 1) * 32); else mbar_wait(sb + B_TFREE, 0);
            asm volatile("mov.u32 %0, %%tid.x;" : "=r"(tid));
            const int k0 = kb + (tid >> 2 & 7);
            const uint32_t a = sb + (tid & 2 ? gate_h(k0) : gate_g(k0)) + (tid & 1) * 8;
#pragma unroll
            for (int i = 0; i < NTILE; i++) if (i < NTILE - 1 || k0 + i * NS1 * 8 < R2MAX / 2) sts64(a + i * NS1 * 8 * 16, v[i].x, v[i].y);
            static_assert(2 * NG0 + (NTILE - 1) * NS1 * 8 <= R2MAX / 2, "gates");
            TKY(1)
        }
    }
    asm volatile("mov.u32 %0, %%tid.x;" : "=r"(tid));
    const int role = lds32(sb + W_ROLE), row0 = role * p.R2, np = min(p.R2, p.E - row0) >> 1, lane = tid & 31;
    uint4 wd = make_uint4(0u, 0u, 0u, 0u), wu = wd;
    if ((lane & 3) == lane >> 3) { wd = lds128(sb + OFF_WB + (lane & 4) * 8); wu = lds128(sb + OFF_WB + 16 + (lane & 4) * 8); }
    const uint32_t wb[8] = {wd.x, wd.y, wd.z, wd.w, wu.x, wu.y, wu.z, wu.w};
    const uint32_t k0 = (lds32(sb + W_UNIT) >> 16) * 0x10001u + 0x03800380u;
    uint8_t* dirty = g_dirty + role * DROW + tid * 2;
    auto flags = [&](uint32_t on) {
        uint32_t f[NPAIR], m = 0;
#pragma unroll
        for (int i = 0; i < NPAIR; i++) asm volatile("{ .reg .pred q; setp.ne.u32 q, %2, 0; mov.u32 %0, 0; @q ld.relaxed.gpu.global.u16 %0, [%1]; }" : "=r"(f[i]) : "l"(dirty + i * NE * 64), "r"(on) : "memory");
#pragma unroll
        for (int i = 0; i < NPAIR; i++) m |= ((f[i] | f[i] >> 7) & 3u) << 2 * i;
        return m;
    };
    auto row_of = [&](int j) { return 2 * tid + (j >> 1) * NE * 64 + (j & 1); };
    uint32_t kept, left = 0, bad = 0, at;
#pragma unroll 1
    for (;; wet = true) {
    if (wet) mbar_wait(sb + B_FLAG, 0);
    TKY(2)
    kept = flags(wet);
    at = __popc(kept);
    TKZ(3, kept)
#pragma unroll
    for (int i = 1; i < 32; i *= 2) { const uint32_t t = __shfl_up_sync(0xffffffffu, at, i); if (lane >= i) at += t; }
    const uint32_t n = __shfl_sync(0xffffffffu, at, 31);
    if (n || !wet) {
        uint32_t q = 0;
        if (lane == 0) q = atoms_add<W_NLIST>(sb, n);
        q = __shfl_sync(0xffffffffu, q, 0);
        if (q + n > NG0) { sts32(sb + W_WRAP, 1u); kept = 0; }
        else {
            q = sb + OFF_LIST + q * 16;
            at = q + (at - __popc(kept)) * 16;
            uint32_t to = at;
            uint32_t m = kept;
#pragma unroll 1
            do {
                if (m) sts32(to, row_of(__ffs(m) - 1));
                m &= m - 1; to += 16;
            } while (m);
            __syncwarp();
            to = q + lane * 16;
#pragma unroll 1
            do {
                const bool on = to < q + n * 16;
                float4 o = make_float4(0.f, 0.f, 0.f, 0.f);
                asm volatile("{ .reg .pred q; setp.ne.u32 q, %5, 0; @q ld.relaxed.gpu.global.v4.f32 {%0,%1,%2,%3}, [%4]; }"
                             : "+f"(o.x), "+f"(o.y), "+f"(o.z), "+f"(o.w) : "l"(&g_ovf[role * RPAD + lds32(to)]), "r"((uint32_t)on) : "memory");
                const float4* w = reinterpret_cast<const float4*>(smem + OFF_WSM);
                const uint4 v = make_uint4(__float_as_uint(fmaf(o.w, w[3].x, fmaf(o.z, w[2].x, fmaf(o.y, w[1].x, o.x * w[0].x)))),
                                           __float_as_uint(fmaf(o.w, w[3].y, fmaf(o.z, w[2].y, fmaf(o.y, w[1].y, o.x * w[0].y)))),
                                           __float_as_uint(fmaf(o.w, w[3].z, fmaf(o.z, w[2].z, fmaf(o.y, w[1].z, o.x * w[0].z)))),
                                           __float_as_uint(fmaf(o.w, w[3].w, fmaf(o.z, w[2].w, fmaf(o.y, w[1].w, o.x * w[0].w)))));
                if (on) sts128<0>(to, v);
                to += 512;
            } while (to < q + n * 16);
        }
    }
    TKY(6)
    if (wet) {
        mbar_wait(sb + B_ROWS, 0);
        TKX(5)
        bar_sync(BAR_ACC, (NE + NC) * 32);
    }
    const int lim = wet ? np : 0;
    uint32_t from = at, bit = wet ? 1u : 1u << (2 * NPAIR - 2);
    uint4* out = reinterpret_cast<uint4*>(p.out + row0) + tid;
#pragma unroll 1
    for (int k = tid; bit < 1u << 2 * NPAIR; k += NE * 32, bit *= 4, out += NE * 32) {
        const uint4 ac = lds128(sb + OFF_ACC + k * 16), g = lds128(sb + gate_g(k)), h = lds128(sb + gate_h(k));
        const uint4 mv = lds128(sb + (row0 * 8 & 127) + k * 16 + (k < NG0 ? 0 : k < 2 * NG0 ? 0x10000 - NG0 * 16 : 0x30000 - NG0 * 32));
        const uint32_t u[4] = {ac.x + BIAS, ac.z + BIAS, ac.y + BIAS, ac.w + BIAS};
        uint32_t a[4];
        float c[4] = {0.f, 0.f, 0.f, 0.f}, d[4] = {0.f, 0.f, 0.f, 0.f};
#pragma unroll
        for (int j = 0; j < 2; j++)
            asm volatile("{ .reg .pred q; setp.ne.u32 q, %5, 0; @q ld.shared.v2.f32 {%0,%1}, [%4]; @q ld.shared.v2.f32 {%2,%3}, [%4+8]; @q add.u32 %4, %4, 16; }"
                         : "+f"(c[2 * j]), "+f"(c[2 * j + 1]), "+f"(d[2 * j]), "+f"(d[2 * j + 1]), "+r"(from) : "r"(kept & bit << j) : "memory");
#pragma unroll
        for (int j = 0; j < 4; j++) a[j] = hsub_bf2(and_or<0x007f007fu>(u[j] >> 9, k0 + 0x04800480u), k0 + 0x04c004c0u);
        mma16(c, a, wb[0], wb[1]); mma16(d, a, wb[2], wb[3]);
#pragma unroll
        for (int j = 0; j < 4; j++) a[j] = and_or<0x007f007fu>(u[j] >> 2, k0 + 0x01000100u);
        mma16(c, a, wb[0], wb[1]); mma16(d, a, wb[2], wb[3]);
#pragma unroll
        for (int j = 0; j < 4; j++) a[j] = and_or<0x00030003u>(u[j], k0);
        mma16(c, a, wb[0], wb[1]); mma16(d, a, wb[2], wb[3]);
        a[0] = hmul_bf2(pack_bf2(c[0], c[1]), g.x); a[1] = hmul_bf2(pack_bf2(c[2], c[3]), g.y);
        a[2] = hmul_bf2(pack_bf2(d[0], d[1]), g.z); a[3] = hmul_bf2(pack_bf2(d[2], d[3]), g.w);
#pragma unroll
        for (int j = 0; j < 4; j++) c[j] = d[j] = 0.f;
        mma16(c, a, wb[4], wb[5]); mma16(d, a, wb[6], wb[7]);
        if (k < lim) {
            *out = make_uint4(hadd_bf2(mv.x, hmul_bf2(pack_bf2(c[0], c[1]), h.x)), hadd_bf2(mv.y, hmul_bf2(pack_bf2(d[0], d[1]), h.z)),
                              hadd_bf2(mv.z, hmul_bf2(pack_bf2(c[2], c[3]), h.y)), hadd_bf2(mv.w, hmul_bf2(pack_bf2(d[2], d[3]), h.w)));
            if (c[0] != c[0] || c[2] != c[2]) bad |= 3u * bit;
        }
    }
    if (wet) break;
    }
    const bool wrap = lds32(sb + W_WRAP);
    if (RARE(wrap)) { left = flags(1u); kept = 0; }
#pragma unroll 1
    for (uint32_t m = left | bad; RARE(m); m &= m - 1) {
        const int j = __ffs(m) - 1, row = row_of(j);
        uint4 v = make_uint4(0u, 0u, 0u, 0u);
        if (kept >> j & 1u) v = lds128(at + __popc(kept & ((1u << j) - 1u)) * 16);
        p.out[row0 + row] = out_row(row, take(&g_ovf[role * RPAD + row], left >> j & 1u),
                                    make_float4(__uint_as_float(v.x), __uint_as_float(v.y), __uint_as_float(v.z), __uint_as_float(v.w)), p.m[row0 + row]);
        if (wrap) g_dirty[role * DROW + row] = 0;
    }
}

template <int HOP> __device__ __forceinline__ uint2 null_rec(int lane, uint32_t R) {
    if (HOP == 1) return make_uint2(0x800000u | H<1>::tag(R), (OFF_CNT1 - OFF_M) / 8);
    return make_uint2(0x08000800u | lane << 28, 0x0fff0000u | H<2>::tag(R));
}
template <int HOP> __device__ __forceinline__ void fill(uint32_t win, int ct, uint32_t R) {
    const uint2 v = null_rec<HOP>(ct, R);
#pragma unroll
    for (int i = 0; i < WIN / (NC * 512); i++) sts128<0>(win + ct * 16 + i * NC * 512, make_uint4(v.x, v.y, v.x, v.y));
}
template <int HOP> __device__ __forceinline__ void reset(uint32_t win, int lane, uint32_t R) {
    const uint2 v = null_rec<HOP>(lane, R);
    const uint32_t a = win + lane * 32 + H<HOP>::mark(R, lane >> 2) * 8;
#pragma unroll
    for (int i = 0; i < 16; i++) sts64(a + i * 1024, v.x, v.y);
    if (lane < 16) sts64(a + 16384, v.x, v.y);
}
__device__ __forceinline__ bool elect() {
    uint32_t q; asm volatile("{ .reg .pred q; elect.sync _|q, 0xffffffff; selp.u32 %0, 1, 0, q; }" : "=r"(q)); return q;
}
__device__ __forceinline__ const unsigned char* mk_ptr(uint32_t lo, uint32_t hi) { return reinterpret_cast<const unsigned char*>((uint64_t)hi << 32 | lo); }
__device__ __forceinline__ void bulk_store(uint32_t lo, uint32_t hi, uint32_t src, uint32_t n) {
    asm volatile("cp.async.bulk.global.shared::cta.bulk_group [%0], [%1], %2;" ::"l"(mk_ptr(lo, hi)), "r"(src), "r"(n) : "memory");
}
template <int HOP>
__device__ __forceinline__ void manager(const Params& p, uint32_t sb, int lane, int role, uint32_t base) {
    typedef H<HOP> h;
    constexpr int V = h::NBIN / 32, PB = h::S * 8;
    const int RT = p.rounds + HOP - 1, lo = HOP == 1 && role >= NG ? NG : 0, hi = lo + h::NBIN;
    const int w = (role - lo) / (HOP * J), j = (role - lo - w * HOP * J) / HOP;
    const Ring rg(p.ring, __reduce_or_sync(0xffffffffu, lds32(sb + W_PAR)), 2 * w + HOP - 1);
    const uint32_t side = lds32(sb + W_SIDE), dhi = rg.main >> 32, mhi = rg.mid >> 32;
    const uint32_t c0 = HOP == 2 ? role & 1 : 0, up = (HOP == 1 && lo) ^ rg.par ^ c0;
    uint32_t dA = ((uint32_t)rg.main + src_off(j) + (c0 << 16) + (up ? 4096 : 12288)) ^ slot_off(base % 3);
    uint32_t dM = ((uint32_t)rg.mid + src_off(j) + c0 * 1024) ^ slot_off(base % 3);
    const int a0 = max(64, lo), b1 = min(68, hi);
    int n0 = (min(NHI, hi) - a0) * PB, a1 = (max(NLO, lo) - lo) * PB;
    const unsigned char* cr = reinterpret_cast<const unsigned char*>(rg.main) + MISC + ((side ^ rg.par) << 12);
    const unsigned char* cr0 = cr + cred_off(lo + lane * V), *cr1 = cr + cred_off(lo + 32 * V + min(lane, V - 1));
    const uint32_t ca0 = sb + h::CNT + lane * V * 4, ca1 = sb + h::CNT + (32 * V + min(lane, V + NDUM)) * 4;
    const uint32_t rot0 = (lane * V & 7) * 16, rot1 = lane * 16;
    uint32_t st = slot_steps(base);
    uint32_t init = h::init(base), prim = sb + h::STG + (HOP == 1 ? h::win(base) : 0u);
    uint32_t cs[5] = {0, 0, 0, 0, 0};
    auto sample = [&]() {
        if (V == 2) asm volatile("ld.relaxed.gpu.global.v2.u32 {%0,%1}, [%2];" : "=r"(cs[0]), "=r"(cs[1]) : "l"(cr0) : "memory");
        else asm volatile("ld.relaxed.gpu.global.v4.u32 {%0,%1,%2,%3}, [%4];" : "=r"(cs[0]), "=r"(cs[1]), "=r"(cs[2]), "=r"(cs[3]) : "l"(cr0) : "memory");
        cs[V] = ld_rlx32(reinterpret_cast<const uint32_t*>(cr1));
    };
    uint32_t low[5] = {rot0, rot0 + 16, rot0 + 32, rot0 + 48, rot1};
    TK_DECL
#pragma unroll 1
    for (int r = 0;; r++) {
        const uint32_t R = base + r, ninit = h::init(R + 1), done = prim;
        TK(5)
        mbar_wait(sb + B_FULL + (HOP - 1) * 8, r & 1);
        TK(0)
        if (HOP == 2) sample();
        uint32_t c[5];
        if (V == 2) asm volatile("ld.shared.v2.u32 {%0,%1}, [%2];" : "=r"(c[0]), "=r"(c[1]) : "r"(ca0) : "memory");
        else asm volatile("ld.shared.v4.u32 {%0,%1,%2,%3}, [%4];" : "=r"(c[0]), "=r"(c[1]), "=r"(c[2]), "=r"(c[3]) : "r"(ca0) : "memory");
        c[V] = lds32(ca1);
        uint32_t nc[5];
#pragma unroll
        for (int k = 0; k <= V; k++) {
            const uint32_t rot = k < V ? rot0 + k * 16 : rot1, z = ninit + (HOP == 1 ? rot : low[k]);
            if (HOP == 2) low[k] = min((max((int)(c[k] - low[k] - init - h::CAP * h::INC), 0) >> h::SH) * 128u + low[k], rot + BOXN * 128u);
            nc[k] = min(max(c[k] + (ninit - init - h::S * h::INC), z), (HOP == 1 ? z : ninit + low[k]) + (h::CAP - h::S) * h::INC);
        }
        if (V == 2) sts64(ca0, nc[0], nc[1]); else sts128<0>(ca0, make_uint4(nc[0], nc[1], nc[2], nc[3]));
        sts32(ca1, lane < V ? nc[V] : lane < V + NDUM ? DUMMY : r);
        __syncwarp();
        if (lane == 0) mbar_arrive(sb + B_OPEN + (HOP - 1) * 8);
        TK(1)
        TK(2)
        asm volatile("fence.proxy.async.shared::cta;" ::: "memory");
        TK(6)
        if (r >= D) {
            int it = 0;
            while (true) {
                uint32_t bad = 0;
#pragma unroll
                for (int k = 0; k <= V; k++) bad |= cs[k] - (R - D + 1);
                if (!__any_sync(0xffffffffu, bad >> 20)) break;
                if (++it > SPIN_LIMIT) __trap();
                if (it > 1) __nanosleep(100);
                sample();
            }
        }
        TK(3)
        if (elect()) {
            const uint32_t dB = (HOP == 1 ? dA ^ 0x10000u : dA) + (up ? 8192 : -8192), sm = prim + (lo ? 2 * PB : 0);
            bulk_store(dA, dhi, sm, 8192);
            bulk_store(dB, dhi, HOP == 1 ? sm + 8192 : prim + 68 * PB, 8192);
            if (n0 > 0) bulk_store(dM + (a0 - 64) * PB, mhi, prim + (a0 - lo) * PB, n0);
            if (a1 < (b1 - lo) * PB) bulk_store((dM ^ 4096u) + (uint32_t)((lo - NLO) * PB + a1), mhi, prim + a1, (b1 - lo) * PB - a1);
            asm volatile("cp.async.bulk.commit_group;" ::: "memory");
            if (r != RT - 1) asm volatile("cp.async.bulk.wait_group.read 0;" ::: "memory");
        }
        __syncwarp();
        TK(4)
        prim = HOP == 1 ? prim ^ 0x20000u : prim >= sb + 0x30000u ? sb : prim + (prim - sb) + 0x10000u;
        if (r == RT - 1) break;
        reset<HOP>(done, lane, R + HOP + 1);
        if (HOP == 1) {
            __syncwarp();
            if (lane == 0) mbar_arrive(sb + B_FREE);
        }
        if (RARE(r == D - 1 || r == RT - D - 1)) {
            uint32_t n = NHI, m = NLO;
            if (HOP == 1 && r == RT - D - 1 && lane < 2) {
                const int row0 = role * p.R2, nr = min(p.R2, p.E - row0) & ~7;
                const uint64_t a = lane ? reinterpret_cast<uint64_t>(p.dist + row0) + 15 & ~15ull : reinterpret_cast<uint64_t>(p.m + row0);
                if (nr > 8) asm volatile("cp.async.bulk.prefetch.L2.global [%0], %1;" ::"l"(a), "r"(lane ? nr * 2 - 16 : nr * 8) : "memory");
            }
            if (r < RT - D - 1) {
                int it = 0;
                while (true) {
                    n = ld_rlx32(reinterpret_cast<const uint32_t*>(p.ring + M_CNT + (side << 12)));
                    if ((n & 0xffffu) + (n >> 16) == NB) break;
                    if (++it > SPIN_LIMIT) __trap();
                }
                m = n = min(max(__reduce_or_sync(0xffffffffu, n) & 0xffffu, (uint32_t)NLO), (uint32_t)NHI);
            }
            n0 = (min((int)n, hi) - a0) * PB;
            a1 = (max((int)m, lo) - lo) * PB;
        }
        if (HOP == 2 && RARE(r == RT - LATE)) fence_gpu();
        if (HOP == 1) sample();
        slot_next(dA, st); slot_next(dM, st);
        st = slot_rot(st);
        init = ninit;
    }
    TK_OUT
}

template <int HOP> struct Reader {
    uint32_t lo, hi, st, line;
    uint32_t* cred;
    __device__ __forceinline__ void init(const Params& p, uint32_t sb, int w, int lane, int role, uint32_t base) {
        constexpr int PB = H<HOP>::S * 8;
        const int first = HOP == 1 ? (role >= NG ? NG : 0) + w * J : w * 2 * J;
        const Ring rg(p.ring, lds32(sb + W_PAR), 2 * w + HOP - 1);
        const uint32_t side = lds32(sb + W_SIDE);
        const bool mid = side ? role < 68 : role >= 64;
        const uint32_t i = role - (side ? (mid ? NLO : 68) : (mid ? 64 : 0));
        const uint32_t c = HOP == 1 ? i >> 5 : lane >> 3 & 1, in = (HOP == 1 ? (i & 31) * PB + (lane & 15) * 16 : i * PB + (lane & 7) * 16) + (lane >> 4) * src_off(3);
        lo = (in + (mid ? ((uint32_t)rg.mid ^ side << 12) + c * 1024 : (uint32_t)rg.main + (c << 16) + (side ^ rg.par ^ c ? 4096 : 12288))) ^ slot_off(base % 3);
        hi = __reduce_or_sync(0xffffffffu, (uint32_t)((mid ? rg.mid : rg.main) >> 32));
        st = slot_steps(base);
        line = opaque((HOP == 1 ? 2 * (role % NG) + (lane >> 3 & 1) : role) + (lane & 1) * 2);
        const bool both = first >= NLO && first < NHI;
        cred = lane < 1 + both ? reinterpret_cast<uint32_t*>(rg.main + MISC + (((both ? lane : first >= NG) ^ rg.par) << 12) + cred_off(role)) : nullptr;
    }
    template <int K> __device__ __forceinline__ void load1(uint2 (&v)[J]) const {
        asm volatile("ld.relaxed.gpu.global.v4.u32 {%0,%1,%2,%3}, [%4+%5];" : "=r"(v[2 * K].x), "=r"(v[2 * K].y), "=r"(v[2 * K + 1].x), "=r"(v[2 * K + 1].y)
                     : "l"(mk_ptr(lo, hi)), "n"(src_off(K)) : "memory");
    }
    static __device__ __forceinline__ uint32_t word(const uint2& v) { return HOP == 1 ? v.x : v.y; }
    template <int K> __device__ __forceinline__ void again(uint2 (&v)[J], uint32_t want, uint32_t m0, uint32_t m1, uint32_t grp) const {
        if (__ballot_sync(0xffffffffu, ((word(v[2 * K]) ^ want) & m0) | ((word(v[2 * K + 1]) ^ want) & m1)) & grp) load1<K>(v);
    }
    __device__ __forceinline__ void load(uint2 (&rec)[J]) const { load1<0>(rec); load1<1>(rec); load1<2>(rec); }
    __device__ __forceinline__ void check(uint2 (&rec)[J], uint32_t R, uint32_t ns, int lane TK_ARG) {
        const uint32_t want = H<HOP>::tag(R), mk = H<HOP>::mark(R, line);
        const uint32_t m0 = mk == 0 ? H<HOP>::TAG : 0u, m1 = mk == 1 ? H<HOP>::TAG : 0u;
        int it = 0;
        while (true) {
            uint32_t b0 = 0, b1 = 0;
#pragma unroll
            for (int j = 0; j < J; j += 2) { b0 |= word(rec[j]) ^ want; b1 |= word(rec[j + 1]) ^ want; }
            if (!__any_sync(0xffffffffu, (b0 & m0) | (b1 & m1))) break;
            if (++it > SPIN_LIMIT) __trap();
            __nanosleep(ns);
            TK_CNT(7)
            const uint32_t grp = 0xffu << (lane & 24u);
            again<0>(rec, want, m0, m1, grp); again<1>(rec, want, m0, m1, grp); again<2>(rec, want, m0, m1, grp);
        }
        if (cred) st_rlx32(cred, R + 1);
        __syncwarp();
        slot_next(lo, st);
        st = slot_rot(st);
    }
    __device__ __forceinline__ void finish() const { if (cred) st_rlx32(cred, 0u); }
};

__device__ __forceinline__ uint32_t probe(unsigned char* a, uint32_t zero) {
    *reinterpret_cast<uint4*>(a) = make_uint4(0u, 0u, 0u, 0u);
    *reinterpret_cast<uint4*>(a + 16) = make_uint4(0u, 0u, 0u, 0u);
    uint32_t best = ~0u, v = threadIdx.x, prev = 0;
#pragma unroll
    for (int t = 0; t <= NPROBE + 1; t++) {
        uint32_t now;
        if (t <= NPROBE) asm volatile("atom.relaxed.gpu.global.add.u32 %0, [%1], 1;" : "=r"(v) : "l"(a + (v & zero)) : "memory");
        else asm volatile("red.relaxed.gpu.global.add.u32 [%0], 1;" ::"l"(a + (v & zero)) : "memory");
        asm volatile("mov.u32 %0, %%clock;" : "=r"(now) :: "memory");
        if (t > 1) best = min(best, now - prev);
        prev = now;
    }
    return best;
}
template <bool B> struct BoolC { static constexpr bool value = B; };

__device__ __forceinline__ void stage1(const Params& p, uint32_t sb, const int pos0, int lane, const bool half) {
    typedef H<1> h;
    constexpr int NP = 4;
    static_assert(NPR == NS1 * NP * 32 - NP * 16, "tiles");
    const int RT = p.rounds;
    uint32_t ff = *reinterpret_cast<const uint16_t*>(p.ang_freq) * 0x10001u;
    auto pair_of = [&](int r, int pos) {
        const int q = r < RT - 1 ? (r * NB + blockIdx.x) * NPR + pos : (RT - 1) * NB * NPR + blockIdx.x * p.lastn + pos;
        return pos < (r < RT - 1 ? NPR : r == RT - 1 ? p.lastn : 0) && q < p.T2 ? q : -1;
    };
    uint2 vi[NP], vo[NP]; uint32_t va[NP];
    auto load_edge = [&](int r) {
#pragma unroll
        for (int u = 0; u < NP; u++) {
            const int q = max(pair_of(r, pos0 + u * 32), 0);
            vi[u] = ld_in(p.idx_in + q); vo[u] = ld_in(p.idx_out + q); va[u] = ld_in(p.angle + q);
        }
    };
    if (p.full) {
#pragma unroll
        for (int u = 0; u < NP; u += 2) {
            const int k = ((blockIdx.x * NPR + pos0 + lane) >> 1) + (!u ? 0 : half ? 0x40000000 : 32);
            tex2(p.ta, k, va[u], va[u + 1]); tex4(p.to, k, vo[u], vo[u + 1]); tex4(p.ti, k, vi[u], vi[u + 1]);
        }
    } else load_edge(0);
    if (blockIdx.x == 0 && pos0 == 0 && (p.T & 1)) {
        const int t = p.T - 1;
        slow_triplet(p, reinterpret_cast<const uint32_t*>(p.idx_in)[t], reinterpret_cast<const uint32_t*>(p.idx_out)[t],
                     bf16r(cos_bf(hmul_bf2(reinterpret_cast<const uint16_t*>(p.angle)[t], ff) & 0xffffu)));
    }
    ff = __reduce_or_sync(0xffffffffu, ff);
    bar_sync(BAR_S1, (NS1 + NC) * 32);
    uint32_t R = __reduce_or_sync(0xffffffffu, lds32(sb + W_BASE) & 31u);
    TK_DECL
    auto step = [&](const int r, const int qn, auto edge) {
        constexpr bool EDGE = decltype(edge)::value;
        uint32_t cc[NP], big = 0;
#pragma unroll
        for (int u = 0; u < NP; u++) {
            va[u] = hmul_bf2(va[u], ff);
            cc[u] = pack_bf2(__cosf(bf_lo(va[u])), __cosf(bf_hi(va[u])));
            big |= hmul_bf2(va[u], 0x3d003d00u);
        }
        if (RARE(big & 0x40004000u)) {
#pragma unroll 1
            for (int u = 0; u < NP; u++) {
                const uint32_t a = pick(u, va);
                float c0 = cos_bf(a & 0xffffu), c1 = cos_bf(a >> 16);
                if ((c0 != c0 || c1 != c1) && (EDGE ? pair_of(r, pos0 + u * 32) >= 0 : !half || u < 2)) {
                    const uint2 i2 = pick(u, vi), o2 = pick(u, vo);
                    if (c0 != c0) slow_triplet(p, i2.x, o2.x, c0);
                    if (c1 != c1) slow_triplet(p, i2.y, o2.y, c1);
                }
                const uint32_t v = pack_bf2(c0 != c0 ? 0.f : c0, c1 != c1 ? 0.f : c1);
#pragma unroll
                for (int k = 0; k < NP; k++) if (k == u) cc[k] = v;
            }
        }
        uint32_t bin[2 * NP], x[2 * NP], y[2 * NP];
        uint32_t dep = 0;
        auto loads = [&]() {
            const int q = qn + (dep & p.zero);
#pragma unroll
            for (int u = 0; u < NP; u += 2) {
                const int k = !u ? q : q + (half ? 0x40000000 : 32);
                tex2(p.ta, k, va[u], va[u + 1]); tex4(p.to, k, vo[u], vo[u + 1]); tex4(p.ti, k, vi[u], vi[u + 1]);
            }
        };
#pragma unroll
        for (int j = 0; j < 2 * NP; j++) {
            const uint32_t ii = j & 1 ? vi[j >> 1].y : vi[j >> 1].x, oo = j & 1 ? vo[j >> 1].y : vo[j >> 1].x;
            bin[j] = imul(ii, p.i1);
            y[j] = __byte_perm(ifma(bin[j], p.k1, ii), cc[j >> 1], j & 1 ? 0x7610 : 0x5410);
            const uint32_t bo = imul(oo, p.i2);
            x[j] = __byte_perm(ifma(bo, p.k2, imul(oo, 8.f)), bo, 0x0514);
            dep |= x[j] | y[j];
            if (EDGE && pair_of(r, pos0 + (j >> 1) * 32) < 0) bin[j] = NG + (lane & (NDUM - 1));
        }
        if (!EDGE) loads();
        else load_edge(r + 1);
        const uint32_t init = h::init(R), lim = init + ((EDGE && r == RT - 1 ? h::S : h::CAP) << h::SH);
        TKS(0)
        mbar_wait(sb + B_OPEN, ~R & 1);
        TKS(1)
        bool freed = false;
        uint32_t over = 0;
#pragma unroll
        for (int g = 0; g < 2 * NP; g += NP) if (!g || EDGE || !half) {
            constexpr int G = NP;
            uint32_t ret[G];
            int mx = 0;
#pragma unroll
            for (int j = 0; j < G; j++) ret[j] = atoms_add<h::CNT>(sb + imul(bin[g + j], 4.f), h::INC);
#pragma unroll
            for (int j = 0; j < G; j++) mx = j ? max(mx, (int)ret[j]) : (int)ret[j];
            if (!freed && __any_sync(0xffffffffu, mx >= (int)(init + 0x10000u))) { TKS(2) mbar_wait(sb + B_FREE, ~R & 1); freed = true; TKS(3) }
            TKS(2)
#pragma unroll
            for (int j = 0; j < G; j++) {
                x[g + j] = and_or<h::TAG>(ret[j], x[g + j]);
                put_rec<h::STG>(ret[j], lim, sb + and_or<0x20000u | h::PM>(ret[j], imul(bin[g + j], 256.f)), x[g + j], y[g + j]);
            }
            if (RARE(mx >= (int)lim)) {
#pragma unroll
                for (int j = 0; j < G; j++) if ((int)ret[j] >= (int)lim) over |= 1u << (g + j);
            }
        }
        __syncwarp();
        if (elect()) mbar_arrive(sb + B_FULL);
        R++;
        TKS(4)
#pragma unroll 1
        while (RARE(over)) {
            TK_CNT(7)
            const int j = __ffs(over) - 1;
            over &= over - 1;
            slow_rec1(p, pick(j, x), pick(j, y), pick(j, bin));
        }
        __syncwarp();
    };
#pragma unroll 1
    for (int q = opaque(((NB + blockIdx.x) * NPR + pos0 + lane) >> 1), r = 1; r < p.full; r++, q += NB * NPR / 2) step(r - 1, q, BoolC<false>());
#pragma unroll 1
    for (int r = max(p.full - 1, 0); r < RT; r++) step(r, 0, BoolC<true>());
    TK_OUT
}

__device__ __forceinline__ void stage2(const Params& p, uint32_t sb, int w, int lane, int role, uint32_t base1, uint32_t base) {
    typedef H<2> h;
    const int RT = p.rounds + 1;
    Reader<1> rd;
    rd.init(p, sb, w, lane, role, base1 + 3);
    uint2 rec[J];
#pragma unroll
    for (int j = 0; j < J; j++) rec[j] = null_rec<1>(lane, base1);
    uint32_t kb = sb + 0x10000u, am = 0x10000u | h::PM;
    const float unit = __uint_as_float(__reduce_or_sync(0xffffffffu, lds32(sb + W_UNIT)));
    TK_DECL
#pragma unroll 1
    for (int r = 0; r < RT; r++) {
        rd.check(rec, base1 + r, POLL_NS, lane TK_PASS);
        if (RARE(r == 1)) bar_sync(BAR_TABLE, 2 * NC * 32);
        const uint32_t want = H<1>::tag(base1 + r);
        TKS(0)
        uint2 mv[J];
#pragma unroll
        for (int j = 0; j < J; j++) {
            mv[j] = make_uint2(0u, 0u);
            const uint32_t a = sb + imul(rec[j].y & 0xffffu, 8.f);
            if (!xor_and<0x8e0000u>(rec[j].x, want)) mv[j] = lds64<OFF_M>(a);
        }
        uint32_t fl = 0;
#pragma unroll
        for (int j = 0; j < J; j++) fl |= mv[j].y;
        if (RARE(fl & 0x40000000u)) {
#pragma unroll 1
            for (int j = 0; j < J; j++) {
                const uint2 v = pick(j, mv), w = pick(j, rec);
                if ((v.y & 0x40000000u) && !((w.x ^ want) & 0x8e0000u)) {
                    if (v.x & 0x40000000u) slow_rec1(p, w.x, w.y, lds32(sb + W_ROLE) % NG);
                    else {
                        const float c = bf_hi(w.y), s = __uint_as_float(lds32(sb + W_UNIT)) * 1024.f;
                        side_add(w.x & 0xffu, __byte_perm(w.x, 0u, 0x4413) >> 3, c * (bf_lo(v.x) * s), c * (bf_hi(v.x) * s),
                                 c * (bf_lo(v.y) * s), c * (bf_hi(v.y & 0xbfffffffu) * s));
                    }
                }
            }
#pragma unroll
            for (int j = 0; j < J; j++) if (mv[j].y & 0x40000000u) rec[j].x = 0x800000u;
        }
        uint32_t w0[J], w1[J], bin[J], ret[J];
#pragma unroll
        for (int j = 0; j < J; j++) {
            const float c = bf_hi(rec[j].y), MG = 8194.0f;
            const uint32_t x = rec[j].x;
            const float v[4] = {bf_lo(mv[j].x), bf_hi(mv[j].x), bf_lo(mv[j].y), bf_hi(mv[j].y)};
            w0[j] = and_or<0xf000f000u>(x, __byte_perm(__float_as_uint(fmaf(c, v[0], MG)), __float_as_uint(fmaf(c, v[1], MG)), 0x5410));
            w1[j] = and_or<0xf000f000u>(x << 4, __byte_perm(__float_as_uint(fmaf(c, v[2], MG)), __float_as_uint(fmaf(c, v[3], MG)), 0x5410));
            bin[j] = min(xor_and<0x8e00ffu>(x, want), NB + (lane & (NDUM - 1)));
        }
        const uint32_t lim = h::init(base + r) + (r == RT - 1 ? 0x10000u : 0x20000u);
        rd.load(rec);
        TKS(1)
        mbar_wait(sb + B_OPEN + 8, (r - 1) & 1);
        TKS(2)
#pragma unroll
        for (int j = 0; j < J; j++) ret[j] = atoms_add<h::CNT>(sb + imul(bin[j], 4.f), h::INC);
        uint32_t mx = 0;
#pragma unroll
        for (int j = 0; j < J; j++) {
            w1[j] = and_or<h::TAG>(ret[j], w1[j]);
            put_rec<0>(ret[j], lim, and_xor(ret[j], am, bin[j] * 128 + kb), w0[j], w1[j]);
            mx = __viaddmax_u32(ret[j], 0u - DUMMY, mx);
        }
        __syncwarp();
        if (lane == 0) mbar_arrive(sb + B_FULL + 8);
        TKS(3)
        if (RARE(mx >= lim - DUMMY)) {
            uint32_t over = 0;
#pragma unroll
            for (int j = 0; j < J; j++) if (ret[j] - DUMMY >= lim - DUMMY) over |= 1u << j;
#pragma unroll 1
            do {
                const int j = __ffs(over) - 1;
                over &= over - 1;
                const uint32_t b = pick(j, bin), v = pick(j, ret) - lim, e = v >> h::SH, at = ((v - e * h::INC - (b & 7u) * 16u - h::CAP * 8) >> 7) + e;
                if (max(at, e) < BOXN && r < RT - LATE) g_box[(b * NB + role) * BOX + at] = make_uint2(pick(j, w0), pick(j, w1) | h::TAG);
                else slow_rec2(p, pick(j, w0), pick(j, w1), b, unit);
            } while (over);
        }
        __syncwarp();
        am = am >= 0x30000u ? 0x10000u | h::PM : am + 0x10000u;
        kb ^= am & 0x30000u;
        TKS(4)
    }
    rd.finish();
    TK_OUT
}

__device__ __forceinline__ void add_recs(uint32_t sb, int lane, const uint2 (&rec)[J], uint32_t want) {
    const uint32_t t = 0u - (lane & 1u), k = (t & 1u << 26) - (want >> 4);
    uint32_t o0[J], o1[J], g = 0;
#pragma unroll
    for (int j = 0; j < J; j++) {
        o0[j] = 0; o1[j] = 0;
        if (xor_and<0x7fffffffu>(rec[j].y, want) < 0x0ffc0000u) {
            const uint32_t a = aux_of(rec[j].x, rec[j].y, k);
            const uint32_t v0 = (rec[j].x & 0x0fff0fffu) - 0x08000800u, v1 = (rec[j].y & 0x0fff0fffu) - 0x08000800u;
            o0[j] = atoms_add<OFF_ACC>(sb + a, mux(v0, v1, t));
            o1[j] = atoms_add<OFF_ACC>(sb + (a ^ 4u), mux(v1, v0, t));
        }
    }
#pragma unroll
    for (int j = 0; j < J; j++) g |= o0[j] | o1[j];
    if (RARE(__any_sync(0xffffffffu, g & 0x80008000u))) {
#pragma unroll 1
        for (int j = 0; j < J; j++) {
            const uint2 w = pick(j, rec);
            const uint32_t aux = aux_of(w.x, w.y), p0 = pick(j, o0), p1 = pick(j, o1);
            const float2 a = acc_fix(t ? p1 : p0, w.x & 0x0fff0fffu), b = acc_fix(t ? p0 : p1, w.y & 0x0fff0fffu);
            const float unit = __uint_as_float(lds32(sb + W_UNIT));
            if (xor_and<0x7fffffffu>(w.y, want) < 0x0ffc0000u && (a.x != 0.f || a.y != 0.f || b.x != 0.f || b.y != 0.f)) {
                side_add(lds32(sb + W_ROLE), aux >> 3, a.x * unit, a.y * unit, b.x * unit, b.y * unit);
                sts32(sb + W_WRAP, 1u);
            }
            __syncwarp();
        }
    }
}
__device__ __forceinline__ void stage3(const Params& p, uint32_t sb, int w, int lane, int role, uint32_t base) {
    const int RT = p.rounds + 1;
    Reader<2> rd;
    rd.init(p, sb, w, lane, role, base);
    uint2 rec[J];
    TK_DECL
#pragma unroll 1
    for (int r = 0; r < RT; r++) {
        rd.load(rec);
        rd.check(rec, base + r, r < RT - 2 ? POLL_NS3 : 100, lane TK_PASS);
        RTS((r & 127) == 41 && w == 0, 1 + (r >> 7))
        TK(0)
        add_recs(sb, lane, rec, H<2>::tag(base + r));
        TK(1)
        if (RARE((uint32_t)(r - (RT - LATE + 1)) < 2u)) {
            static_assert(BOX == 32, "box");
            float4* box = reinterpret_cast<float4*>(g_box) + (lds32(sb + W_ROLE) * NB + (w * 2 + r - (RT - LATE + 1)) * J) * (BOX / 2) + lane;
            TKY(0)
#pragma unroll
            for (int j = 0; j < J / 2; j++) {
                const float4 v = ld_rlx128f(box + j * 32);
                rec[2 * j] = make_uint2(__float_as_uint(v.x), __float_as_uint(v.y)); rec[2 * j + 1] = make_uint2(__float_as_uint(v.z), __float_as_uint(v.w));
            }
#pragma unroll
            for (int j = 0; j < J / 2; j++) if (rec[2 * j].x) box[j * 32] = make_float4(0.f, 0.f, 0.f, 0.f);
            add_recs(sb, lane, rec, H<2>::TAG);
            TKY(1)
        }
    }
    rd.finish();
    TK_OUT
}

__device__ __forceinline__ uint32_t row_max(uint32_t x, uint32_t y) {
    const uint32_t mx = __vmaxu2(x & 0x7fff7fffu, y & 0x7fff7fffu);
    return max(mx & 0xffffu, mx >> 16);
}
__device__ __forceinline__ uint32_t amax2(uint32_t a, uint32_t b) {
    uint32_t r; asm("max.NaN.xorsign.abs.bf16x2 %0, %1, %2;" : "=r"(r) : "r"(a), "r"(b)); return r;
}
constexpr int NTAB = 9, TABC = 2 * NC * 32 * 16;
__device__ __forceinline__ void load_piece(const Params& p, uint32_t sb, int role, int i) {
    const int r0 = (role >= NG ? role - NG : role) * p.R1, n = max(min(min(p.R1, p.E - r0) * 8 - i * TABC, TABC), 0);
    asm volatile("mbarrier.arrive.expect_tx.shared::cta.b64 _, [%0], %1;" ::"r"(sb + B_TAB + i * 8), "r"(n) : "memory");
    if (n) asm volatile("cp.async.bulk.shared::cluster.global.mbarrier::complete_tx::bytes [%0], [%1], %2, [%3];"
                        ::"r"(sb + OFF_M + i * TABC), "l"(p.m + r0 + i * (TABC / 8)), "r"(n), "r"(sb + B_TAB + i * 8) : "memory");
}
static_assert(NTAB * TABC >= R1MAX * 8 && NTAB * TABC - TABC / 2 <= R1MAX * 8, "table");
constexpr int EWIN = 5;

__global__ void __launch_bounds__(NTHR, 1) fused_kernel(const Params p) {
    const int tid = threadIdx.x, lane = tid & 31;
    const int hw = __reduce_max_sync(0xffffffffu, tid >> 5);
    const uint32_t sb = __reduce_or_sync(0xffffffffu, (uint32_t)__cvta_generic_to_shared(smem));
    TKX(0)
    RTS(tid == 0, 0)
    uint32_t cta;
    asm volatile("mov.u32 %0, %%ctaid.x;" : "=r"(cta));
    if (hw != W_M1 && hw != W_M2) {
        const int job = hw < W_M1 ? hw : hw - 1;
        if (lane == 0 && job < 2 * NPAGE + 2)
            sts32(sb + OFF_PROBE + job * 4, probe(p.ring + (size_t)max(job / 2 - 1, 0) * PAGE + PROBE + (cta & 31) * 128 + (cta >> 5 & 3) * 16384 + (cta >> 7 << 20) +
                                                  ((job & 1) << 12 ^ (job < 2 ? 0x3000 : 0)), p.zero));
        if (job < 4) bar_arrive(BAR_SIDE, 5 * 32); else bar_arrive(BAR_PROBE, 27 * 32);
        TKX(1)
    }
    if (hw < NS1) {
        stage1(p, sb, hw * 128 + lane, lane, hw == NS1 - 1);
    } else if (hw == W_M1) {
        const uint32_t epoch = ld_rlx32(reinterpret_cast<const uint32_t*>(p.ring + M_BASE)) ^ 33u;
        if (lane == 0) {
            if (sb & 255u) __trap();
            mbar_init(sb + B_FULL, NS1); mbar_init(sb + B_OPEN, 1); mbar_init(sb + B_FREE, 1); mbar_init(sb + B_TFREE, NC); mbar_init(sb + B_FLAG, 32); mbar_init(sb + B_INIT, 1); sts32(sb + W_ITEM, NS1);
            for (int i = 0; i < NTAB; i++) mbar_init(sb + B_TAB + i * 8, 1);
            asm volatile("fence.proxy.async.shared::cta;" ::: "memory");
        }
        const uint32_t base = __reduce_or_sync(0xffffffffu, epoch) & 31u;
        if (lane == 0) { sts32(sb + W_BASE, epoch); sts64(sb + W_NLIST, 0u, 0u); }
        if (lane == 0 && (base & 1u)) { mbar_arrive(sb + B_OPEN); mbar_arrive(sb + B_FREE); }
        bar_arrive(BAR_BASE, (NC + 1) * 32);
        TKY(5)
        bar_sync(BAR_SIDE, 5 * 32);
        TKY(6)
        {
            const uint2 la = lds64<OFF_PROBE>(sb), lb = lds64<OFF_PROBE + 8>(sb);
            const uint32_t side = min(la.y, lb.y) < min(la.x, lb.x);
            uint32_t v = 0;
            if (lane == 0) {
                asm volatile("atom.relaxed.gpu.global.add.u32 %0, [%1], %2;" : "=r"(v) : "l"(p.ring + M_CNT), "r"(side ? 0x10000u : 1u) : "memory");
                asm volatile("red.relaxed.gpu.global.add.u32 [%0], %1;" ::"l"(p.ring + M_CNT + 4096), "r"(side ? 0x10000u : 1u) : "memory");
            }
            bar_sync(BAR_PROBE, 27 * 32);
            const uint2 l = lds64<OFF_PROBE + 8>(sb + min(lane, NPAGE - 1) * 8);
            const uint32_t mine = (__ballot_sync(0xffffffffu, (l.y < l.x) != side) & ~1u) | 0x80000000u;
            if (lane == 0) {
                uint32_t par;
                asm volatile("atom.relaxed.gpu.global.cas.b32 %0, [%1], 0, %2;" : "=r"(par) : "l"(p.ring + M_PAR), "r"(mine) : "memory");
                const uint32_t role = side ? NB - 1 - (v >> 16) : v & 0xffffu;
#pragma unroll 1
                for (int i = 0; i < AHEAD; i++) load_piece(p, sb, role, i);
                sts32(sb + W_ROLE, role); sts32(sb + W_SIDE, role < NLO ? 0u : role >= NHI ? 1u : side);
                sts32(sb + W_END, (epoch | 1023u) + 1u + (base + p.rounds) % 24u + ((epoch >> 5 & 31u) + p.rounds + 1) % 24u * 32u);
                sts32(sb + W_PAR, par ? par : mine);
            }
            TKX(2)
        }
        bar_arrive(BAR_PAR, (2 * NC + 2) * 32);
        manager<1>(p, sb, opaque(lane), __reduce_max_sync(0xffffffffu, lds32(sb + W_ROLE)), base);
        asm volatile("cp.async.bulk.wait_group 0;" ::: "memory");
        bar_arrive(BAR_H1, (NS1 + 1) * 32);
        TKX(4)
        {
            const int role = lds32(sb + W_ROLE);
#pragma unroll 1
            for (int i = lane * 16; i < DROW; i += NPF * 512) {
                float4 f[NPF];
#pragma unroll
                for (int u = 0; u < NPF; u++) f[u] = ld_rlx128f(reinterpret_cast<const float4*>(g_dirty + role * DROW + i + u * 512));
#pragma unroll
                for (int u = 0; u < NPF; u++) {
                    if (__float_as_uint(f[u].x) | __float_as_uint(f[u].y)) prefetch_l2(g_ovf + role * RPAD + i + u * 512);
                    if (__float_as_uint(f[u].z) | __float_as_uint(f[u].w)) prefetch_l2(g_ovf + role * RPAD + i + u * 512 + 8);
                }
            }
        }
        bar_sync(BAR_DONE, (NE + 1) * 32);
        TKY(0)
        const uint32_t flag = lds32(sb + W_END) >> 10 & 0xffffu;
        if (lane < 2) {
            fence_gpu();
            asm volatile("st.relaxed.gpu.global.u16 [%0], %1;" ::"l"(p.ring + M_FLAG + lane * 4096 + blockIdx.x * 2), "h"((uint16_t)flag) : "memory");
        }
        TKY(1)
        __syncwarp();
        bar_arrive(BAR_ROWS, 64);
        wait_flags(p, sb, lane, flag * 0x10001u);
        TKX(5)
        mbar_arrive(sb + B_FLAG);
        if (blockIdx.x == 0) {
            if (lane == 0) *reinterpret_cast<uint32_t*>(p.ring + M_BASE) = lds32(sb + W_END) ^ 33u;
            if (lane < 3) *reinterpret_cast<uint32_t*>(p.ring + (lane & 2 ? M_PAR : M_CNT + (lane & 1) * 4096)) = 0;
        }
    } else if (hw == W_M2) {
        uint2 sm[16];
#pragma unroll
        for (int i = 0; i < 8; i++) ld_in4(p.m + 2 * min((i * 8 + (lane >> 2)) * (p.E >> 7) + (lane & 3), (p.E >> 1) - 1), sm[2 * i], sm[2 * i + 1]);
        const float wd = __bfloat162float(lane & 16 ? p.w_up[lane & 15] : p.w_down[lane & 15]);
        const uint16_t* wg = reinterpret_cast<const uint16_t*>(lane & 16 ? p.w_rbf : p.w_sbf) + (lane & 3) * 8 + (lane >> 2 & 3);
        const uint16_t* cp = reinterpret_cast<const uint16_t*>(p.centers) + (lane & 3) * 2;
        const uint32_t w0 = __ldg(wg), w1 = __ldg(wg + 4), c0 = __ldg(cp), c1 = __ldg(cp + 1);
        if (lane == 0) { mbar_init(sb + B_FULL + 8, NC); mbar_init(sb + B_OPEN + 8, 1); mbar_init(sb + B_ROWS, 1); }
        sts128<OFF_HIST>(sb + lane * 16, make_uint4(0u, 0u, 0u, 0u)); sts128<OFF_HIST + 512>(sb + lane * 16, make_uint4(0u, 0u, 0u, 0u));
        __syncwarp();
#pragma unroll
        for (int i = 0; i < 16; i++) atoms_add<OFF_HIST>(sb + (row_max(sm[i].x, sm[i].y) >> 7) * 4, 1u);
        __syncwarp();
        uint32_t best = 0;
#pragma unroll 1
        for (int e = 11 + lane; e <= 230; e += 32) {
            uint32_t c = 0;
#pragma unroll
            for (int i = 0; i < EWIN; i++) c += lds32(sb + OFF_HIST + (e - i) * 4);
            best = max(best, c << 8 | (255 - e));
        }
        const uint32_t e = 255 - (__reduce_max_sync(0xffffffffu, best) & 255u);
        if (lane == 0) { sts32(sb + W_EXP, e); sts32(sb + W_UNIT, (e - 10) << 23); }
        reinterpret_cast<float*>(smem + OFF_WSM)[lane] = wd;
        const int wi = (lane & 4) * 4 + (lane & 1) * 8 + (lane & 2) + (lane >> 3 & 1);
        const uint32_t fr = __byte_perm(__float_as_uint(__shfl_sync(0xffffffffu, wd, wi)), __float_as_uint(__shfl_sync(0xffffffffu, wd, wi + 4)), 0x7632);
        if (lane < 16) sts32(sb + OFF_WB + lane * 4, fr);
        sts64(sb + OFF_WG + lane * 8, w0 | w1 << 16, c0 | c1 << 16);
        TKY(5)
        bar_sync(BAR_PAR, (2 * NC + 2) * 32);
        if (lane == 0) mbar_arrive(sb + B_INIT);
        manager<2>(p, sb, opaque(lane), __reduce_max_sync(0xffffffffu, lds32(sb + W_ROLE)), __reduce_or_sync(0xffffffffu, lds32(sb + W_BASE)) >> 5 & 31u);
        TKX(4)
        asm volatile("cp.async.bulk.wait_group.read 0;" ::: "memory");
        bar_sync(BAR_ROWS, 64);
        if (lane == 0) {
            const int row0 = lds32(sb + W_ROLE) * p.R2, np = min(p.R2, p.E - row0) >> 1, off = row0 * 8 & 127;
            asm volatile("mbarrier.arrive.expect_tx.shared::cta.b64 _, [%0], %1;" ::"r"(sb + B_ROWS), "r"(max(np, 0) * 16 + (max(np, 0) + NG0 - 1) / NG0 * off) : "memory");
#pragma unroll 1
            for (int k = 0; k < np; k += NG0)
                asm volatile("cp.async.bulk.shared::cluster.global.mbarrier::complete_tx::bytes [%0], [%1], %2, [%3];"
                             ::"r"(sb + H<2>::win(k / NG0)), "l"(p.m + (row0 - off / 8 + 2 * k)), "r"(min(np - k, NG0) * 16 + off), "r"(sb + B_ROWS) : "memory");
        }
        asm volatile("cp.async.bulk.wait_group 0;" ::: "memory");
    } else {
        const int w = __reduce_max_sync(0xffffffffu, hw < W_M1 ? hw - NS1 : hw - W_M1 - 1), ct = w * 32 + lane;
        if (hw < W_M1) {
            bar_sync(BAR_BASE, (NC + 1) * 32);
            const uint32_t b1 = lds32(sb + W_BASE) & 31u, b2 = lds32(sb + W_BASE) >> 5 & 31u;
            if (ct < NG + NDUM) sts32(sb + OFF_CNT1 + ct * 4, ct < NG ? H<1>::init(b1) + (ct & 7) * 16 : DUMMY);
            if (ct <= NB + NDUM) sts32(sb + OFF_CNT2 + ct * 4, ct < NB ? H<2>::init(b2) + (ct & 7) * 16 : DUMMY);
            fill<1>(sb + OFF_H1 + H<1>::win(b1), ct, b1); fill<1>(sb + OFF_H1 + H<1>::win(b1 + 1), ct, b1 + 1);
            bar_arrive(BAR_S1, (NS1 + NC) * 32);
#pragma unroll
            for (int i = 0; i < 3; i++) fill<2>(sb + H<2>::win(i), ct, b2 + i);
        }
        bar_sync(BAR_PAR, (2 * NC + 2) * 32);
        TKY(4)
        const int role = __reduce_max_sync(0xffffffffu, lds32(sb + W_ROLE));
        const uint32_t epoch = __reduce_or_sync(0xffffffffu, lds32(sb + W_BASE));
        if (hw < W_M1) {
            for (int i = ct; i < R2MAX / 2; i += NC * 32) reinterpret_cast<uint4*>(smem + OFF_ACC)[i] = make_uint4(0x40004000u, 0x40004000u, 0x40004000u, 0x40004000u);
            mbar_wait(sb + B_TAB + KDRY * 8, 0);
            stage2(p, sb, w, opaque(lane), role, (epoch & 31u) - 1u, epoch >> 5 & 31u);
        } else {
            const int e = lds32(sb + W_EXP);
            const uint32_t sc = (uint32_t)(254 - e) * 0x800080u, top = (e << 7 | 0x807fu) * 0x10001u;
            auto conv = [&](uint32_t& x, uint32_t& y) {
                const uint32_t mx = row_max(x, y);
                const int d = e - (int)(mx >> 7);
                x = hmul_bf2(x, sc); y = hmul_bf2(y, sc);
                if (d >= EWIN) y |= 0x40000000u;
                if (d < 0 || (d >= EWIN && e > 127)) { x = 0x40000000u; y = x; }
                if (mx == 0) { x = 0; y = 0; }
            };
#pragma unroll 1
            for (int i = 0; i < NTAB; i++) {
                mbar_wait(sb + B_TAB + i * 8, 0);
                if (ct == 0 && i < NTAB - AHEAD) load_piece(p, sb, role, i + AHEAD);
                const uint32_t t = sb + OFF_M + i * TABC + ct * 16, t1 = t + TABC / 2 < sb + OFF_M + R1MAX * 8 ? t + TABC / 2 : t;
                uint4 v[2] = {lds128(t), lds128(t1)};
                uint32_t ok = ~0u;
#pragma unroll
                for (int u = 0; u < 2; u++) {
                    const uint32_t a = amax2(v[u].x, v[u].y), b = amax2(v[u].z, v[u].w), mx = amax2(__byte_perm(a, b, 0x5410), __byte_perm(a, b, 0x7632)) & 0x7fff7fffu;
                    ok &= (top - mx) ^ (top - EWIN * 0x800080u - mx);
                }
                if (RARE(~ok & 0x80008000u)) {
#pragma unroll 1
                    for (int u = 0; u < 4; u++) {
                        conv(v[0].x, v[0].y);
                        const uint2 f = make_uint2(v[0].x, v[0].y);
                        v[0] = make_uint4(v[0].z, v[0].w, v[1].x, v[1].y); v[1] = make_uint4(v[1].z, v[1].w, f.x, f.y);
                    }
                } else {
#pragma unroll
                    for (int u = 0; u < 2; u++) v[u] = make_uint4(hmul_bf2(v[u].x, sc), hmul_bf2(v[u].y, sc), hmul_bf2(v[u].z, sc), hmul_bf2(v[u].w, sc));
                }
                sts128<0>(t, v[0]); sts128<0>(t1, v[1]);
                __syncwarp();
            }
            TKX(3)
            bar_sync(BAR_TABLE, 2 * NC * 32);
            stage3(p, sb, w, opaque(lane), role, epoch >> 5 & 31u);
            TKX(4)
            bar_sync(BAR_ACC, (NE + NC) * 32);
            if (!lds32(sb + W_WRAP)) {
                int i;
                asm volatile("mov.u32 %0, %%tid.x;" : "=r"(i));
                const int ro = lds32(sb + W_ROLE);
#pragma unroll 1
                for (i -= (W_M1 + 1) * 32; i < DROW / 16; i += NC * 32) {
                    float4* f = reinterpret_cast<float4*>(g_dirty + ro * DROW) + i;
                    const float4 v = ld_rlx128f(f);
                    uint32_t m = __float_as_uint(v.x) | __float_as_uint(v.y) << 1 | __float_as_uint(v.z) << 2 | __float_as_uint(v.w) << 3;
                    if (m) *f = make_float4(0.f, 0.f, 0.f, 0.f);
#pragma unroll 1
                    for (; m; m &= m - 1) {
                        const int b = __ffs(m) - 1;
                        g_ovf[ro * RPAD + i * 16 + (b & 3) * 4 + (b >> 3)] = make_float4(0.f, 0.f, 0.f, 0.f);
                    }
                }
            }
        }
    }
    if (hw < W_M1) {
        bar_arrive(BAR_DONE, (NE + 1) * 32);
        __syncwarp();
        TKX(4)
        finish_rows(p, sb, hw < NS1);
    }
}

__global__ void fb_scatter(const uint2* __restrict__ m, const int* __restrict__ idx_in, const int* __restrict__ idx_out,
                           const uint16_t* __restrict__ angle, const __nv_bfloat16* __restrict__ ang_freq, int T, int e0, int e1) {
    const uint32_t fb = *reinterpret_cast<const uint16_t*>(ang_freq);
    for (long long t = blockIdx.x * (long long)blockDim.x + threadIdx.x; t < T; t += (long long)gridDim.x * blockDim.x) {
        int o = idx_out[t];
        if (o < e0 || o >= e1) continue;
        float c = bf16r(cos_bf(hmul_bf2(angle[t], fb) & 0xffffu));
        uint2 v = __ldg(m + idx_in[t]);
        red4(&g_ovf[o - e0], c * bf_lo(v.x), c * bf_hi(v.x), c * bf_lo(v.y), c * bf_hi(v.y));
    }
}
__global__ void fb_final(const Params p, int e0, int e1) {
    int e = e0 + blockIdx.x * blockDim.x + threadIdx.x;
    if (e >= e1) return;
    float4 a4 = g_ovf[e - e0];
    g_ovf[e - e0] = make_float4(0.f, 0.f, 0.f, 0.f);
    float a[4] = {a4.x, a4.y, a4.z, a4.w};
    float d = __bfloat162float(p.dist[e]);
    float g[4] = {0, 0, 0, 0}, h[4] = {0, 0, 0, 0};
    for (int r = 0; r < 8; r++) {
        float df = bf16r(d - __bfloat162float(p.centers[r]));
        float rb = bf16r(expf(bf16r(-10.0f * bf16r(df * df))));
        for (int k = 0; k < 4; k++) {
            g[k] += rb * __bfloat162float(p.w_sbf[r * 4 + k]);
            h[k] += rb * __bfloat162float(p.w_rbf[r * 4 + k]);
        }
    }
    float ag[4];
    for (int k = 0; k < 4; k++) {
        float s = 0.f;
        for (int j = 0; j < 4; j++) s += a[j] * __bfloat162float(p.w_down[j * 4 + k]);
        ag[k] = bf16r(s * g[k]);
    }
    uint2 mv = p.m[e];
    float mm[4] = {bf_lo(mv.x), bf_hi(mv.x), bf_lo(mv.y), bf_hi(mv.y)};
    __nv_bfloat16 o[4];
    for (int k = 0; k < 4; k++) {
        float u = 0.f;
        for (int j = 0; j < 4; j++) u += ag[j] * __bfloat162float(p.w_up[j * 4 + k]);
        o[k] = __float2bfloat16_rn(mm[k] + bf16r(bf16r(u) * bf16r(h[k])));
    }
    p.out[e] = *reinterpret_cast<uint2*>(o);
}

}

static cudaTextureObject_t make_tex(const void* ptr, size_t bytes, int words) {
    cudaResourceDesc rd = {}; cudaTextureDesc td = {};
    rd.resType = cudaResourceTypeLinear; rd.res.linear.devPtr = const_cast<void*>(ptr); rd.res.linear.sizeInBytes = bytes;
    rd.res.linear.desc = cudaCreateChannelDesc(32, words > 1 ? 32 : 0, words > 2 ? 32 : 0, words > 2 ? 32 : 0, cudaChannelFormatKindUnsigned);
    td.readMode = cudaReadModeElementType;
    cudaTextureObject_t t = 0;
    if (cudaCreateTextureObject(&t, &rd, &td, nullptr) != cudaSuccess) { t = 0; (void)cudaGetLastError(); }
    return t;
}

extern "C" void kernel_launch(void* const* d_in, const int* in_sizes, int n_in, void* d_out, int out_size) {
    typedef const __nv_bfloat16* B;
    Params p;
    p.m = (const uint2*)d_in[0]; p.idx_in = (const uint2*)d_in[1]; p.idx_out = (const uint2*)d_in[2]; p.dist = (B)d_in[3];
    p.angle = (const uint32_t*)d_in[4]; p.centers = (B)d_in[5]; p.ang_freq = (B)d_in[6]; p.w_rbf = (B)d_in[7]; p.w_sbf = (B)d_in[8];
    p.w_down = (B)d_in[9]; p.w_up = (B)d_in[10]; p.out = (uint2*)d_out;
    p.E = in_sizes[3]; p.T = in_sizes[1]; p.T2 = p.T >> 1; p.zero = 0;
    p.R1 = p.R2 = p.rounds = p.lastn = p.full = 0; p.i1 = p.i2 = p.k1 = p.k2 = 0.f;
    static int ok = -1;
    static unsigned char* ring = nullptr;
    if (ok < 0) {
        void* ra = nullptr;
        cudaGetSymbolAddress(&ra, g_ring);
        ring = reinterpret_cast<unsigned char*>(((uintptr_t)ra + PAGE - 1) & ~(uintptr_t)(PAGE - 1));
        int dev = 0, sms = 0, occ = 0;
        cudaGetDevice(&dev);
        cudaDeviceGetAttribute(&sms, cudaDevAttrMultiProcessorCount, dev);
        cudaError_t e = cudaFuncSetAttribute(fused_kernel, cudaFuncAttributeMaxDynamicSharedMemorySize, SMEM_BYTES);
        if (e == cudaSuccess) e = cudaOccupancyMaxActiveBlocksPerMultiprocessor(&occ, fused_kernel, NTHR, SMEM_BYTES);
        ok = (e == cudaSuccess && occ >= 1 && sms >= NB) ? 1 : 0;
        (void)cudaGetLastError();
    }
    p.ring = ring;
    static cudaTextureObject_t tx[3];
    static const void* of[3];
    static int of_t = -1;
    if (of[0] != d_in[1] || of[1] != d_in[2] || of[2] != d_in[4] || of_t != p.T) {
        tx[0] = make_tex(p.idx_in, (size_t)(p.T >> 2) * 16, 4); tx[1] = make_tex(p.idx_out, (size_t)(p.T >> 2) * 16, 4); tx[2] = make_tex(p.angle, (size_t)(p.T >> 2) * 8, 2);
        of[0] = d_in[1]; of[1] = d_in[2]; of[2] = d_in[4]; of_t = p.T;
    }
    p.ti = tx[0]; p.to = tx[1]; p.ta = tx[2];
    const bool fused = ok == 1 && p.E <= EMAX && p.E >= 2 * NB && p.E % 2 == 0 && p.T >= 2;
    if (fused) {
        p.R1 = ((p.E + NG - 1) / NG + 1) & ~1;
        if (p.R1 > 1024) p.R1 = (p.R1 + 15) & ~15;
        p.R2 = ((p.E + NB - 1) / NB + 1) & ~1;
        p.i1 = nextafterf(1.f / p.R1, 2.f); p.i2 = nextafterf(1.f / p.R2, 2.f); p.k1 = -(float)p.R1; p.k2 = -8.f * p.R2;
        const int per = NB * NPR;
        int full = p.T2 / per, rest = p.T2 - full * per;
        p.full = p.ti && p.to && p.ta ? full : 0;
        p.lastn = (rest + NB - 1) / NB;
        if (p.lastn > NPR / 2) { full++; p.lastn = 0; }
        if (full < D) { full = D; p.lastn = 0; }
        p.rounds = full + 1;
        fused_kernel<<<NB, NTHR, SMEM_BYTES>>>(p);
    } else {
        for (int e0 = 0; e0 < p.E; e0 += EMAX) {
            int e1 = p.E - e0 < EMAX ? p.E : e0 + EMAX;
            fb_scatter<<<1056, 256>>>(p.m, (const int*)d_in[1], (const int*)d_in[2], (const uint16_t*)d_in[4], p.ang_freq, p.T, e0, e1);
            fb_final<<<(e1 - e0 + 255) / 256, 256>>>(p, e0, e1);
        }
    }
}
```

```cpp
#include <cuda_runtime.h>
#include <cuda_bf16.h>
#include <stdint.h>
#include <math.h>

#define RARE(x) __builtin_expect(!!(x), 0)
namespace {

constexpr int NB = 132, NG = 66;
constexpr int R2MAX = 6062, R1MAX = 12128;
constexpr int EMAX = NB * R2MAX;
constexpr int NTHR = 1024;
constexpr int NS1 = 8, NC = 11, J = 6;
constexpr int NPR = 960;
constexpr int D = 3;
constexpr int WIN = 16896;
constexpr int NDUM = 16;
constexpr uint32_t DUMMY = 0xc0000000u;
constexpr int AHEAD = 3, KDRY = 4, NPF = 6, NPROBE = 2, POLL_NS = 200, POLL_NS3 = 400;

constexpr int OFF_ACC = WIN, OFF_BAR = OFF_ACC + R2MAX * 8;
constexpr int OFF_H1 = 0x10000 + WIN, OFF_M = OFF_H1 + WIN, OFF_PROBE = OFF_M + R1MAX * 8;
constexpr int OFF_CNT1 = OFF_H1 + 0x20000 + WIN, OFF_CNT2 = OFF_CNT1 + (NG + NDUM + 2) * 4;
constexpr int OFF_HIST = OFF_ACC;
constexpr int OFF_WSM = OFF_CNT2 + (NB + NDUM) * 4 + 16;
constexpr int OFF_WB = OFF_WSM + 128, OFF_WG = OFF_WB + 64;
constexpr int SMEM_BYTES = OFF_WG + 256;
static_assert(SMEM_BYTES <= 232448 && OFF_BAR + 64 <= 0x10000 && OFF_PROBE + 256 <= 0x30000, "smem");
static_assert(OFF_BAR % 8 == 0 && OFF_WSM % 16 == 0 && OFF_CNT2 % 16 == 0, "align");
static_assert(NC * J == NG && NC * 32 * 6 * 16 == 2 * WIN, "shape");

template <int HOP> struct H {
    static constexpr int S = HOP == 1 ? 32 : 16, NBIN = HOP == 1 ? NG : NB, CAP = 2 * S, SH = HOP == 1 ? 11 : 12;
    static constexpr int TB = HOP == 1 ? 17 : 28, CNT = HOP == 1 ? OFF_CNT1 : OFF_CNT2, STG = HOP == 1 ? OFF_H1 : 0;
    static constexpr uint32_t INC = (1u << SH) + 8u, PM = (S - 1) * 8, TAG = 7u << TB;
    static __device__ __forceinline__ uint32_t tag(uint32_t R) { return R << TB & TAG; }
    static __device__ __forceinline__ uint32_t init(uint32_t R) { return tag(R) | ((1u << TB) - 0x10000u); }
    static __device__ __forceinline__ uint32_t mark(uint32_t R, uint32_t line) { return ((HOP == 1 ? R >> 1 : R) + line) & 3u; }
    static __device__ __forceinline__ uint32_t win(int r) { return HOP == 1 ? (r & 1) << 17 : (0x310u >> (r % 3 * 4) & 3u) << 16; }
};

constexpr uint32_t PAGE = 1u << 21;
constexpr int NPAGE = NC + 2;
__device__ __align__(256) unsigned char g_ring[(size_t)(NPAGE + 1) * PAGE];
constexpr int MISC = 0xa0000;
constexpr int M_CNT = MISC + 1024, M_PAR = M_CNT + 4;
constexpr int M_BASE = M_CNT + 8;
constexpr int M_FLAG = MISC + 2048;
constexpr int PROBE = MISC + 0x40000;
__device__ __forceinline__ uint32_t cred_off(uint32_t role) { return role * 4 + min(role >> 5, 3u) * (16384 - 128); }
struct Ring {
    uint64_t main, mid;
    uint32_t par;
    __device__ __forceinline__ Ring(const unsigned char* ring, uint32_t pars, int k) {
        main = reinterpret_cast<uint64_t>(ring) + ((uint64_t)k << 20);
        par = pars >> (k >> 1) & 1u;
        mid = reinterpret_cast<uint64_t>(ring) + (uint64_t)NC * PAGE + (((k >> 3 << 20) + (k >> 2 & 1) * 0x11000u + (k & 1) * 2048) ^ (k >> 1 & 1) * 0x3000u ^ (pars >> (NC + (k >> 4)) & 1u) << 12);
    }
};
constexpr int NLO = 60, NHI = 72;
__host__ __device__ constexpr uint32_t src_off(int j) { return (j % 3) << 14 | (j / 3) << 18; }
__device__ __forceinline__ uint32_t slot_off(uint32_t s) { return (0xa930u >> s * 4 & 15u) << 16; }
__device__ __forceinline__ uint32_t slot_steps(uint32_t R) { return (uint32_t)(0x30a09030aull >> (2 - R % 3) * 8) & 0xffffffu; }
__device__ __forceinline__ void slot_next(uint32_t& a, uint32_t st) { a ^= st & 0xf0000u; }
__device__ __forceinline__ uint32_t slot_rot(uint32_t st) { return __byte_perm(st, 0u, 0x4102); }
constexpr int RPAD = 6064, DROW = 6144;
__device__ __align__(128) uint8_t g_dirty[NB * DROW];
constexpr int BOX = 32, BOXN = 24, LATE = 8;
__device__ __align__(128) uint2 g_box[NB * NB * BOX];
__device__ __align__(128) float4 g_ovf[NB * RPAD];

struct Params {
    const uint2* m; const uint2* idx_in; const uint2* idx_out; const __nv_bfloat16* dist; const uint32_t* angle;
    const __nv_bfloat16* centers; const __nv_bfloat16* ang_freq; const __nv_bfloat16* w_rbf; const __nv_bfloat16* w_sbf;
    const __nv_bfloat16* w_down; const __nv_bfloat16* w_up; uint2* out; unsigned char* ring;
    cudaTextureObject_t ti, to, ta;
    int E, T, T2, R1, R2, rounds, lastn, full; uint32_t zero; float i1, i2, k1, k2;
};

__device__ __forceinline__ float bf16r(float x) { return __bfloat162float(__float2bfloat16_rn(x)); }
__device__ __forceinline__ float bf_lo(uint32_t v) { return __uint_as_float(v << 16); }
__device__ __forceinline__ float bf_hi(uint32_t v) { return __uint_as_float(v & 0xffff0000u); }
__device__ __forceinline__ void red4(float4* a, float x, float y, float z, float w) {
    asm volatile("red.global.add.v4.f32 [%0], {%1,%2,%3,%4};" ::"l"(a), "f"(x), "f"(y), "f"(z), "f"(w) : "memory");
}
__device__ __forceinline__ void bar_sync(int id, int n) { __syncwarp(); asm volatile("bar.sync %0, %1;" ::"r"(id), "r"(n) : "memory"); }
__device__ __forceinline__ void bar_arrive(int id, int n) { __syncwarp(); asm volatile("bar.arrive %0, %1;" ::"r"(id), "r"(n) : "memory"); }
template <int OFF> __device__ __forceinline__ uint32_t atoms_add(uint32_t addr, uint32_t v) {
    uint32_t r; asm volatile("atom.shared.add.u32 %0, [%1+%3], %2;" : "=r"(r) : "r"(addr), "r"(v), "n"(OFF) : "memory"); return r;
}
__device__ __forceinline__ void sts64(uint32_t addr, uint32_t x, uint32_t y) {
    asm volatile("st.shared.v2.u32 [%0], {%1,%2};" ::"r"(addr), "r"(x), "r"(y) : "memory");
}
__device__ __forceinline__ void sts32(uint32_t addr, uint32_t x) { asm volatile("st.shared.u32 [%0], %1;" ::"r"(addr), "r"(x) : "memory"); }
template <int OFF = 0> __device__ __forceinline__ uint2 lds64(uint32_t addr) {
    uint2 v; asm volatile("ld.shared.v2.u32 {%0,%1}, [%2+%3];" : "=r"(v.x), "=r"(v.y) : "r"(addr), "n"(OFF) : "memory"); return v;
}
__device__ __forceinline__ uint32_t lds32(uint32_t addr) {
    uint32_t v; asm volatile("ld.shared.u32 %0, [%1];" : "=r"(v) : "r"(addr) : "memory"); return v;
}
template <int OFF> __device__ __forceinline__ void sts128(uint32_t a, const uint4& v) {
    asm volatile("st.shared.v4.u32 [%0+%5], {%1,%2,%3,%4};" ::"r"(a), "r"(v.x), "r"(v.y), "r"(v.z), "r"(v.w), "n"(OFF) : "memory");
}
__device__ __forceinline__ uint4 lds128(uint32_t a) {
    uint4 v; asm volatile("ld.shared.v4.u32 {%0,%1,%2,%3}, [%4];" : "=r"(v.x), "=r"(v.y), "=r"(v.z), "=r"(v.w) : "r"(a) : "memory"); return v;
}
__device__ __forceinline__ uint32_t ld_rlx32(const uint32_t* p) {
    uint32_t v; asm volatile("ld.relaxed.gpu.global.u32 %0, [%1];" : "=r"(v) : "l"(p) : "memory"); return v;
}
__device__ __forceinline__ uint2 ld_rlx64(const void* p) {
    uint2 v; asm volatile("ld.relaxed.gpu.global.v2.u32 {%0,%1}, [%2];" : "=r"(v.x), "=r"(v.y) : "l"(p) : "memory"); return v;
}
__device__ __forceinline__ float4 ld_rlx128f(const float4* p) {
    float4 v; asm volatile("ld.relaxed.gpu.global.v4.f32 {%0,%1,%2,%3}, [%4];" : "=f"(v.x), "=f"(v.y), "=f"(v.z), "=f"(v.w) : "l"(p) : "memory"); return v;
}
__device__ __forceinline__ float4 take(float4* p, bool q) {
    float4 v;
    asm volatile("{ .reg .b128 a; .reg .b64 x, y; .reg .pred q; mov.b64 x, 0; mov.b128 a, {x, x}; setp.ne.u32 q, %5, 0;\n"
                 "@q atom.relaxed.gpu.global.exch.b128 a, [%4], a; mov.b128 {x, y}, a; mov.b64 {%0,%1}, x; mov.b64 {%2,%3}, y; }"
                 : "=f"(v.x), "=f"(v.y), "=f"(v.z), "=f"(v.w) : "l"(p), "r"((uint32_t)q) : "memory");
    return v;
}
__device__ __forceinline__ void fence_gpu() { asm volatile("fence.acq_rel.gpu;" ::: "memory"); }
__device__ __forceinline__ void st_rlx32(uint32_t* p, uint32_t v) { asm volatile("st.relaxed.gpu.global.u32 [%0], %1;" ::"l"(p), "r"(v) : "memory"); }
__device__ __forceinline__ uint32_t hmul_bf2(uint32_t a, uint32_t b) {
    uint32_t r; asm("mul.rn.bf16x2 %0, %1, %2;" : "=r"(r) : "r"(a), "r"(b)); return r;
}
__device__ __forceinline__ uint32_t hsub_bf2(uint32_t a, uint32_t b) {
    uint32_t r; asm("sub.rn.bf16x2 %0, %1, %2;" : "=r"(r) : "r"(a), "r"(b)); return r;
}
__device__ __forceinline__ uint32_t hadd_bf2(uint32_t a, uint32_t b) {
    uint32_t r; asm("add.rn.bf16x2 %0, %1, %2;" : "=r"(r) : "r"(a), "r"(b)); return r;
}
__device__ __forceinline__ int opaque(int v) { return __shfl_sync(0xffffffffu, v, threadIdx.x); }
constexpr int SPIN_LIMIT = 1 << 22;

__constant__ uint32_t c_inv2pi[8] = {0u, 0x28be60dbu, 0x9391054au, 0x7f09d5f4u, 0x7d4d3770u, 0x36d8a566u, 0x4f10e410u, 0x7f9458eau};
constexpr uint32_t BIGX = 0x4280u;
__device__ __forceinline__ float cos_big(uint32_t xb) {
    uint32_t e = (xb >> 7) & 0xffu, M = (xb & 0x7fu) | 0x80u;
    uint32_t pp = e - 102u;
    uint32_t wi = pp >> 5;
    uint32_t t0 = c_inv2pi[wi], t1 = c_inv2pi[wi + 1], t2 = c_inv2pi[wi + 2];
    uint32_t f = M * __funnelshift_l(t1, t0, pp) + __umulhi(M, __funnelshift_l(t2, t1, pp));
    float c = __cosf((float)(int)f * 1.4629180792671596e-9f);
    return e == 255u ? __uint_as_float(0x7fc00000u) : c;
}
__device__ __forceinline__ float cos_bf(uint32_t xb) {
    return (xb & 0x7fffu) > BIGX ? cos_big(xb) : __cosf(__uint_as_float(xb << 16));
}
__device__ __forceinline__ uint32_t pack_bf2(float lo, float hi) {
    uint32_t r; asm("cvt.rn.bf16x2.f32 %0, %1, %2;" : "=r"(r) : "f"(hi), "f"(lo)); return r;
}
template <int N> __device__ __forceinline__ uint32_t pick(int k, const uint32_t (&a)[N]) {
    uint32_t v = a[0];
#pragma unroll
    for (int i = 1; i < N; i++) if (k == i) v = a[i];
    return v;
}
template <int N> __device__ __forceinline__ uint2 pick(int k, const uint2 (&a)[N]) {
    uint2 v = a[0];
#pragma unroll
    for (int i = 1; i < N; i++) if (k == i) v = a[i];
    return v;
}
__device__ __forceinline__ uint32_t imul(uint32_t a, float s) { uint32_t r; asm("mul.rz.f32 %0, %1, %2;" : "=r"(r) : "r"(a), "f"(s)); return r; }
__device__ __forceinline__ uint32_t ifma(uint32_t a, float s, uint32_t c) { uint32_t r; asm("fma.rn.f32 %0, %1, %2, %3;" : "=r"(r) : "r"(a), "f"(s), "r"(c)); return r; }
extern __shared__ __align__(1024) unsigned char smem[];
__device__ __forceinline__ void side_add(uint32_t bin, uint32_t row, float a, float b, float c, float d) {
    red4(&g_ovf[bin * RPAD + row], a, b, c, d);
    g_dirty[bin * DROW + row] = 1;
}
__device__ __forceinline__ void slow_triplet(const Params& p, uint32_t ii, uint32_t oo, float c) {
    const uint2 v = __ldg(p.m + ii);
    const uint32_t bo = imul(oo, p.i2);
    side_add(bo, oo - bo * p.R2, c * bf_lo(v.x), c * bf_hi(v.x), c * bf_lo(v.y), c * bf_hi(v.y));
}
__device__ __forceinline__ void slow_rec1(const Params& p, uint32_t x, uint32_t y, uint32_t bin) {
    const uint2 v = __ldg(p.m + bin * p.R1 + (y & 0xffffu));
    const float c = bf_hi(y);
    side_add(x & 0xffu, __byte_perm(x, 0u, 0x4413) >> 3, c * bf_lo(v.x), c * bf_hi(v.x), c * bf_lo(v.y), c * bf_hi(v.y));
}
__device__ __forceinline__ uint32_t aux_of(uint32_t w0, uint32_t w1, uint32_t k = 0) {
    uint32_t u; asm("lop3.b32 %0, %1, %2, 0xf000f000, 0xe4;" : "=r"(u) : "r"(w0), "r"((w1 >> 4) + k));
    return __byte_perm(u, 0u, 0x4413);
}
__device__ __forceinline__ void slow_rec2(const Params& p, uint32_t w0, uint32_t w1, uint32_t bin, float unit) {
    side_add(bin, aux_of(w0, w1) >> 3, (float)((int)(w0 & 0xfffu) - 2048) * unit, (float)((int)(w0 >> 16 & 0xfffu) - 2048) * unit,
             (float)((int)(w1 & 0xfffu) - 2048) * unit, (float)((int)(w1 >> 16 & 0xfffu) - 2048) * unit);
}
template <uint32_t M> __device__ __forceinline__ uint32_t and_or(uint32_t a, uint32_t c) {
    uint32_t r; asm("lop3.b32 %0, %1, %2, %3, 0xea;" : "=r"(r) : "r"(a), "n"(M), "r"(c)); return r;
}
template <uint32_t M> __device__ __forceinline__ uint32_t xor_and(uint32_t a, uint32_t c) {
    uint32_t r; asm("lop3.b32 %0, %1, %2, %3, 0x48;" : "=r"(r) : "r"(a), "n"(M), "r"(c)); return r;
}
__device__ __forceinline__ uint32_t mux(uint32_t a, uint32_t b, uint32_t m) {
    uint32_t r; asm("lop3.b32 %0, %1, %2, %3, 0xd8;" : "=r"(r) : "r"(a), "r"(b), "r"(m)); return r;
}
__device__ __forceinline__ uint32_t and_xor(uint32_t a, uint32_t m, uint32_t c) {
    uint32_t r; asm("lop3.b32 %0, %1, %2, %3, 0x6a;" : "=r"(r) : "r"(a), "r"(m), "r"(c)); return r;
}
__device__ __forceinline__ uint2 ld_in(const uint2* a) {
    uint2 v; asm volatile("ld.global.nc.L1::no_allocate.v2.u32 {%0,%1}, [%2];" : "=r"(v.x), "=r"(v.y) : "l"(a)); return v;
}
__device__ __forceinline__ uint32_t ld_in(const uint32_t* a) {
    uint32_t v; asm volatile("ld.global.nc.L1::no_allocate.u32 %0, [%1];" : "=r"(v) : "l"(a)); return v;
}
__device__ __forceinline__ void ld_in4(const uint2* p, uint2& a, uint2& b) {
    asm volatile("ld.global.nc.L1::no_allocate.v4.u32 {%0,%1,%2,%3}, [%4];" : "=r"(a.x), "=r"(a.y), "=r"(b.x), "=r"(b.y) : "l"(p));
}
__device__ __forceinline__ void tex4(cudaTextureObject_t t, int i, uint2& a, uint2& b) {
    asm volatile("tex.1d.v4.u32.s32 {%0,%1,%2,%3}, [%4, {%5}];" : "=r"(a.x), "=r"(a.y), "=r"(b.x), "=r"(b.y) : "l"(t), "r"(i));
}
__device__ __forceinline__ void tex2(cudaTextureObject_t t, int i, uint32_t& a, uint32_t& b) {
    asm volatile("{ .reg .b32 z, w; tex.1d.v4.u32.s32 {%0,%1,z,w}, [%2, {%3}]; }" : "=r"(a), "=r"(b) : "l"(t), "r"(i) : "memory");
}
template <int OFF> __device__ __forceinline__ void put_rec(uint32_t ret, uint32_t lim, uint32_t addr, uint32_t x, uint32_t y) {
    asm volatile("{ .reg .pred q; setp.lt.u32 q, %0, %1; @q st.shared.v2.u32 [%2+%5], {%3,%4}; }" ::"r"(ret), "r"(lim), "r"(addr), "r"(x), "r"(y), "n"(OFF) : "memory");
}
__device__ __forceinline__ uint32_t mbar_try(uint32_t mb, uint32_t parity) {
    uint32_t ok;
    asm volatile("{ .reg .pred q; mbarrier.try_wait.parity.shared::cta.b64 q, [%1], %2; selp.u32 %0, 1, 0, q; }" : "=r"(ok) : "r"(mb), "r"(parity) : "memory");
    return ok;
}
__device__ __forceinline__ void mbar_wait(uint32_t mb, uint32_t parity) {
    if (!mbar_try(mb, parity)) {
        int it = 0;
        while (!mbar_try(mb, parity)) if (++it > SPIN_LIMIT) __trap();
    }
}
__device__ __forceinline__ void mbar_init(uint32_t mb, uint32_t n) { asm volatile("mbarrier.init.shared::cta.b64 [%0], %1;" ::"r"(mb), "r"(n) : "memory"); }
__device__ __forceinline__ void mbar_arrive(uint32_t mb) { asm volatile("mbarrier.arrive.shared::cta.b64 _, [%0];" ::"r"(mb) : "memory"); }
constexpr int B_FULL = OFF_BAR, B_OPEN = OFF_BAR + 16, B_FREE = OFF_BAR + 32;
constexpr int W_END = OFF_BAR + 40, W_SIDE = OFF_BAR + 44, W_PAR = OFF_BAR + 48, W_ROLE = OFF_BAR + 52, W_EXP = OFF_BAR + 56, W_UNIT = OFF_BAR + 60, W_NLIST = OFF_PROBE + 112, W_WRAP = OFF_PROBE + 116, W_BASE = OFF_PROBE + 120, B_TAB = OFF_PROBE + 128, B_ROWS = OFF_PROBE + 248, B_TFREE = OFF_PROBE + 240, B_FLAG = OFF_PROBE + 232, B_INIT = OFF_PROBE + 224, W_ITEM = OFF_PROBE + 124;
enum { BAR_S1 = 1, BAR_SIDE, BAR_PROBE, BAR_PAR, BAR_TABLE, BAR_DONE, BAR_ACC, BAR_H1, BAR_BASE, BAR_ROWS };
constexpr int W_M1 = NS1 + NC, W_M2 = 31;

#define RTS(c, i)
#define TK_DECL
#define TK(i)
#define TK_CNT(i)
#define TK_OUT
#define TK_ARG
#define TK_PASS
#define TKS(i) TK(i)
#define TKX(i)
#define TKY(i) {}
#define TKZ(i, d)

__device__ __forceinline__ void prefetch_l2(const void* a) { asm volatile("prefetch.global.L2 [%0];" ::"l"(a)); }
__device__ __forceinline__ void wait_flags(const Params& p, uint32_t sb, int lane, uint32_t need) {
    const unsigned char* f = p.ring + M_FLAG + (lds32(sb + W_SIDE) << 12);
    int it = 0;
    while (true) {
        uint32_t a[4];
        asm volatile("ld.acquire.gpu.global.v4.u32 {%0,%1,%2,%3}, [%4];" : "=r"(a[0]), "=r"(a[1]), "=r"(a[2]), "=r"(a[3]) : "l"(f + min(lane, 16) * 16) : "memory");
        const uint32_t d = (a[0] ^ need) | (a[1] ^ need) | (lane < 16 ? (a[2] ^ need) | (a[3] ^ need) : 0u);
        if (__all_sync(0xffffffffu, d == 0)) break;
        __nanosleep(50);
        if (++it > SPIN_LIMIT) __trap();
    }
}
__device__ __forceinline__ float exp_fast(float x) { float r; asm("ex2.approx.ftz.f32 %0, %1;" : "=f"(r) : "f"(x * 1.4426950408889634f)); return r; }
constexpr uint32_t BIAS = 0x3d803d80u, ZERO = 0x7d80u;
__device__ __forceinline__ float2 acc_fix(uint32_t old, uint32_t q) {
    const uint32_t u = old + BIAS, n = u + q - 0x08000800u;
    return make_float2((float)((int)(u & 0xffffu) + (int)(q & 0xffffu) - 2048 - (int)(n & 0xffffu)), (float)((int)(u >> 16) + (int)(q >> 16) - 2048 - (int)(n >> 16)));
}
constexpr int NE = NS1 + NC, NPAIR = (R2MAX / 2 + NE * 32 - 1) / (NE * 32), NTILE = 16, NG0 = NS1 * 8 * NTILE;
constexpr int OFF_G = OFF_M, GH = R2MAX * 8, OFF_LIST = OFF_G;
static_assert(2 * R2MAX <= R1MAX && NG0 * 16 + 112 <= WIN && 3 * NG0 >= NPAIR * NE * 32 && NPAIR * NE * 64 <= DROW, "gates");
__device__ __forceinline__ int gate_g(int k) { return (k < NG0 ? OFF_H1 : OFF_G) + k * 16; }
__device__ __forceinline__ int gate_h(int k) { return (k < NG0 ? OFF_H1 + 0x20000 : OFF_G + GH) + k * 16; }
__device__ __forceinline__ uint2 out_row(int row, const float4& o, const float4& add, const uint2& mv) {
    const float* w = reinterpret_cast<const float*>(smem + OFF_WSM);
    const float unit = *reinterpret_cast<const float*>(smem + W_UNIT), K = 8388608.f + ZERO;
    const uint2 ac = reinterpret_cast<const uint2*>(smem + OFF_ACC)[row];
    const uint32_t* g = reinterpret_cast<const uint32_t*>(smem + gate_g(row >> 1)) + (row & 1), *h = reinterpret_cast<const uint32_t*>(smem + gate_h(row >> 1)) + (row & 1);
    const uint32_t c0 = ac.x + BIAS, c1 = ac.y + BIAS;
    const float a[4] = {fmaf(__uint_as_float(__byte_perm(c0, 0x4b00u, 0x5410)) - K, unit, o.x), fmaf(__uint_as_float(__byte_perm(c0, 0x4b00u, 0x5432)) - K, unit, o.y),
                        fmaf(__uint_as_float(__byte_perm(c1, 0x4b00u, 0x5410)) - K, unit, o.z), fmaf(__uint_as_float(__byte_perm(c1, 0x4b00u, 0x5432)) - K, unit, o.w)};
    float sd[4], uu[4];
#pragma unroll
    for (int k = 0; k < 4; k++) sd[k] = fmaf(a[3], w[12 + k], fmaf(a[2], w[8 + k], fmaf(a[1], w[4 + k], a[0] * w[k])));
    const uint32_t a01 = hmul_bf2(pack_bf2(sd[0] + add.x, sd[1] + add.y), g[0]), a23 = hmul_bf2(pack_bf2(sd[2] + add.z, sd[3] + add.w), g[2]);
#pragma unroll
    for (int k = 0; k < 4; k++) uu[k] = fmaf(bf_hi(a23), w[28 + k], fmaf(bf_lo(a23), w[24 + k], fmaf(bf_hi(a01), w[20 + k], bf_lo(a01) * w[16 + k])));
    return make_uint2(hadd_bf2(mv.x, hmul_bf2(pack_bf2(uu[0], uu[1]), h[0])), hadd_bf2(mv.y, hmul_bf2(pack_bf2(uu[2], uu[3]), h[2])));
}
__device__ __forceinline__ void mma16(float (&c)[4], const uint32_t (&a)[4], uint32_t b0, uint32_t b1) {
    asm volatile("mma.sync.aligned.m16n8k16.row.col.f32.bf16.bf16.f32 {%0,%1,%2,%3}, {%4,%5,%6,%7}, {%8,%9}, {%0,%1,%2,%3};"
                 : "+f"(c[0]), "+f"(c[1]), "+f"(c[2]), "+f"(c[3]) : "r"(a[0]), "r"(a[1]), "r"(a[2]), "r"(a[3]), "r"(b0), "r"(b1));
}
__device__ __forceinline__ void finish_rows(const Params& p, uint32_t sb, bool s1) {
    int tid;
    bool wet = false;
    {
        asm volatile("mov.u32 %0, %%tid.x;" : "=r"(tid));
        const int lane = tid & 31;
        if (s1) mbar_wait(sb + B_INIT, 0); else if (lane == 0) mbar_arrive(sb + B_TFREE);
#pragma unroll 1
        for (bool own = s1;; own = false, wet = true) {
            asm volatile("mov.u32 %0, %%tid.x;" : "=r"(tid));
            uint32_t item = tid >> 5;
            if (!own) item = tid & 31 ? 0u : atoms_add<W_ITEM>(sb, 1u);
            item = __reduce_max_sync(0xffffffffu, item);
            if (item >= 3 * NS1) break;
            const int kb = item / NS1 * NG0 + item % NS1 * 8, q = (lds32(sb + W_ROLE) * p.R2 >> 1) + kb + (tid >> 2 & 7) + (tid & 3) * NS1 * 8;
            uint32_t ds[NTILE / 4];
#pragma unroll
            for (int j = 0; j < NTILE / 4; j++) ds[j] = ld_in(reinterpret_cast<const uint32_t*>(p.dist) + min(q + j * NS1 * 32, (p.E >> 1) - 1));
            const uint2 wc = lds64<OFF_WG>(sb + (tid & 31) * 8);
            const uint32_t wb = wc.x, cen = wc.y;
            TKZ(4, (ds[0] ^ ds[1] ^ ds[2] ^ ds[3] ^ wb ^ cen))
            uint2 v[NTILE];
#pragma unroll
            for (int i = 0; i < NTILE; i++) {
                const uint32_t x = __shfl_sync(0xffffffffu, ds[i >> 2], i & 3, 4);
                uint32_t rb[2];
#pragma unroll
                for (int u = 0; u < 2; u++) {
                    const uint32_t df = hsub_bf2(__byte_perm(x, 0u, u ? 0x3232 : 0x1010), cen);
                    const uint32_t ar = hmul_bf2(hmul_bf2(df, df), 0xc120c120u);
                    rb[u] = pack_bf2(exp_fast(bf_lo(ar)), exp_fast(bf_hi(ar)));
                }
                float c[4];
                asm volatile("mma.sync.aligned.m16n8k8.row.col.f32.bf16.bf16.f32 {%0,%1,%2,%3}, {%4,%5}, {%6}, {%7,%7,%7,%7};"
                             : "=f"(c[0]), "=f"(c[1]), "=f"(c[2]), "=f"(c[3]) : "r"(rb[0]), "r"(rb[1]), "r"(wb), "f"(0.f));
                v[i] = make_uint2(pack_bf2(c[0], c[1]), pack_bf2(c[2], c[3]));
            }
            TKZ(5, (v[15].x ^ v[9].y))
            if (own) bar_sync(BAR_H1, (NS1 + 1) * 32); else mbar_wait(sb + B_TFREE, 0);
            asm volatile("mov.u32 %0, %%tid.x;" : "=r"(tid));
            const int k0 = kb + (tid >> 2 & 7);
            const uint32_t a = sb + (tid & 2 ? gate_h(k0) : gate_g(k0)) + (tid & 1) * 8;
#pragma unroll
            for (int i = 0; i < NTILE; i++) if (i < NTILE - 1 || k0 + i * NS1 * 8 < R2MAX / 2) sts64(a + i * NS1 * 8 * 16, v[i].x, v[i].y);
            static_assert(2 * NG0 + (NTILE - 1) * NS1 * 8 <= R2MAX / 2, "gates");
            TKY(1)
        }
    }
    asm volatile("mov.u32 %0, %%tid.x;" : "=r"(tid));
    const int role = lds32(sb + W_ROLE), row0 = role * p.R2, np = min(p.R2, p.E - row0) >> 1, lane = tid & 31;
    uint4 wd = make_uint4(0u, 0u, 0u, 0u), wu = wd;
    if ((lane & 3) == lane >> 3) { wd = lds128(sb + OFF_WB + (lane & 4) * 8); wu = lds128(sb + OFF_WB + 16 + (lane & 4) * 8); }
    const uint32_t wb[8] = {wd.x, wd.y, wd.z, wd.w, wu.x, wu.y, wu.z, wu.w};
    const uint32_t k0 = (lds32(sb + W_UNIT) >> 16) * 0x10001u + 0x03800380u;
    uint8_t* dirty = g_dirty + role * DROW + tid * 2;
    auto flags = [&](uint32_t on) {
        uint32_t f[NPAIR], m = 0;
#pragma unroll
        for (int i = 0; i < NPAIR; i++) asm volatile("{ .reg .pred q; setp.ne.u32 q, %2, 0; mov.u32 %0, 0; @q ld.relaxed.gpu.global.u16 %0, [%1]; }" : "=r"(f[i]) : "l"(dirty + i * NE * 64), "r"(on) : "memory");
#pragma unroll
        for (int i = 0; i < NPAIR; i++) m |= ((f[i] | f[i] >> 7) & 3u) << 2 * i;
        return m;
    };
    auto row_of = [&](int j) { return 2 * tid + (j >> 1) * NE * 64 + (j & 1); };
    uint32_t kept, left = 0, bad = 0, at;
#pragma unroll 1
    for (;; wet = true) {
        if (wet) mbar_wait(sb + B_FLAG, 0);
        TKY(2)
        kept = flags(wet);
        at = __popc(kept);
        TKZ(3, kept)
#pragma unroll
        for (int i = 1; i < 32; i *= 2) { const uint32_t t = __shfl_up_sync(0xffffffffu, at, i); if (lane >= i) at += t; }
        const uint32_t n = __shfl_sync(0xffffffffu, at, 31);
        if (n || !wet) {
            uint32_t q = 0;
            if (lane == 0) q = atoms_add<W_NLIST>(sb, n);
            q = __shfl_sync(0xffffffffu, q, 0);
            if (q + n > NG0) { sts32(sb + W_WRAP, 1u); kept = 0; }
            else {
                q = sb + OFF_LIST + q * 16;
                at = q + (at - __popc(kept)) * 16;
                uint32_t to = at;
                uint32_t m = kept;
#pragma unroll 1
                do {
                    if (m) sts32(to, row_of(__ffs(m) - 1));
                    m &= m - 1; to += 16;
                } while (m);
                __syncwarp();
                to = q + lane * 16;
#pragma unroll 1
                do {
                    const bool on = to < q + n * 16;
                    float4 o = make_float4(0.f, 0.f, 0.f, 0.f);
                    asm volatile("{ .reg .pred q; setp.ne.u32 q, %5, 0; @q ld.relaxed.gpu.global.v4.f32 {%0,%1,%2,%3}, [%4]; }"
                                 : "+f"(o.x), "+f"(o.y), "+f"(o.z), "+f"(o.w) : "l"(&g_ovf[role * RPAD + lds32(to)]), "r"((uint32_t)on) : "memory");
                    const float4* w = reinterpret_cast<const float4*>(smem + OFF_WSM);
                    const uint4 v = make_uint4(__float_as_uint(fmaf(o.w, w[3].x, fmaf(o.z, w[2].x, fmaf(o.y, w[1].x, o.x * w[0].x)))),
                                               __float_as_uint(fmaf(o.w, w[3].y, fmaf(o.z, w[2].y, fmaf(o.y, w[1].y, o.x * w[0].y)))),
                                               __float_as_uint(fmaf(o.w, w[3].z, fmaf(o.z, w[2].z, fmaf(o.y, w[1].z, o.x * w[0].z)))),
                                               __float_as_uint(fmaf(o.w, w[3].w, fmaf(o.z, w[2].w, fmaf(o.y, w[1].w, o.x * w[0].w)))));
                    if (on) sts128<0>(to, v);
                    to += 512;
                } while (to < q + n * 16);
            }
        }
        TKY(6)
        if (wet) {
            mbar_wait(sb + B_ROWS, 0);
            TKX(5)
            bar_sync(BAR_ACC, (NE + NC) * 32);
        }
        const int lim = wet ? np : 0;
        uint32_t from = at, bit = wet ? 1u : 1u << (2 * NPAIR - 2);
        uint4* out = reinterpret_cast<uint4*>(p.out + row0) + tid;
#pragma unroll 1
        for (int k = tid; bit < 1u << 2 * NPAIR; k += NE * 32, bit *= 4, out += NE * 32) {
            const uint4 ac = lds128(sb + OFF_ACC + k * 16), g = lds128(sb + gate_g(k)), h = lds128(sb + gate_h(k));
            const uint4 mv = lds128(sb + (row0 * 8 & 127) + k * 16 + (k < NG0 ? 0 : k < 2 * NG0 ? 0x10000 - NG0 * 16 : 0x30000 - NG0 * 32));
            const uint32_t u[4] = {ac.x + BIAS, ac.z + BIAS, ac.y + BIAS, ac.w + BIAS};
            uint32_t a[4];
            float c[4] = {0.f, 0.f, 0.f, 0.f}, d[4] = {0.f, 0.f, 0.f, 0.f};
#pragma unroll
            for (int j = 0; j < 2; j++)
                asm volatile("{ .reg .pred q; setp.ne.u32 q, %5, 0; @q ld.shared.v2.f32 {%0,%1}, [%4]; @q ld.shared.v2.f32 {%2,%3}, [%4+8]; @q add.u32 %4, %4, 16; }"
                             : "+f"(c[2 * j]), "+f"(c[2 * j + 1]), "+f"(d[2 * j]), "+f"(d[2 * j + 1]), "+r"(from) : "r"(kept & bit << j) : "memory");
#pragma unroll
            for (int j = 0; j < 4; j++) a[j] = hsub_bf2(and_or<0x007f007fu>(u[j] >> 9, k0 + 0x04800480u), k0 + 0x04c004c0u);
            mma16(c, a, wb[0], wb[1]); mma16(d, a, wb[2], wb[3]);
#pragma unroll
            for (int j = 0; j < 4; j++) a[j] = and_or<0x007f007fu>(u[j] >> 2, k0 + 0x01000100u);
            mma16(c, a, wb[0], wb[1]); mma16(d, a, wb[2], wb[3]);
#pragma unroll
            for (int j = 0; j < 4; j++) a[j] = and_or<0x00030003u>(u[j], k0);
            mma16(c, a, wb[0], wb[1]); mma16(d, a, wb[2], wb[3]);
            a[0] = hmul_bf2(pack_bf2(c[0], c[1]), g.x); a[1] = hmul_bf2(pack_bf2(c[2], c[3]), g.y);
            a[2] = hmul_bf2(pack_bf2(d[0], d[1]), g.z); a[3] = hmul_bf2(pack_bf2(d[2], d[3]), g.w);
#pragma unroll
            for (int j = 0; j < 4; j++) c[j] = d[j] = 0.f;
            mma16(c, a, wb[4], wb[5]); mma16(d, a, wb[6], wb[7]);
            if (k < lim) {
                *out = make_uint4(hadd_bf2(mv.x, hmul_bf2(pack_bf2(c[0], c[1]), h.x)), hadd_bf2(mv.y, hmul_bf2(pack_bf2(d[0], d[1]), h.z)),
                                  hadd_bf2(mv.z, hmul_bf2(pack_bf2(c[2], c[3]), h.y)), hadd_bf2(mv.w, hmul_bf2(pack_bf2(d[2], d[3]), h.w)));
                if (c[0] != c[0] || c[2] != c[2]) bad |= 3u * bit;
            }
        }
        if (wet) break;
    }
    const bool wrap = lds32(sb + W_WRAP);
    if (RARE(wrap)) { left = flags(1u); kept = 0; }
#pragma unroll 1
    for (uint32_t m = left | bad; RARE(m); m &= m - 1) {
        const int j = __ffs(m) - 1, row = row_of(j);
        uint4 v = make_uint4(0u, 0u, 0u, 0u);
        if (kept >> j & 1u) v = lds128(at + __popc(kept & ((1u << j) - 1u)) * 16);
        p.out[row0 + row] = out_row(row, take(&g_ovf[role * RPAD + row], left >> j & 1u),
                                    make_float4(__uint_as_float(v.x), __uint_as_float(v.y), __uint_as_float(v.z), __uint_as_float(v.w)), p.m[row0 + row]);
        if (wrap) g_dirty[role * DROW + row] = 0;
    }
}

template <int HOP> __device__ __forceinline__ uint2 null_rec(int lane, uint32_t R) {
    if (HOP == 1) return make_uint2(0x800000u | H<1>::tag(R), (OFF_CNT1 - OFF_M) / 8);
    return make_uint2(0x08000800u | lane << 28, 0x0fff0000u | H<2>::tag(R));
}
template <int HOP> __device__ __forceinline__ void fill(uint32_t win, int ct, uint32_t R) {
    const uint2 v = null_rec<HOP>(ct, R);
#pragma unroll
    for (int i = 0; i < WIN / (NC * 512); i++) sts128<0>(win + ct * 16 + i * NC * 512, make_uint4(v.x, v.y, v.x, v.y));
}
template <int HOP> __device__ __forceinline__ void reset(uint32_t win, int lane, uint32_t R) {
    const uint2 v = null_rec<HOP>(lane, R);
    const uint32_t a = win + lane * 32 + H<HOP>::mark(R, lane >> 2) * 8;
#pragma unroll
    for (int i = 0; i < 16; i++) sts64(a + i * 1024, v.x, v.y);
    if (lane < 16) sts64(a + 16384, v.x, v.y);
}
__device__ __forceinline__ bool elect() {
    uint32_t q; asm volatile("{ .reg .pred q; elect.sync _|q, 0xffffffff; selp.u32 %0, 1, 0, q; }" : "=r"(q)); return q;
}
__device__ __forceinline__ const unsigned char* mk_ptr(uint32_t lo, uint32_t hi) { return reinterpret_cast<const unsigned char*>((uint64_t)hi << 32 | lo); }
__device__ __forceinline__ void bulk_store(uint32_t lo, uint32_t hi, uint32_t src, uint32_t n) {
    asm volatile("cp.async.bulk.global.shared::cta.bulk_group [%0], [%1], %2;" ::"l"(mk_ptr(lo, hi)), "r"(src), "r"(n) : "memory");
}
template <int HOP>
__device__ __forceinline__ void manager(const Params& p, uint32_t sb, int lane, int role, uint32_t base) {
    typedef H<HOP> h;
    constexpr int V = h::NBIN / 32, PB = h::S * 8;
    const int RT = p.rounds + HOP - 1, lo = HOP == 1 && role >= NG ? NG : 0, hi = lo + h::NBIN;
    const int w = (role - lo) / (HOP * J), j = (role - lo - w * HOP * J) / HOP;
    const Ring rg(p.ring, __reduce_or_sync(0xffffffffu, lds32(sb + W_PAR)), 2 * w + HOP - 1);
    const uint32_t side = lds32(sb + W_SIDE), dhi = rg.main >> 32, mhi = rg.mid >> 32;
    const uint32_t c0 = HOP == 2 ? role & 1 : 0, up = (HOP == 1 && lo) ^ rg.par ^ c0;
    uint32_t dA = ((uint32_t)rg.main + src_off(j) + (c0 << 16) + (up ? 4096 : 12288)) ^ slot_off(base % 3);
    uint32_t dM = ((uint32_t)rg.mid + src_off(j) + c0 * 1024) ^ slot_off(base % 3);
    const int a0 = max(64, lo), b1 = min(68, hi);
    int n0 = (min(NHI, hi) - a0) * PB, a1 = (max(NLO, lo) - lo) * PB;
    const unsigned char* cr = reinterpret_cast<const unsigned char*>(rg.main) + MISC + ((side ^ rg.par) << 12);
    const unsigned char* cr0 = cr + cred_off(lo + lane * V), *cr1 = cr + cred_off(lo + 32 * V + min(lane, V - 1));
    const uint32_t ca0 = sb + h::CNT + lane * V * 4, ca1 = sb + h::CNT + (32 * V + min(lane, V + NDUM)) * 4;
    const uint32_t rot0 = (lane * V & 7) * 16, rot1 = lane * 16;
    uint32_t st = slot_steps(base);
    uint32_t init = h::init(base), prim = sb + h::STG + (HOP == 1 ? h::win(base) : 0u);
    uint32_t cs[5] = {0, 0, 0, 0, 0};
    auto sample = [&]() {
        if (V == 2) asm volatile("ld.relaxed.gpu.global.v2.u32 {%0,%1}, [%2];" : "=r"(cs[0]), "=r"(cs[1]) : "l"(cr0) : "memory");
        else asm volatile("ld.relaxed.gpu.global.v4.u32 {%0,%1,%2,%3}, [%4];" : "=r"(cs[0]), "=r"(cs[1]), "=r"(cs[2]), "=r"(cs[3]) : "l"(cr0) : "memory");
        cs[V] = ld_rlx32(reinterpret_cast<const uint32_t*>(cr1));
    };
    uint32_t low[5] = {rot0, rot0 + 16, rot0 + 32, rot0 + 48, rot1};
    TK_DECL
#pragma unroll 1
    for (int r = 0;; r++) {
        const uint32_t R = base + r, ninit = h::init(R + 1), done = prim;
        TK(5)
        mbar_wait(sb + B_FULL + (HOP - 1) * 8, r & 1);
        TK(0)
        if (HOP == 2) sample();
        uint32_t c[5];
        if (V == 2) asm volatile("ld.shared.v2.u32 {%0,%1}, [%2];" : "=r"(c[0]), "=r"(c[1]) : "r"(ca0) : "memory");
        else asm volatile("ld.shared.v4.u32 {%0,%1,%2,%3}, [%4];" : "=r"(c[0]), "=r"(c[1]), "=r"(c[2]), "=r"(c[3]) : "r"(ca0) : "memory");
        c[V] = lds32(ca1);
        uint32_t nc[5];
#pragma unroll
        for (int k = 0; k <= V; k++) {
            const uint32_t rot = k < V ? rot0 + k * 16 : rot1, z = ninit + (HOP == 1 ? rot : low[k]);
            if (HOP == 2) low[k] = min((max((int)(c[k] - low[k] - init - h::CAP * h::INC), 0) >> h::SH) * 128u + low[k], rot + BOXN * 128u);
            nc[k] = min(max(c[k] + (ninit - init - h::S * h::INC), z), (HOP == 1 ? z : ninit + low[k]) + (h::CAP - h::S) * h::INC);
        }
        if (V == 2) sts64(ca0, nc[0], nc[1]); else sts128<0>(ca0, make_uint4(nc[0], nc[1], nc[2], nc[3]));
        sts32(ca1, lane < V ? nc[V] : lane < V + NDUM ? DUMMY : r);
        __syncwarp();
        if (lane == 0) mbar_arrive(sb + B_OPEN + (HOP - 1) * 8);
        TK(1)
        TK(2)
        asm volatile("fence.proxy.async.shared::cta;" ::: "memory");
        TK(6)
        if (r >= D) {
            int it = 0;
            while (true) {
                uint32_t bad = 0;
#pragma unroll
                for (int k = 0; k <= V; k++) bad |= cs[k] - (R - D + 1);
                if (!__any_sync(0xffffffffu, bad >> 20)) break;
                if (++it > SPIN_LIMIT) __trap();
                if (it > 1) __nanosleep(100);
                sample();
            }
        }
        TK(3)
        if (elect()) {
            const uint32_t dB = (HOP == 1 ? dA ^ 0x10000u : dA) + (up ? 8192 : -8192), sm = prim + (lo ? 2 * PB : 0);
            bulk_store(dA, dhi, sm, 8192);
            bulk_store(dB, dhi, HOP == 1 ? sm + 8192 : prim + 68 * PB, 8192);
            if (n0 > 0) bulk_store(dM + (a0 - 64) * PB, mhi, prim + (a0 - lo) * PB, n0);
            if (a1 < (b1 - lo) * PB) bulk_store((dM ^ 4096u) + (uint32_t)((lo - NLO) * PB + a1), mhi, prim + a1, (b1 - lo) * PB - a1);
            asm volatile("cp.async.bulk.commit_group;" ::: "memory");
            if (r != RT - 1) asm volatile("cp.async.bulk.wait_group.read 0;" ::: "memory");
        }
        __syncwarp();
        TK(4)
        prim = HOP == 1 ? prim ^ 0x20000u : prim >= sb + 0x30000u ? sb : prim + (prim - sb) + 0x10000u;
        if (r == RT - 1) break;
        reset<HOP>(done, lane, R + HOP + 1);
        if (HOP == 1) {
            __syncwarp();
            if (lane == 0) mbar_arrive(sb + B_FREE);
        }
        if (RARE(r == D - 1 || r == RT - D - 1)) {
            uint32_t n = NHI, m = NLO;
            if (HOP == 1 && r == RT - D - 1 && lane < 2) {
                const int row0 = role * p.R2, nr = min(p.R2, p.E - row0) & ~7;
                const uint64_t a = lane ? reinterpret_cast<uint64_t>(p.dist + row0) + 15 & ~15ull : reinterpret_cast<uint64_t>(p.m + row0);
                if (nr > 8) asm volatile("cp.async.bulk.prefetch.L2.global [%0], %1;" ::"l"(a), "r"(lane ? nr * 2 - 16 : nr * 8) : "memory");
            }
            if (r < RT - D - 1) {
                int it = 0;
                while (true) {
                    n = ld_rlx32(reinterpret_cast<const uint32_t*>(p.ring + M_CNT + (side << 12)));
                    if ((n & 0xffffu) + (n >> 16) == NB) break;
                    if (++it > SPIN_LIMIT) __trap();
                }
                m = n = min(max(__reduce_or_sync(0xffffffffu, n) & 0xffffu, (uint32_t)NLO), (uint32_t)NHI);
            }
            n0 = (min((int)n, hi) - a0) * PB;
            a1 = (max((int)m, lo) - lo) * PB;
        }
        if (HOP == 2 && RARE(r == RT - LATE)) fence_gpu();
        if (HOP == 1) sample();
        slot_next(dA, st); slot_next(dM, st);
        st = slot_rot(st);
        init = ninit;
    }
    TK_OUT
}

template <int HOP> struct Reader {
    uint32_t lo, hi, st, line;
    uint32_t* cred;
    __device__ __forceinline__ void init(const Params& p, uint32_t sb, int w, int lane, int role, uint32_t base) {
        constexpr int PB = H<HOP>::S * 8;
        const int first = HOP == 1 ? (role >= NG ? NG : 0) + w * J : w * 2 * J;
        const Ring rg(p.ring, lds32(sb + W_PAR), 2 * w + HOP - 1);
        const uint32_t side = lds32(sb + W_SIDE);
        const bool mid = side ? role < 68 : role >= 64;
        const uint32_t i = role - (side ? (mid ? NLO : 68) : (mid ? 64 : 0));
        const uint32_t c = HOP == 1 ? i >> 5 : lane >> 3 & 1, in = (HOP == 1 ? (i & 31) * PB + (lane & 15) * 16 : i * PB + (lane & 7) * 16) + (lane >> 4) * src_off(3);
        lo = (in + (mid ? ((uint32_t)rg.mid ^ side << 12) + c * 1024 : (uint32_t)rg.main + (c << 16) + (side ^ rg.par ^ c ? 4096 : 12288))) ^ slot_off(base % 3);
        hi = __reduce_or_sync(0xffffffffu, (uint32_t)((mid ? rg.mid : rg.main) >> 32));
        st = slot_steps(base);
        line = opaque((HOP == 1 ? 2 * (role % NG) + (lane >> 3 & 1) : role) + (lane & 1) * 2);
        const bool both = first >= NLO && first < NHI;
        cred = lane < 1 + both ? reinterpret_cast<uint32_t*>(rg.main + MISC + (((both ? lane : first >= NG) ^ rg.par) << 12) + cred_off(role)) : nullptr;
    }
    template <int K> __device__ __forceinline__ void load1(uint2 (&v)[J]) const {
        asm volatile("ld.relaxed.gpu.global.v4.u32 {%0,%1,%2,%3}, [%4+%5];" : "=r"(v[2 * K].x), "=r"(v[2 * K].y), "=r"(v[2 * K + 1].x), "=r"(v[2 * K + 1].y)
                     : "l"(mk_ptr(lo, hi)), "n"(src_off(K)) : "memory");
    }
    static __device__ __forceinline__ uint32_t word(const uint2& v) { return HOP == 1 ? v.x : v.y; }
    template <int K> __device__ __forceinline__ void again(uint2 (&v)[J], uint32_t want, uint32_t m0, uint32_t m1, uint32_t grp) const {
        if (__ballot_sync(0xffffffffu, ((word(v[2 * K]) ^ want) & m0) | ((word(v[2 * K + 1]) ^ want) & m1)) & grp) load1<K>(v);
    }
    __device__ __forceinline__ void load(uint2 (&rec)[J]) const { load1<0>(rec); load1<1>(rec); load1<2>(rec); }
    __device__ __forceinline__ void check(uint2 (&rec)[J], uint32_t R, uint32_t ns, int lane TK_ARG) {
        const uint32_t want = H<HOP>::tag(R), mk = H<HOP>::mark(R, line);
        const uint32_t m0 = mk == 0 ? H<HOP>::TAG : 0u, m1 = mk == 1 ? H<HOP>::TAG : 0u;
        int it = 0;
        while (true) {
            uint32_t b0 = 0, b1 = 0;
#pragma unroll
            for (int j = 0; j < J; j += 2) { b0 |= word(rec[j]) ^ want; b1 |= word(rec[j + 1]) ^ want; }
            if (!__any_sync(0xffffffffu, (b0 & m0) | (b1 & m1))) break;
            if (++it > SPIN_LIMIT) __trap();
            __nanosleep(ns);
            TK_CNT(7)
            const uint32_t grp = 0xffu << (lane & 24u);
            again<0>(rec, want, m0, m1, grp); again<1>(rec, want, m0, m1, grp); again<2>(rec, want, m0, m1, grp);
        }
        if (cred) st_rlx32(cred, R + 1);
        __syncwarp();
        slot_next(lo, st);
        st = slot_rot(st);
    }
    __device__ __forceinline__ void finish() const { if (cred) st_rlx32(cred, 0u); }
};

__device__ __forceinline__ uint32_t probe(unsigned char* a, uint32_t zero) {
    *reinterpret_cast<uint4*>(a) = make_uint4(0u, 0u, 0u, 0u);
    *reinterpret_cast<uint4*>(a + 16) = make_uint4(0u, 0u, 0u, 0u);
    uint32_t best = ~0u, v = threadIdx.x, prev = 0;
#pragma unroll
    for (int t = 0; t <= NPROBE + 1; t++) {
        uint32_t now;
        if (t <= NPROBE) asm volatile("atom.relaxed.gpu.global.add.u32 %0, [%1], 1;" : "=r"(v) : "l"(a + (v & zero)) : "memory");
        else asm volatile("red.relaxed.gpu.global.add.u32 [%0], 1;" ::"l"(a + (v & zero)) : "memory");
        asm volatile("mov.u32 %0, %%clock;" : "=r"(now) :: "memory");
        if (t > 1) best = min(best, now - prev);
        prev = now;
    }
    return best;
}
template <bool B> struct BoolC { static constexpr bool value = B; };

__device__ __forceinline__ void stage1(const Params& p, uint32_t sb, const int pos0, int lane, const bool half) {
    typedef H<1> h;
    constexpr int NP = 4;
    static_assert(NPR == NS1 * NP * 32 - NP * 16, "tiles");
    const int RT = p.rounds;
    uint32_t ff = *reinterpret_cast<const uint16_t*>(p.ang_freq) * 0x10001u;
    auto pair_of = [&](int r, int pos) {
        const int q = r < RT - 1 ? (r * NB + blockIdx.x) * NPR + pos : (RT - 1) * NB * NPR + blockIdx.x * p.lastn + pos;
        return pos < (r < RT - 1 ? NPR : r == RT - 1 ? p.lastn : 0) && q < p.T2 ? q : -1;
    };
    uint2 vi[NP], vo[NP]; uint32_t va[NP];
    auto load_edge = [&](int r) {
#pragma unroll
        for (int u = 0; u < NP; u++) {
            const int q = max(pair_of(r, pos0 + u * 32), 0);
            vi[u] = ld_in(p.idx_in + q); vo[u] = ld_in(p.idx_out + q); va[u] = ld_in(p.angle + q);
        }
    };
    if (p.full) {
#pragma unroll
        for (int u = 0; u < NP; u += 2) {
            const int k = ((blockIdx.x * NPR + pos0 + lane) >> 1) + (!u ? 0 : half ? 0x40000000 : 32);
            tex2(p.ta, k, va[u], va[u + 1]); tex4(p.to, k, vo[u], vo[u + 1]); tex4(p.ti, k, vi[u], vi[u + 1]);
        }
    } else load_edge(0);
    if (blockIdx.x == 0 && pos0 == 0 && (p.T & 1)) {
        const int t = p.T - 1;
        slow_triplet(p, reinterpret_cast<const uint32_t*>(p.idx_in)[t], reinterpret_cast<const uint32_t*>(p.idx_out)[t],
                     bf16r(cos_bf(hmul_bf2(reinterpret_cast<const uint16_t*>(p.angle)[t], ff) & 0xffffu)));
    }
    ff = __reduce_or_sync(0xffffffffu, ff);
    bar_sync(BAR_S1, (NS1 + NC) * 32);
    uint32_t R = __reduce_or_sync(0xffffffffu, lds32(sb + W_BASE) & 31u);
    TK_DECL
    auto step = [&](const int r, const int qn, auto edge) {
        constexpr bool EDGE = decltype(edge)::value;
        uint32_t cc[NP], big = 0;
#pragma unroll
        for (int u = 0; u < NP; u++) {
            va[u] = hmul_bf2(va[u], ff);
            cc[u] = pack_bf2(__cosf(bf_lo(va[u])), __cosf(bf_hi(va[u])));
            big |= hmul_bf2(va[u], 0x3d003d00u);
        }
        if (RARE(big & 0x40004000u)) {
#pragma unroll 1
            for (int u = 0; u < NP; u++) {
                const uint32_t a = pick(u, va);
                float c0 = cos_bf(a & 0xffffu), c1 = cos_bf(a >> 16);
                if ((c0 != c0 || c1 != c1) && (EDGE ? pair_of(r, pos0 + u * 32) >= 0 : !half || u < 2)) {
                    const uint2 i2 = pick(u, vi), o2 = pick(u, vo);
                    if (c0 != c0) slow_triplet(p, i2.x, o2.x, c0);
                    if (c1 != c1) slow_triplet(p, i2.y, o2.y, c1);
                }
                const uint32_t v = pack_bf2(c0 != c0 ? 0.f : c0, c1 != c1 ? 0.f : c1);
#pragma unroll
                for (int k = 0; k < NP; k++) if (k == u) cc[k] = v;
            }
        }
        uint32_t bin[2 * NP], x[2 * NP], y[2 * NP];
        uint32_t dep = 0;
        auto loads = [&]() {
            const int q = qn + (dep & p.zero);
#pragma unroll
            for (int u = 0; u < NP; u += 2) {
                const int k = !u ? q : q + (half ? 0x40000000 : 32);
                tex2(p.ta, k, va[u], va[u + 1]); tex4(p.to, k, vo[u], vo[u + 1]); tex4(p.ti, k, vi[u], vi[u + 1]);
            }
        };
#pragma unroll
        for (int j = 0; j < 2 * NP; j++) {
            const uint32_t ii = j & 1 ? vi[j >> 1].y : vi[j >> 1].x, oo = j & 1 ? vo[j >> 1].y : vo[j >> 1].x;
            bin[j] = imul(ii, p.i1);
            y[j] = __byte_perm(ifma(bin[j], p.k1, ii), cc[j >> 1], j & 1 ? 0x7610 : 0x5410);
            const uint32_t bo = imul(oo, p.i2);
            x[j] = __byte_perm(ifma(bo, p.k2, imul(oo, 8.f)), bo, 0x0514);
            dep |= x[j] | y[j];
            if (EDGE && pair_of(r, pos0 + (j >> 1) * 32) < 0) bin[j] = NG + (lane & (NDUM - 1));
        }
        if (!EDGE) loads();
        else if (r < RT - 1) load_edge(r + 1);
        const uint32_t init = h::init(R), lim = init + ((EDGE && r == RT - 1 ? h::S : h::CAP) << h::SH);
        TKS(0)
        mbar_wait(sb + B_OPEN, ~R & 1);
        TKS(1)
        bool freed = false;
        uint32_t over = 0;
#pragma unroll
        for (int g = 0; g < 2 * NP; g += NP) if (!g || EDGE || !half) {
            constexpr int G = NP;
            uint32_t ret[G];
            int mx = 0;
#pragma unroll
            for (int j = 0; j < G; j++) ret[j] = atoms_add<h::CNT>(sb + imul(bin[g + j], 4.f), h::INC);
#pragma unroll
            for (int j = 0; j < G; j++) mx = j ? max(mx, (int)ret[j]) : (int)ret[j];
            if (!freed && __any_sync(0xffffffffu, mx >= (int)(init + 0x10000u))) { TKS(2) mbar_wait(sb + B_FREE, ~R & 1); freed = true; TKS(3) }
            TKS(2)
#pragma unroll
            for (int j = 0; j < G; j++) {
                x[g + j] = and_or<h::TAG>(ret[j], x[g + j]);
                put_rec<h::STG>(ret[j], lim, sb + and_or<0x20000u | h::PM>(ret[j], imul(bin[g + j], 256.f)), x[g + j], y[g + j]);
            }
            if (RARE(mx >= (int)lim)) {
#pragma unroll
                for (int j = 0; j < G; j++) if ((int)ret[j] >= (int)lim) over |= 1u << (g + j);
            }
        }
        __syncwarp();
        if (elect()) mbar_arrive(sb + B_FULL);
        R++;
        TKS(4)
#pragma unroll 1
        while (RARE(over)) {
            TK_CNT(7)
            const int j = __ffs(over) - 1;
            over &= over - 1;
            slow_rec1(p, pick(j, x), pick(j, y), pick(j, bin));
        }
        __syncwarp();
    };
#pragma unroll 1
    for (int q = opaque(((NB + blockIdx.x) * NPR + pos0 + lane) >> 1), r = 1; r < p.full; r++, q += NB * NPR / 2) step(r - 1, q, BoolC<false>());
#pragma unroll 1
    for (int r = max(p.full - 1, 0); r < RT; r++) step(r, 0, BoolC<true>());
    TK_OUT
}

__device__ __forceinline__ void stage2(const Params& p, uint32_t sb, int w, int lane, int role, uint32_t base1, uint32_t base) {
    typedef H<2> h;
    const int RT = p.rounds + 1;
    Reader<1> rd;
    rd.init(p, sb, w, lane, role, base1 + 3);
    uint2 rec[J];
#pragma unroll
    for (int j = 0; j < J; j++) rec[j] = null_rec<1>(lane, base1);
    uint32_t kb = sb + 0x10000u, am = 0x10000u | h::PM;
    const float unit = __uint_as_float(__reduce_or_sync(0xffffffffu, lds32(sb + W_UNIT)));
    TK_DECL
#pragma unroll 1
    for (int r = 0; r < RT; r++) {
        rd.check(rec, base1 + r, POLL_NS, lane TK_PASS);
        if (RARE(r == 1)) bar_sync(BAR_TABLE, 2 * NC * 32);
        const uint32_t want = H<1>::tag(base1 + r);
        TKS(0)
        uint2 mv[J];
#pragma unroll
        for (int j = 0; j < J; j++) {
            mv[j] = make_uint2(0u, 0u);
            const uint32_t a = sb + imul(rec[j].y & 0xffffu, 8.f);
            if (!xor_and<0x8e0000u>(rec[j].x, want)) mv[j] = lds64<OFF_M>(a);
        }
        uint32_t fl = 0;
#pragma unroll
        for (int j = 0; j < J; j++) fl |= mv[j].y;
        if (RARE(fl & 0x40000000u)) {
#pragma unroll 1
            for (int j = 0; j < J; j++) {
                const uint2 v = pick(j, mv), w = pick(j, rec);
                if ((v.y & 0x40000000u) && !((w.x ^ want) & 0x8e0000u)) {
                    if (v.x & 0x40000000u) slow_rec1(p, w.x, w.y, lds32(sb + W_ROLE) % NG);
                    else {
                        const float c = bf_hi(w.y), s = __uint_as_float(lds32(sb + W_UNIT)) * 1024.f;
                        side_add(w.x & 0xffu, __byte_perm(w.x, 0u, 0x4413) >> 3, c * (bf_lo(v.x) * s), c * (bf_hi(v.x) * s),
                                 c * (bf_lo(v.y) * s), c * (bf_hi(v.y & 0xbfffffffu) * s));
                    }
                }
            }
#pragma unroll
            for (int j = 0; j < J; j++) if (mv[j].y & 0x40000000u) rec[j].x = 0x800000u;
        }
        uint32_t w0[J], w1[J], bin[J], ret[J];
#pragma unroll
        for (int j = 0; j < J; j++) {
            const float c = bf_hi(rec[j].y), MG = 8194.0f;
            const uint32_t x = rec[j].x;
            const float v[4] = {bf_lo(mv[j].x), bf_hi(mv[j].x), bf_lo(mv[j].y), bf_hi(mv[j].y)};
            w0[j] = and_or<0xf000f000u>(x, __byte_perm(__float_as_uint(fmaf(c, v[0], MG)), __float_as_uint(fmaf(c, v[1], MG)), 0x5410));
            w1[j] = and_or<0xf000f000u>(x << 4, __byte_perm(__float_as_uint(fmaf(c, v[2], MG)), __float_as_uint(fmaf(c, v[3], MG)), 0x5410));
            bin[j] = min(xor_and<0x8e00ffu>(x, want), NB + (lane & (NDUM - 1)));
        }
        const uint32_t lim = h::init(base + r) + (r == RT - 1 ? 0x10000u : 0x20000u);
        rd.load(rec);
        TKS(1)
        mbar_wait(sb + B_OPEN + 8, (r - 1) & 1);
        TKS(2)
#pragma unroll
        for (int j = 0; j < J; j++) ret[j] = atoms_add<h::CNT>(sb + imul(bin[j], 4.f), h::INC);
        uint32_t mx = 0;
#pragma unroll
        for (int j = 0; j < J; j++) {
            w1[j] = and_or<h::TAG>(ret[j], w1[j]);
            put_rec<0>(ret[j], lim, and_xor(ret[j], am, bin[j] * 128 + kb), w0[j], w1[j]);
            mx = __viaddmax_u32(ret[j], 0u - DUMMY, mx);
        }
        __syncwarp();
        if (lane == 0) mbar_arrive(sb + B_FULL + 8);
        TKS(3)
        if (RARE(mx >= lim - DUMMY)) {
            uint32_t over = 0;
#pragma unroll
            for (int j = 0; j < J; j++) if (ret[j] - DUMMY >= lim - DUMMY) over |= 1u << j;
#pragma unroll 1
            do {
                const int j = __ffs(over) - 1;
                over &= over - 1;
                const uint32_t b = pick(j, bin), v = pick(j, ret) - lim, e = v >> h::SH, at = ((v - e * h::INC - (b & 7u) * 16u - h::CAP * 8) >> 7) + e;
                if (max(at, e) < BOXN && r < RT - LATE) g_box[(b * NB + role) * BOX + at] = make_uint2(pick(j, w0), pick(j, w1) | h::TAG);
                else slow_rec2(p, pick(j, w0), pick(j, w1), b, unit);
            } while (over);
        }
        __syncwarp();
        am = am >= 0x30000u ? 0x10000u | h::PM : am + 0x10000u;
        kb ^= am & 0x30000u;
        TKS(4)
    }
    rd.finish();
    TK_OUT
}

__device__ __forceinline__ void add_recs(uint32_t sb, int lane, const uint2 (&rec)[J], uint32_t want) {
    const uint32_t t = 0u - (lane & 1u), k = (t & 1u << 26) - (want >> 4);
    uint32_t o0[J], o1[J], g = 0;
#pragma unroll
    for (int j = 0; j < J; j++) {
        o0[j] = 0; o1[j] = 0;
        if (xor_and<0x7fffffffu>(rec[j].y, want) < 0x0ffc0000u) {
            const uint32_t a = aux_of(rec[j].x, rec[j].y, k);
            const uint32_t v0 = (rec[j].x & 0x0fff0fffu) - 0x08000800u, v1 = (rec[j].y & 0x0fff0fffu) - 0x08000800u;
            o0[j] = atoms_add<OFF_ACC>(sb + a, mux(v0, v1, t));
            o1[j] = atoms_add<OFF_ACC>(sb + (a ^ 4u), mux(v1, v0, t));
        }
    }
#pragma unroll
    for (int j = 0; j < J; j++) g |= o0[j] | o1[j];
    if (RARE(__any_sync(0xffffffffu, g & 0x80008000u))) {
#pragma unroll 1
        for (int j = 0; j < J; j++) {
            const uint2 w = pick(j, rec);
            const uint32_t aux = aux_of(w.x, w.y), p0 = pick(j, o0), p1 = pick(j, o1);
            const float2 a = acc_fix(t ? p1 : p0, w.x & 0x0fff0fffu), b = acc_fix(t ? p0 : p1, w.y & 0x0fff0fffu);
            const float unit = __uint_as_float(lds32(sb + W_UNIT));
            if (xor_and<0x7fffffffu>(w.y, want) < 0x0ffc0000u && (a.x != 0.f || a.y != 0.f || b.x != 0.f || b.y != 0.f)) {
                side_add(lds32(sb + W_ROLE), aux >> 3, a.x * unit, a.y * unit, b.x * unit, b.y * unit);
                sts32(sb + W_WRAP, 1u);
            }
            __syncwarp();
        }
    }
}
__device__ __forceinline__ void stage3(const Params& p, uint32_t sb, int w, int lane, int role, uint32_t base) {
    const int RT = p.rounds + 1;
    Reader<2> rd;
    rd.init(p, sb, w, lane, role, base);
    uint2 rec[J];
    TK_DECL
#pragma unroll 1
    for (int r = 0; r < RT; r++) {
        rd.load(rec);
        rd.check(rec, base + r, r < RT - 2 ? POLL_NS3 : 100, lane TK_PASS);
        RTS((r & 127) == 41 && w == 0, 1 + (r >> 7))
        TK(0)
        add_recs(sb, lane, rec, H<2>::tag(base + r));
        TK(1)
        if (RARE((uint32_t)(r - (RT - LATE + 1)) < 2u)) {
            static_assert(BOX == 32, "box");
            float4* box = reinterpret_cast<float4*>(g_box) + (lds32(sb + W_ROLE) * NB + (w * 2 + r - (RT - LATE + 1)) * J) * (BOX / 2) + lane;
            TKY(0)
#pragma unroll
            for (int j = 0; j < J / 2; j++) {
                const float4 v = ld_rlx128f(box + j * 32);
                rec[2 * j] = make_uint2(__float_as_uint(v.x), __float_as_uint(v.y)); rec[2 * j + 1] = make_uint2(__float_as_uint(v.z), __float_as_uint(v.w));
            }
#pragma unroll
            for (int j = 0; j < J / 2; j++) if (rec[2 * j].x) box[j * 32] = make_float4(0.f, 0.f, 0.f, 0.f);
            add_recs(sb, lane, rec, H<2>::TAG);
            TKY(1)
        }
    }
    rd.finish();
    TK_OUT
}

__device__ __forceinline__ uint32_t row_max(uint32_t x, uint32_t y) {
    const uint32_t mx = __vmaxu2(x & 0x7fff7fffu, y & 0x7fff7fffu);
    return max(mx & 0xffffu, mx >> 16);
}
__device__ __forceinline__ uint32_t amax2(uint32_t a, uint32_t b) {
    uint32_t r; asm("max.NaN.xorsign.abs.bf16x2 %0, %1, %2;" : "=r"(r) : "r"(a), "r"(b)); return r;
}
constexpr int NTAB = 9, TABC = 2 * NC * 32 * 16;
__device__ __forceinline__ void load_piece(const Params& p, uint32_t sb, int role, int i) {
    const int r0 = (role >= NG ? role - NG : role) * p.R1, n = max(min(min(p.R1, p.E - r0) * 8 - i * TABC, TABC), 0);
    asm volatile("mbarrier.arrive.expect_tx.shared::cta.b64 _, [%0], %1;" ::"r"(sb + B_TAB + i * 8), "r"(n) : "memory");
    if (n) asm volatile("cp.async.bulk.shared::cluster.global.mbarrier::complete_tx::bytes [%0], [%1], %2, [%3];"
                        ::"r"(sb + OFF_M + i * TABC), "l"(p.m + r0 + i * (TABC / 8)), "r"(n), "r"(sb + B_TAB + i * 8) : "memory");
}
static_assert(NTAB * TABC >= R1MAX * 8 && NTAB * TABC - TABC / 2 <= R1MAX * 8, "table");
constexpr int EWIN = 5;

__global__ void __launch_bounds__(NTHR, 1) fused_kernel(const Params p) {
    const int tid = threadIdx.x, lane = tid & 31;
    const int hw = __reduce_max_sync(0xffffffffu, tid >> 5);
    const uint32_t sb = __reduce_or_sync(0xffffffffu, (uint32_t)__cvta_generic_to_shared(smem));
    TKX(0)
    RTS(tid == 0, 0)
    uint32_t cta;
    asm volatile("mov.u32 %0, %%ctaid.x;" : "=r"(cta));
    if (hw != W_M1 && hw != W_M2) {
        const int job = hw < W_M1 ? hw : hw - 1;
        if (lane == 0 && job < 2 * NPAGE + 2)
            sts32(sb + OFF_PROBE + job * 4, probe(p.ring + (size_t)max(job / 2 - 1, 0) * PAGE + PROBE + (cta & 31) * 128 + (cta >> 5 & 3) * 16384 + (cta >> 7 << 20) +
                                                  ((job & 1) << 12 ^ (job < 2 ? 0x3000 : 0)), p.zero));
        if (job < 4) bar_arrive(BAR_SIDE, 5 * 32); else bar_arrive(BAR_PROBE, 27 * 32);
        TKX(1)
    }
    if (hw < NS1) {
        stage1(p, sb, hw * 128 + lane, lane, hw == NS1 - 1);
    } else if (hw == W_M1) {
        const uint32_t epoch = ld_rlx32(reinterpret_cast<const uint32_t*>(p.ring + M_BASE)) ^ 33u;
        if (lane == 0) {
            if (sb & 255u) __trap();
            mbar_init(sb + B_FULL, NS1); mbar_init(sb + B_OPEN, 1); mbar_init(sb + B_FREE, 1); mbar_init(sb + B_TFREE, NC); mbar_init(sb + B_FLAG, 32); mbar_init(sb + B_INIT, 1); sts32(sb + W_ITEM, NS1);
            for (int i = 0; i < NTAB; i++) mbar_init(sb + B_TAB + i * 8, 1);
            asm volatile("fence.proxy.async.shared::cta;" ::: "memory");
        }
        const uint32_t base = __reduce_or_sync(0xffffffffu, epoch) & 31u;
        if (lane == 0) { sts32(sb + W_BASE, epoch); sts64(sb + W_NLIST, 0u, 0u); }
        if (lane == 0 && (base & 1u)) { mbar_arrive(sb + B_OPEN); mbar_arrive(sb + B_FREE); }
        bar_arrive(BAR_BASE, (NC + 1) * 32);
        TKY(5)
        bar_sync(BAR_SIDE, 5 * 32);
        TKY(6)
        {
            const uint2 la = lds64<OFF_PROBE>(sb), lb = lds64<OFF_PROBE + 8>(sb);
            const uint32_t side = min(la.y, lb.y) < min(la.x, lb.x);
            uint32_t v = 0;
            if (lane == 0) {
                asm volatile("atom.relaxed.gpu.global.add.u32 %0, [%1], %2;" : "=r"(v) : "l"(p.ring + M_CNT), "r"(side ? 0x10000u : 1u) : "memory");
                asm volatile("red.relaxed.gpu.global.add.u32 [%0], %1;" ::"l"(p.ring + M_CNT + 4096), "r"(side ? 0x10000u : 1u) : "memory");
            }
            bar_sync(BAR_PROBE, 27 * 32);
            const uint2 l = lds64<OFF_PROBE + 8>(sb + min(lane, NPAGE - 1) * 8);
            const uint32_t mine = (__ballot_sync(0xffffffffu, (l.y < l.x) != side) & ~1u) | 0x80000000u;
            if (lane == 0) {
                uint32_t par;
                asm volatile("atom.relaxed.gpu.global.cas.b32 %0, [%1], 0, %2;" : "=r"(par) : "l"(p.ring + M_PAR), "r"(mine) : "memory");
                const uint32_t role = side ? NB - 1 - (v >> 16) : v & 0xffffu;
#pragma unroll 1
                for (int i = 0; i < AHEAD; i++) load_piece(p, sb, role, i);
                sts32(sb + W_ROLE, role); sts32(sb + W_SIDE, role < NLO ? 0u : role >= NHI ? 1u : side);
                sts32(sb + W_END, (epoch | 1023u) + 1u + (base + p.rounds) % 24u + ((epoch >> 5 & 31u) + p.rounds + 1) % 24u * 32u);
                sts32(sb + W_PAR, par ? par : mine);
            }
            TKX(2)
        }
        bar_arrive(BAR_PAR, (2 * NC + 2) * 32);
        manager<1>(p, sb, opaque(lane), __reduce_max_sync(0xffffffffu, lds32(sb + W_ROLE)), base);
        asm volatile("cp.async.bulk.wait_group 0;" ::: "memory");
        bar_arrive(BAR_H1, (NS1 + 1) * 32);
        TKX(4)
        {
            const int role = lds32(sb + W_ROLE);
#pragma unroll 1
            for (int i = lane * 16; i < DROW; i += NPF * 512) {
                float4 f[NPF];
#pragma unroll
                for (int u = 0; u < NPF; u++) f[u] = ld_rlx128f(reinterpret_cast<const float4*>(g_dirty + role * DROW + i + u * 512));
#pragma unroll
                for (int u = 0; u < NPF; u++) {
                    if (__float_as_uint(f[u].x) | __float_as_uint(f[u].y)) prefetch_l2(g_ovf + role * RPAD + i + u * 512);
                    if (__float_as_uint(f[u].z) | __float_as_uint(f[u].w)) prefetch_l2(g_ovf + role * RPAD + i + u * 512 + 8);
                }
            }
        }
        bar_sync(BAR_DONE, (NE + 1) * 32);
        TKY(0)
        const uint32_t flag = lds32(sb + W_END) >> 10 & 0xffffu;
        if (lane < 2) {
            fence_gpu();
            asm volatile("st.relaxed.gpu.global.u16 [%0], %1;" ::"l"(p.ring + M_FLAG + lane * 4096 + blockIdx.x * 2), "h"((uint16_t)flag) : "memory");
        }
        TKY(1)
        __syncwarp();
        bar_arrive(BAR_ROWS, 64);
        wait_flags(p, sb, lane, flag * 0x10001u);
        TKX(5)
        mbar_arrive(sb + B_FLAG);
        if (blockIdx.x == 0) {
            if (lane == 0) *reinterpret_cast<uint32_t*>(p.ring + M_BASE) = lds32(sb + W_END) ^ 33u;
            if (lane < 3) *reinterpret_cast<uint32_t*>(p.ring + (lane & 2 ? M_PAR : M_CNT + (lane & 1) * 4096)) = 0;
        }
    } else if (hw == W_M2) {
        uint2 sm[16];
#pragma unroll
        for (int i = 0; i < 8; i++) ld_in4(p.m + 2 * min((i * 8 + (lane >> 2)) * (p.E >> 7) + (lane & 3), (p.E >> 1) - 1), sm[2 * i], sm[2 * i + 1]);
        const float wd = __bfloat162float(lane & 16 ? p.w_up[lane & 15] : p.w_down[lane & 15]);
        const uint16_t* wg = reinterpret_cast<const uint16_t*>(lane & 16 ? p.w_rbf : p.w_sbf) + (lane & 3) * 8 + (lane >> 2 & 3);
        const uint16_t* cp = reinterpret_cast<const uint16_t*>(p.centers) + (lane & 3) * 2;
        const uint32_t w0 = __ldg(wg), w1 = __ldg(wg + 4), c0 = __ldg(cp), c1 = __ldg(cp + 1);
        if (lane == 0) { mbar_init(sb + B_FULL + 8, NC); mbar_init(sb + B_OPEN + 8, 1); mbar_init(sb + B_ROWS, 1); }
        sts128<OFF_HIST>(sb + lane * 16, make_uint4(0u, 0u, 0u, 0u)); sts128<OFF_HIST + 512>(sb + lane * 16, make_uint4(0u, 0u, 0u, 0u));
        __syncwarp();
#pragma unroll
        for (int i = 0; i < 16; i++) atoms_add<OFF_HIST>(sb + (row_max(sm[i].x, sm[i].y) >> 7) * 4, 1u);
        __syncwarp();
        uint32_t best = 0;
#pragma unroll 1
        for (int e = 11 + lane; e <= 230; e += 32) {
            uint32_t c = 0;
#pragma unroll
            for (int i = 0; i < EWIN; i++) c += lds32(sb + OFF_HIST + (e - i) * 4);
            best = max(best, c << 8 | (255 - e));
        }
        const uint32_t e = 255 - (__reduce_max_sync(0xffffffffu, best) & 255u);
        if (lane == 0) { sts32(sb + W_EXP, e); sts32(sb + W_UNIT, (e - 10) << 23); }
        reinterpret_cast<float*>(smem + OFF_WSM)[lane] = wd;
        const int wi = (lane & 4) * 4 + (lane & 1) * 8 + (lane & 2) + (lane >> 3 & 1);
        const uint32_t fr = __byte_perm(__float_as_uint(__shfl_sync(0xffffffffu, wd, wi)), __float_as_uint(__shfl_sync(0xffffffffu, wd, wi + 4)), 0x7632);
        if (lane < 16) sts32(sb + OFF_WB + lane * 4, fr);
        sts64(sb + OFF_WG + lane * 8, w0 | w1 << 16, c0 | c1 << 16);
        TKY(5)
        bar_sync(BAR_PAR, (2 * NC + 2) * 32);
        if (lane == 0) mbar_arrive(sb + B_INIT);
        manager<2>(p, sb, opaque(lane), __reduce_max_sync(0xffffffffu, lds32(sb + W_ROLE)), __reduce_or_sync(0xffffffffu, lds32(sb + W_BASE)) >> 5 & 31u);
        TKX(4)
        asm volatile("cp.async.bulk.wait_group.read 0;" ::: "memory");
        bar_sync(BAR_ROWS, 64);
        if (lane == 0) {
            const int row0 = lds32(sb + W_ROLE) * p.R2, np = min(p.R2, p.E - row0) >> 1, off = row0 * 8 & 127;
            asm volatile("mbarrier.arrive.expect_tx.shared::cta.b64 _, [%0], %1;" ::"r"(sb + B_ROWS), "r"(max(np, 0) * 16 + (max(np, 0) + NG0 - 1) / NG0 * off) : "memory");
#pragma unroll 1
            for (int k = 0; k < np; k += NG0)
                asm volatile("cp.async.bulk.shared::cluster.global.mbarrier::complete_tx::bytes [%0], [%1], %2, [%3];"
                             ::"r"(sb + H<2>::win(k / NG0)), "l"(p.m + (row0 - off / 8 + 2 * k)), "r"(min(np - k, NG0) * 16 + off), "r"(sb + B_ROWS) : "memory");
        }
        asm volatile("cp.async.bulk.wait_group 0;" ::: "memory");
    } else {
        const int w = __reduce_max_sync(0xffffffffu, hw < W_M1 ? hw - NS1 : hw - W_M1 - 1), ct = w * 32 + lane;
        if (hw < W_M1) {
            bar_sync(BAR_BASE, (NC + 1) * 32);
            const uint32_t b1 = lds32(sb + W_BASE) & 31u, b2 = lds32(sb + W_BASE) >> 5 & 31u;
            if (ct < NG + NDUM) sts32(sb + OFF_CNT1 + ct * 4, ct < NG ? H<1>::init(b1) + (ct & 7) * 16 : DUMMY);
            if (ct <= NB + NDUM) sts32(sb + OFF_CNT2 + ct * 4, ct < NB ? H<2>::init(b2) + (ct & 7) * 16 : DUMMY);
            fill<1>(sb + OFF_H1 + H<1>::win(b1), ct, b1); fill<1>(sb + OFF_H1 + H<1>::win(b1 + 1), ct, b1 + 1);
            bar_arrive(BAR_S1, (NS1 + NC) * 32);
#pragma unroll
            for (int i = 0; i < 3; i++) fill<2>(sb + H<2>::win(i), ct, b2 + i);
        }
        bar_sync(BAR_PAR, (2 * NC + 2) * 32);
        TKY(4)
        const int role = __reduce_max_sync(0xffffffffu, lds32(sb + W_ROLE));
        const uint32_t epoch = __reduce_or_sync(0xffffffffu, lds32(sb + W_BASE));
        if (hw < W_M1) {
            for (int i = ct; i < R2MAX / 2; i += NC * 32) reinterpret_cast<uint4*>(smem + OFF_ACC)[i] = make_uint4(0x40004000u, 0x40004000u, 0x40004000u, 0x40004000u);
            mbar_wait(sb + B_TAB + KDRY * 8, 0);
            stage2(p, sb, w, opaque(lane), role, (epoch & 31u) - 1u, epoch >> 5 & 31u);
        } else {
            const int e = lds32(sb + W_EXP);
            const uint32_t sc = (uint32_t)(254 - e) * 0x800080u, top = (e << 7 | 0x807fu) * 0x10001u;
            auto conv = [&](uint32_t& x, uint32_t& y) {
                const uint32_t mx = row_max(x, y);
                const int d = e - (int)(mx >> 7);
                x = hmul_bf2(x, sc); y = hmul_bf2(y, sc);
                if (d >= EWIN) y |= 0x40000000u;
                if (d < 0 || (d >= EWIN && e > 127)) { x = 0x40000000u; y = x; }
                if (mx == 0) { x = 0; y = 0; }
            };
#pragma unroll 1
            for (int i = 0; i < NTAB; i++) {
                mbar_wait(sb + B_TAB + i * 8, 0);
                if (ct == 0 && i < NTAB - AHEAD) load_piece(p, sb, role, i + AHEAD);
                const uint32_t t = sb + OFF_M + i * TABC + ct * 16, t1 = t + TABC / 2 < sb + OFF_M + R1MAX * 8 ? t + TABC / 2 : t;
                uint4 v[2] = {lds128(t), lds128(t1)};
                uint32_t ok = ~0u;
#pragma unroll
                for (int u = 0; u < 2; u++) {
                    const uint32_t a = amax2(v[u].x, v[u].y), b = amax2(v[u].z, v[u].w), mx = amax2(__byte_perm(a, b, 0x5410), __byte_perm(a, b, 0x7632)) & 0x7fff7fffu;
                    ok &= (top - mx) ^ (top - EWIN * 0x800080u - mx);
                }
                if (RARE(~ok & 0x80008000u)) {
#pragma unroll 1
                    for (int u = 0; u < 4; u++) {
                        conv(v[0].x, v[0].y);
                        const uint2 f = make_uint2(v[0].x, v[0].y);
                        v[0] = make_uint4(v[0].z, v[0].w, v[1].x, v[1].y); v[1] = make_uint4(v[1].z, v[1].w, f.x, f.y);
                    }
                } else {
#pragma unroll
                    for (int u = 0; u < 2; u++) v[u] = make_uint4(hmul_bf2(v[u].x, sc), hmul_bf2(v[u].y, sc), hmul_bf2(v[u].z, sc), hmul_bf2(v[u].w, sc));
                }
                sts128<0>(t, v[0]); sts128<0>(t1, v[1]);
                __syncwarp();
            }
            TKX(3)
            bar_sync(BAR_TABLE, 2 * NC * 32);
            stage3(p, sb, w, opaque(lane), role, epoch >> 5 & 31u);
            TKX(4)
            bar_sync(BAR_ACC, (NE + NC) * 32);
            if (!lds32(sb + W_WRAP)) {
                int i;
                asm volatile("mov.u32 %0, %%tid.x;" : "=r"(i));
                const int ro = lds32(sb + W_ROLE);
#pragma unroll 1
                for (i -= (W_M1 + 1) * 32; i < DROW / 16; i += NC * 32) {
                    float4* f = reinterpret_cast<float4*>(g_dirty + ro * DROW) + i;
                    const float4 v = ld_rlx128f(f);
                    uint32_t m = __float_as_uint(v.x) | __float_as_uint(v.y) << 1 | __float_as_uint(v.z) << 2 | __float_as_uint(v.w) << 3;
                    if (m) *f = make_float4(0.f, 0.f, 0.f, 0.f);
#pragma unroll 1
                    for (; m; m &= m - 1) {
                        const int b = __ffs(m) - 1;
                        g_ovf[ro * RPAD + i * 16 + (b & 3) * 4 + (b >> 3)] = make_float4(0.f, 0.f, 0.f, 0.f);
                    }
                }
            }
        }
    }
    if (hw < W_M1) {
        bar_arrive(BAR_DONE, (NE + 1) * 32);
        __syncwarp();
        TKX(4)
        finish_rows(p, sb, hw < NS1);
    }
}

__global__ void fb_scatter(const uint2* __restrict__ m, const int* __restrict__ idx_in, const int* __restrict__ idx_out,
                           const uint16_t* __restrict__ angle, const __nv_bfloat16* __restrict__ ang_freq, int T, int e0, int e1) {
    const uint32_t fb = *reinterpret_cast<const uint16_t*>(ang_freq);
    for (long long t = blockIdx.x * (long long)blockDim.x + threadIdx.x; t < T; t += (long long)gridDim.x * blockDim.x) {
        int o = idx_out[t];
        if (o < e0 || o >= e1) continue;
        float c = bf16r(cos_bf(hmul_bf2(angle[t], fb) & 0xffffu));
        uint2 v = __ldg(m + idx_in[t]);
        red4(&g_ovf[o - e0], c * bf_lo(v.x), c * bf_hi(v.x), c * bf_lo(v.y), c * bf_hi(v.y));
    }
}
__global__ void fb_final(const Params p, int e0, int e1) {
    int e = e0 + blockIdx.x * blockDim.x + threadIdx.x;
    if (e >= e1) return;
    float4 a4 = g_ovf[e - e0];
    g_ovf[e - e0] = make_float4(0.f, 0.f, 0.f, 0.f);
    float a[4] = {a4.x, a4.y, a4.z, a4.w};
    float d = __bfloat162float(p.dist[e]);
    float g[4] = {0, 0, 0, 0}, h[4] = {0, 0, 0, 0};
    for (int r = 0; r < 8; r++) {
        float df = bf16r(d - __bfloat162float(p.centers[r]));
        float rb = bf16r(expf(bf16r(-10.0f * bf16r(df * df))));
        for (int k = 0; k < 4; k++) {
            g[k] += rb * __bfloat162float(p.w_sbf[r * 4 + k]);
            h[k] += rb * __bfloat162float(p.w_rbf[r * 4 + k]);
        }
    }
    float ag[4];
    for (int k = 0; k < 4; k++) {
        float s = 0.f;
        for (int j = 0; j < 4; j++) s += a[j] * __bfloat162float(p.w_down[j * 4 + k]);
        ag[k] = bf16r(s * g[k]);
    }
    uint2 mv = p.m[e];
    float mm[4] = {bf_lo(mv.x), bf_hi(mv.x), bf_lo(mv.y), bf_hi(mv.y)};
    __nv_bfloat16 o[4];
    for (int k = 0; k < 4; k++) {
        float u = 0.f;
        for (int j = 0; j < 4; j++) u += ag[j] * __bfloat162float(p.w_up[j * 4 + k]);
        o[k] = __float2bfloat16_rn(mm[k] + bf16r(bf16r(u) * bf16r(h[k])));
    }
    p.out[e] = *reinterpret_cast<uint2*>(o);
}

}

static cudaTextureObject_t make_tex(const void* ptr, size_t bytes, int words) {
    cudaResourceDesc rd = {}; cudaTextureDesc td = {};
    rd.resType = cudaResourceTypeLinear; rd.res.linear.devPtr = const_cast<void*>(ptr); rd.res.linear.sizeInBytes = bytes;
    rd.res.linear.desc = cudaCreateChannelDesc(32, words > 1 ? 32 : 0, words > 2 ? 32 : 0, words > 2 ? 32 : 0, cudaChannelFormatKindUnsigned);
    td.readMode = cudaReadModeElementType;
    cudaTextureObject_t t = 0;
    if (cudaCreateTextureObject(&t, &rd, &td, nullptr) != cudaSuccess) { t = 0; (void)cudaGetLastError(); }
    return t;
}

extern "C" void kernel_launch(void* const* d_in, const int* in_sizes, int n_in, void* d_out, int out_size) {
    typedef const __nv_bfloat16* B;
    Params p;
    p.m = (const uint2*)d_in[0]; p.idx_in = (const uint2*)d_in[1]; p.idx_out = (const uint2*)d_in[2]; p.dist = (B)d_in[3];
    p.angle = (const uint32_t*)d_in[4]; p.centers = (B)d_in[5]; p.ang_freq = (B)d_in[6]; p.w_rbf = (B)d_in[7]; p.w_sbf = (B)d_in[8];
    p.w_down = (B)d_in[9]; p.w_up = (B)d_in[10]; p.out = (uint2*)d_out;
    p.E = in_sizes[3]; p.T = in_sizes[1]; p.T2 = p.T >> 1; p.zero = 0;
    p.R1 = p.R2 = p.rounds = p.lastn = p.full = 0; p.i1 = p.i2 = p.k1 = p.k2 = 0.f;
    static int ok = -1;
    static unsigned char* ring = nullptr;
    if (ok < 0) {
        void* ra = nullptr;
        cudaGetSymbolAddress(&ra, g_ring);
        ring = reinterpret_cast<unsigned char*>(((uintptr_t)ra + PAGE - 1) & ~(uintptr_t)(PAGE - 1));
        int dev = 0, sms = 0, occ = 0;
        cudaGetDevice(&dev);
        cudaDeviceGetAttribute(&sms, cudaDevAttrMultiProcessorCount, dev);
        cudaError_t e = cudaFuncSetAttribute(fused_kernel, cudaFuncAttributeMaxDynamicSharedMemorySize, SMEM_BYTES);
        if (e == cudaSuccess) e = cudaOccupancyMaxActiveBlocksPerMultiprocessor(&occ, fused_kernel, NTHR, SMEM_BYTES);
        ok = (e == cudaSuccess && occ >= 1 && sms >= NB) ? 1 : 0;
        (void)cudaGetLastError();
    }
    p.ring = ring;
    static cudaTextureObject_t tx[3];
    static const void* of[3];
    static int of_t = -1;
    if (of[0] != d_in[1] || of[1] != d_in[2] || of[2] != d_in[4] || of_t != p.T) {
        tx[0] = make_tex(p.idx_in, (size_t)(p.T >> 2) * 16, 4); tx[1] = make_tex(p.idx_out, (size_t)(p.T >> 2) * 16, 4); tx[2] = make_tex(p.angle, (size_t)(p.T >> 2) * 8, 2);
        of[0] = d_in[1]; of[1] = d_in[2]; of[2] = d_in[4]; of_t = p.T;
    }
    p.ti = tx[0]; p.to = tx[1]; p.ta = tx[2];
    const bool fused = ok == 1 && p.E <= EMAX && p.E >= 2 * NB && p.E % 2 == 0 && p.T >= 2;
    if (fused) {
        p.R1 = ((p.E + NG - 1) / NG + 1) & ~1;
        if (p.R1 > 1024) p.R1 = (p.R1 + 15) & ~15;
        p.R2 = ((p.E + NB - 1) / NB + 1) & ~1;
        p.i1 = nextafterf(1.f / p.R1, 2.f); p.i2 = nextafterf(1.f / p.R2, 2.f); p.k1 = -(float)p.R1; p.k2 = -8.f * p.R2;
        const int per = NB * NPR;
        int full = p.T2 / per, rest = p.T2 - full * per;
        p.full = p.ti && p.to && p.ta ? full : 0;
        p.lastn = (rest + NB - 1) / NB;
        if (p.lastn > NPR / 2) { full++; p.lastn = 0; }
        if (full < D) { full = D; p.lastn = 0; }
        p.rounds = full + 1;
        fused_kernel<<<NB, NTHR, SMEM_BYTES>>>(p);
    } else {
        for (int e0 = 0; e0 < p.E; e0 += EMAX) {
            int e1 = p.E - e0 < EMAX ? p.E : e0 + EMAX;
            fb_scatter<<<1056, 256>>>(p.m, (const int*)d_in[1], (const int*)d_in[2], (const uint16_t*)d_in[4], p.ang_freq, p.T, e0, e1);
            fb_final<<<(e1 - e0 + 255) / 256, 256>>>(p, e0, e1);
        }
    }
}
```

```cpp
#include <cuda_runtime.h>
#include <cuda_bf16.h>
#include <stdint.h>
#include <math.h>

#define RARE(x) __builtin_expect(!!(x), 0)
namespace {

constexpr int NB = 132, NG = 66;
constexpr int R2MAX = 6062, R1MAX = 12128;
constexpr int EMAX = NB * R2MAX;
constexpr int NTHR = 1024;
constexpr int NS1 = 8, NC = 11, J = 6;
constexpr int NPR = 960;
constexpr int D = 3;
constexpr int WIN = 16896;
constexpr int NDUM = 16;
constexpr uint32_t DUMMY = 0xc0000000u;
constexpr int AHEAD = 3, KDRY = 4, NPF = 6, NPROBE = 2, POLL_NS = 200, POLL_NS3 = 400;

constexpr int OFF_ACC = WIN, OFF_BAR = OFF_ACC + R2MAX * 8;
constexpr int OFF_H1 = 0x10000 + WIN, OFF_M = OFF_H1 + WIN, OFF_PROBE = OFF_M + R1MAX * 8;
constexpr int OFF_CNT1 = OFF_H1 + 0x20000 + WIN, OFF_CNT2 = OFF_CNT1 + (NG + NDUM + 2) * 4;
constexpr int OFF_HIST = OFF_ACC;
constexpr int OFF_WSM = OFF_CNT2 + (NB + NDUM) * 4 + 16;
constexpr int OFF_WB = OFF_WSM + 128, OFF_WG = OFF_WB + 64;
constexpr int SMEM_BYTES = OFF_WG + 256;
static_assert(SMEM_BYTES <= 232448 && OFF_BAR + 64 <= 0x10000 && OFF_PROBE + 256 <= 0x30000, "smem");
static_assert(OFF_BAR % 8 == 0 && OFF_WSM % 16 == 0 && OFF_CNT2 % 16 == 0, "align");
static_assert(NC * J == NG && NC * 32 * 6 * 16 == 2 * WIN, "shape");

template <int HOP> struct H {
    static constexpr int S = HOP == 1 ? 32 : 16, NBIN = HOP == 1 ? NG : NB, CAP = 2 * S, SH = HOP == 1 ? 11 : 12;
    static constexpr int TB = HOP == 1 ? 17 : 28, CNT = HOP == 1 ? OFF_CNT1 : OFF_CNT2, STG = HOP == 1 ? OFF_H1 : 0;
    static constexpr uint32_t INC = (1u << SH) + 8u, PM = (S - 1) * 8, TAG = 7u << TB;
    static __device__ __forceinline__ uint32_t tag(uint32_t R) { return R << TB & TAG; }
    static __device__ __forceinline__ uint32_t init(uint32_t R) { return tag(R) | ((1u << TB) - 0x10000u); }
    static __device__ __forceinline__ uint32_t mark(uint32_t R, uint32_t line) { return ((HOP == 1 ? R >> 1 : R) + line) & 3u; }
    static __device__ __forceinline__ uint32_t win(int r) { return HOP == 1 ? (r & 1) << 17 : (0x310u >> (r % 3 * 4) & 3u) << 16; }
};

constexpr uint32_t PAGE = 1u << 21;
constexpr int NPAGE = NC + 2;
__device__ __align__(256) unsigned char g_ring[(size_t)(NPAGE + 1) * PAGE];
constexpr int MISC = 0xa0000;
constexpr int M_CNT = MISC + 1024, M_PAR = M_CNT + 4;
constexpr int M_BASE = M_CNT + 8;
constexpr int M_FLAG = MISC + 2048;
constexpr int PROBE = MISC + 0x40000;
__device__ __forceinline__ uint32_t cred_off(uint32_t role) { return role * 4 + min(role >> 5, 3u) * (16384 - 128); }
struct Ring {
    uint64_t main, mid;
    uint32_t par;
    __device__ __forceinline__ Ring(const unsigned char* ring, uint32_t pars, int k) {
        main = reinterpret_cast<uint64_t>(ring) + ((uint64_t)k << 20);
        par = pars >> (k >> 1) & 1u;
        mid = reinterpret_cast<uint64_t>(ring) + (uint64_t)NC * PAGE + (((k >> 3 << 20) + (k >> 2 & 1) * 0x11000u + (k & 1) * 2048) ^ (k >> 1 & 1) * 0x3000u ^ (pars >> (NC + (k >> 4)) & 1u) << 12);
    }
};
constexpr int NLO = 60, NHI = 72;
__host__ __device__ constexpr uint32_t src_off(int j) { return (j % 3) << 14 | (j / 3) << 18; }
__device__ __forceinline__ uint32_t slot_off(uint32_t s) { return (0xa930u >> s * 4 & 15u) << 16; }
__device__ __forceinline__ uint32_t slot_steps(uint32_t R) { return (uint32_t)(0x30a09030aull >> (2 - R % 3) * 8) & 0xffffffu; }
__device__ __forceinline__ void slot_next(uint32_t& a, uint32_t st) { a ^= st & 0xf0000u; }
__device__ __forceinline__ uint32_t slot_rot(uint32_t st) { return __byte_perm(st, 0u, 0x4102); }
constexpr int RPAD = 6064, DROW = 6144;
__device__ __align__(128) uint8_t g_dirty[NB * DROW];
constexpr int BOX = 32, BOXN = 24, LATE = 8;
__device__ __align__(128) uint2 g_box[NB * NB * BOX];
__device__ __align__(128) float4 g_ovf[NB * RPAD];

struct Params {
    const uint2* m; const uint2* idx_in; const uint2* idx_out; const __nv_bfloat16* dist; const uint32_t* angle;
    const __nv_bfloat16* centers; const __nv_bfloat16* ang_freq; const __nv_bfloat16* w_rbf; const __nv_bfloat16* w_sbf;
    const __nv_bfloat16* w_down; const __nv_bfloat16* w_up; uint2* out; unsigned char* ring;
    cudaTextureObject_t ti, to, ta;
    int E, T, T2, R1, R2, rounds, lastn, full; uint32_t zero; float i1, i2, k1, k2;
};

__device__ __forceinline__ float bf16r(float x) { return __bfloat162float(__float2bfloat16_rn(x)); }
__device__ __forceinline__ float bf_lo(uint32_t v) { return __uint_as_float(v << 16); }
__device__ __forceinline__ float bf_hi(uint32_t v) { return __uint_as_float(v & 0xffff0000u); }
__device__ __forceinline__ void red4(float4* a, float x, float y, float z, float w) {
    asm volatile("red.global.add.v4.f32 [%0], {%1,%2,%3,%4};" ::"l"(a), "f"(x), "f"(y), "f"(z), "f"(w) : "memory");
}
__device__ __forceinline__ void bar_sync(int id, int n) { __syncwarp(); asm volatile("bar.sync %0, %1;" ::"r"(id), "r"(n) : "memory"); }
__device__ __forceinline__ void bar_arrive(int id, int n) { __syncwarp(); asm volatile("bar.arrive %0, %1;" ::"r"(id), "r"(n) : "memory"); }
template <int OFF> __device__ __forceinline__ uint32_t atoms_add(uint32_t addr, uint32_t v) {
    uint32_t r; asm volatile("atom.shared.add.u32 %0, [%1+%3], %2;" : "=r"(r) : "r"(addr), "r"(v), "n"(OFF) : "memory"); return r;
}
__device__ __forceinline__ void sts64(uint32_t addr, uint32_t x, uint32_t y) {
    asm volatile("st.shared.v2.u32 [%0], {%1,%2};" ::"r"(addr), "r"(x), "r"(y) : "memory");
}
__device__ __forceinline__ void sts32(uint32_t addr, uint32_t x) { asm volatile("st.shared.u32 [%0], %1;" ::"r"(addr), "r"(x) : "memory"); }
template <int OFF = 0> __device__ __forceinline__ uint2 lds64(uint32_t addr) {
    uint2 v; asm volatile("ld.shared.v2.u32 {%0,%1}, [%2+%3];" : "=r"(v.x), "=r"(v.y) : "r"(addr), "n"(OFF) : "memory"); return v;
}
__device__ __forceinline__ uint32_t lds32(uint32_t addr) {
    uint32_t v; asm volatile("ld.shared.u32 %0, [%1];" : "=r"(v) : "r"(addr) : "memory"); return v;
}
template <int OFF> __device__ __forceinline__ void sts128(uint32_t a, const uint4& v) {
    asm volatile("st.shared.v4.u32 [%0+%5], {%1,%2,%3,%4};" ::"r"(a), "r"(v.x), "r"(v.y), "r"(v.z), "r"(v.w), "n"(OFF) : "memory");
}
__device__ __forceinline__ uint4 lds128(uint32_t a) {
    uint4 v; asm volatile("ld.shared.v4.u32 {%0,%1,%2,%3}, [%4];" : "=r"(v.x), "=r"(v.y), "=r"(v.z), "=r"(v.w) : "r"(a) : "memory"); return v;
}
__device__ __forceinline__ uint32_t ld_rlx32(const uint32_t* p) {
    uint32_t v; asm volatile("ld.relaxed.gpu.global.u32 %0, [%1];" : "=r"(v) : "l"(p) : "memory"); return v;
}
__device__ __forceinline__ uint2 ld_rlx64(const void* p) {
    uint2 v; asm volatile("ld.relaxed.gpu.global.v2.u32 {%0,%1}, [%2];" : "=r"(v.x), "=r"(v.y) : "l"(p) : "memory"); return v;
}
__device__ __forceinline__ float4 ld_rlx128f(const float4* p) {
    float4 v; asm volatile("ld.relaxed.gpu.global.v4.f32 {%0,%1,%2,%3}, [%4];" : "=f"(v.x), "=f"(v.y), "=f"(v.z), "=f"(v.w) : "l"(p) : "memory"); return v;
}
__device__ __forceinline__ float4 take(float4* p, bool q) {
    float4 v;
    asm volatile("{ .reg .b128 a; .reg .b64 x, y; .reg .pred q; mov.b64 x, 0; mov.b128 a, {x, x}; setp.ne.u32 q, %5, 0;\n"
                 "@q atom.relaxed.gpu.global.exch.b128 a, [%4], a; mov.b128 {x, y}, a; mov.b64 {%0,%1}, x; mov.b64 {%2,%3}, y; }"
                 : "=f"(v.x), "=f"(v.y), "=f"(v.z), "=f"(v.w) : "l"(p), "r"((uint32_t)q) : "memory");
    return v;
}
__device__ __forceinline__ void fence_gpu() { asm volatile("fence.acq_rel.gpu;" ::: "memory"); }
__device__ __forceinline__ void st_rlx32(uint32_t* p, uint32_t v) { asm volatile("st.relaxed.gpu.global.u32 [%0], %1;" ::"l"(p), "r"(v) : "memory"); }
__device__ __forceinline__ uint32_t hmul_bf2(uint32_t a, uint32_t b) {
    uint32_t r; asm("mul.rn.bf16x2 %0, %1, %2;" : "=r"(r) : "r"(a), "r"(b)); return r;
}
__device__ __forceinline__ uint32_t hsub_bf2(uint32_t a, uint32_t b) {
    uint32_t r; asm("sub.rn.bf16x2 %0, %1, %2;" : "=r"(r) : "r"(a), "r"(b)); return r;
}
__device__ __forceinline__ uint32_t hadd_bf2(uint32_t a, uint32_t b) {
    uint32_t r; asm("add.rn.bf16x2 %0, %1, %2;" : "=r"(r) : "r"(a), "r"(b)); return r;
}
__device__ __forceinline__ int opaque(int v) { return __shfl_sync(0xffffffffu, v, threadIdx.x); }
constexpr int SPIN_LIMIT = 1 << 22;

__constant__ uint32_t c_inv2pi[8] = {0u, 0x28be60dbu, 0x9391054au, 0x7f09d5f4u, 0x7d4d3770u, 0x36d8a566u, 0x4f10e410u, 0x7f9458eau};
constexpr uint32_t BIGX = 0x4280u;
__device__ __forceinline__ float cos_big(uint32_t xb) {
    uint32_t e = (xb >> 7) & 0xffu, M = (xb & 0x7fu) | 0x80u;
    uint32_t pp = e - 102u;
    uint32_t wi = pp >> 5;
    uint32_t t0 = c_inv2pi[wi], t1 = c_inv2pi[wi + 1], t2 = c_inv2pi[wi + 2];
    uint32_t f = M * __funnelshift_l(t1, t0, pp) + __umulhi(M, __funnelshift_l(t2, t1, pp));
    float c = __cosf((float)(int)f * 1.4629180792671596e-9f);
    return e == 255u ? __uint_as_float(0x7fc00000u) : c;
}
__device__ __forceinline__ float cos_bf(uint32_t xb) {
    return (xb & 0x7fffu) > BIGX ? cos_big(xb) : __cosf(__uint_as_float(xb << 16));
}
__device__ __forceinline__ uint32_t pack_bf2(float lo, float hi) {
    uint32_t r; asm("cvt.rn.bf16x2.f32 %0, %1, %2;" : "=r"(r) : "f"(hi), "f"(lo)); return r;
}
template <int N> __device__ __forceinline__ uint32_t pick(int k, const uint32_t (&a)[N]) {
    uint32_t v = a[0];
#pragma unroll
    for (int i = 1; i < N; i++) if (k == i) v = a[i];
    return v;
}
template <int N> __device__ __forceinline__ uint2 pick(int k, const uint2 (&a)[N]) {
    uint2 v = a[0];
#pragma unroll
    for (int i = 1; i < N; i++) if (k == i) v = a[i];
    return v;
}
__device__ __forceinline__ uint32_t imul(uint32_t a, float s) { uint32_t r; asm("mul.rz.f32 %0, %1, %2;" : "=r"(r) : "r"(a), "f"(s)); return r; }
__device__ __forceinline__ uint32_t ifma(uint32_t a, float s, uint32_t c) { uint32_t r; asm("fma.rn.f32 %0, %1, %2, %3;" : "=r"(r) : "r"(a), "f"(s), "r"(c)); return r; }
extern __shared__ __align__(1024) unsigned char smem[];
__device__ __forceinline__ void side_add(uint32_t bin, uint32_t row, float a, float b, float c, float d) {
    red4(&g_ovf[bin * RPAD + row], a, b, c, d);
    g_dirty[bin * DROW + row] = 1;
}
__device__ __forceinline__ void slow_triplet(const Params& p, uint32_t ii, uint32_t oo, float c) {
    const uint2 v = __ldg(p.m + ii);
    const uint32_t bo = imul(oo, p.i2);
    side_add(bo, oo - bo * p.R2, c * bf_lo(v.x), c * bf_hi(v.x), c * bf_lo(v.y), c * bf_hi(v.y));
}
__device__ __forceinline__ void slow_rec1(const Params& p, uint32_t x, uint32_t y, uint32_t bin) {
    const uint2 v = __ldg(p.m + bin * p.R1 + (y & 0xffffu));
    const float c = bf_hi(y);
    side_add(x & 0xffu, __byte_perm(x, 0u, 0x4413) >> 3, c * bf_lo(v.x), c * bf_hi(v.x), c * bf_lo(v.y), c * bf_hi(v.y));
}
__device__ __forceinline__ uint32_t aux_of(uint32_t w0, uint32_t w1, uint32_t k = 0) {
    uint32_t u; asm("lop3.b32 %0, %1, %2, 0xf000f000, 0xe4;" : "=r"(u) : "r"(w0), "r"((w1 >> 4) + k));
    return __byte_perm(u, 0u, 0x4413);
}
__device__ __forceinline__ void slow_rec2(const Params& p, uint32_t w0, uint32_t w1, uint32_t bin, float unit) {
    side_add(bin, aux_of(w0, w1) >> 3, (float)((int)(w0 & 0xfffu) - 2048) * unit, (float)((int)(w0 >> 16 & 0xfffu) - 2048) * unit,
             (float)((int)(w1 & 0xfffu) - 2048) * unit, (float)((int)(w1 >> 16 & 0xfffu) - 2048) * unit);
}
template <uint32_t M> __device__ __forceinline__ uint32_t and_or(uint32_t a, uint32_t c) {
    uint32_t r; asm("lop3.b32 %0, %1, %2, %3, 0xea;" : "=r"(r) : "r"(a), "n"(M), "r"(c)); return r;
}
template <uint32_t M> __device__ __forceinline__ uint32_t xor_and(uint32_t a, uint32_t c) {
    uint32_t r; asm("lop3.b32 %0, %1, %2, %3, 0x48;" : "=r"(r) : "r"(a), "n"(M), "r"(c)); return r;
}
__device__ __forceinline__ uint32_t mux(uint32_t a, uint32_t b, uint32_t m) {
    uint32_t r; asm("lop3.b32 %0, %1, %2, %3, 0xd8;" : "=r"(r) : "r"(a), "r"(b), "r"(m)); return r;
}
__device__ __forceinline__ uint32_t and_xor(uint32_t a, uint32_t m, uint32_t c) {
    uint32_t r; asm("lop3.b32 %0, %1, %2, %3, 0x6a;" : "=r"(r) : "r"(a), "r"(m), "r"(c)); return r;
}
__device__ __forceinline__ uint2 ld_in(const uint2* a) {
    uint2 v; asm volatile("ld.global.nc.L1::no_allocate.v2.u32 {%0,%1}, [%2];" : "=r"(v.x), "=r"(v.y) : "l"(a)); return v;
}
__device__ __forceinline__ uint32_t ld_in(const uint32_t* a) {
    uint32_t v; asm volatile("ld.global.nc.L1::no_allocate.u32 %0, [%1];" : "=r"(v) : "l"(a)); return v;
}
__device__ __forceinline__ void ld_in4(const uint2* p, uint2& a, uint2& b) {
    asm volatile("ld.global.nc.L1::no_allocate.v4.u32 {%0,%1,%2,%3}, [%4];" : "=r"(a.x), "=r"(a.y), "=r"(b.x), "=r"(b.y) : "l"(p));
}
__device__ __forceinline__ void tex4(cudaTextureObject_t t, int i, uint2& a, uint2& b) {
    asm volatile("tex.1d.v4.u32.s32 {%0,%1,%2,%3}, [%4, {%5}];" : "=r"(a.x), "=r"(a.y), "=r"(b.x), "=r"(b.y) : "l"(t), "r"(i));
}
__device__ __forceinline__ void tex2(cudaTextureObject_t t, int i, uint32_t& a, uint32_t& b) {
    asm volatile("{ .reg .b32 z, w; tex.1d.v4.u32.s32 {%0,%1,z,w}, [%2, {%3}]; }" : "=r"(a), "=r"(b) : "l"(t), "r"(i) : "memory");
}
template <int OFF> __device__ __forceinline__ void put_rec(uint32_t ret, uint32_t lim, uint32_t addr, uint32_t x, uint32_t y) {
    asm volatile("{ .reg .pred q; setp.lt.u32 q, %0, %1; @q st.shared.v2.u32 [%2+%5], {%3,%4}; }" ::"r"(ret), "r"(lim), "r"(addr), "r"(x), "r"(y), "n"(OFF) : "memory");
}
__device__ __forceinline__ uint32_t mbar_try(uint32_t mb, uint32_t parity) {
    uint32_t ok;
    asm volatile("{ .reg .pred q; mbarrier.try_wait.parity.shared::cta.b64 q, [%1], %2; selp.u32 %0, 1, 0, q; }" : "=r"(ok) : "r"(mb), "r"(parity) : "memory");
    return ok;
}
__device__ __forceinline__ void mbar_wait(uint32_t mb, uint32_t parity) {
    if (!mbar_try(mb, parity)) {
        int it = 0;
        while (!mbar_try(mb, parity)) if (++it > SPIN_LIMIT) __trap();
    }
}
__device__ __forceinline__ void mbar_init(uint32_t mb, uint32_t n) { asm volatile("mbarrier.init.shared::cta.b64 [%0], %1;" ::"r"(mb), "r"(n) : "memory"); }
__device__ __forceinline__ void mbar_arrive(uint32_t mb) { asm volatile("mbarrier.arrive.shared::cta.b64 _, [%0];" ::"r"(mb) : "memory"); }
constexpr int B_FULL = OFF_BAR, B_OPEN = OFF_BAR + 16, B_FREE = OFF_BAR + 32;
constexpr int W_END = OFF_BAR + 40, W_SIDE = OFF_BAR + 44, W_PAR = OFF_BAR + 48, W_ROLE = OFF_BAR + 52, W_EXP = OFF_BAR + 56, W_UNIT = OFF_BAR + 60, W_NLIST = OFF_PROBE + 112, W_WRAP = OFF_PROBE + 116, W_BASE = OFF_PROBE + 120, B_TAB = OFF_PROBE + 128, B_ROWS = OFF_PROBE + 248, B_TFREE = OFF_PROBE + 240, B_FLAG = OFF_PROBE + 232, B_INIT = OFF_PROBE + 224, W_ITEM = OFF_PROBE + 124;
enum { BAR_S1 = 1, BAR_SIDE, BAR_PROBE, BAR_PAR, BAR_TABLE, BAR_DONE, BAR_ACC, BAR_H1, BAR_BASE, BAR_ROWS };
constexpr int W_M1 = NS1 + NC, W_M2 = 31;

#define RTS(c, i)
#define TK_DECL
#define TK(i)
#define TK_CNT(i)
#define TK_OUT
#define TK_ARG
#define TK_PASS
#define TKS(i) TK(i)
#define TKX(i)
#define TKY(i) {}
#define TKZ(i, d)

__device__ __forceinline__ void prefetch_l2(const void* a) { asm volatile("prefetch.global.L2 [%0];" ::"l"(a)); }
__device__ __forceinline__ void wait_flags(const Params& p, uint32_t sb, int lane, uint32_t need) {
    const unsigned char* f = p.ring + M_FLAG + (lds32(sb + W_SIDE) << 12);
    int it = 0;
    while (true) {
        uint32_t a[4];
        asm volatile("ld.acquire.gpu.global.v4.u32 {%0,%1,%2,%3}, [%4];" : "=r"(a[0]), "=r"(a[1]), "=r"(a[2]), "=r"(a[3]) : "l"(f + min(lane, 16) * 16) : "memory");
        const uint32_t d = (a[0] ^ need) | (a[1] ^ need) | (lane < 16 ? (a[2] ^ need) | (a[3] ^ need) : 0u);
        if (__all_sync(0xffffffffu, d == 0)) break;
        __nanosleep(50);
        if (++it > SPIN_LIMIT) __trap();
    }
}
__device__ __forceinline__ float exp_fast(float x) { float r; asm("ex2.approx.ftz.f32 %0, %1;" : "=f"(r) : "f"(x * 1.4426950408889634f)); return r; }
constexpr uint32_t BIAS = 0x3d803d80u, ZERO = 0x7d80u;
__device__ __forceinline__ float2 acc_fix(uint32_t old, uint32_t q) {
    const uint32_t u = old + BIAS, n = u + q - 0x08000800u;
    return make_float2((float)((int)(u & 0xffffu) + (int)(q & 0xffffu) - 2048 - (int)(n & 0xffffu)), (float)((int)(u >> 16) + (int)(q >> 16) - 2048 - (int)(n >> 16)));
}
constexpr int NE = NS1 + NC, NPAIR = (R2MAX / 2 + NE * 32 - 1) / (NE * 32), NTILE = 16, NG0 = NS1 * 8 * NTILE;
constexpr int OFF_G = OFF_M, GH = R2MAX * 8, OFF_LIST = OFF_G, LCAP = NG0 / 10;
static_assert(2 * R2MAX <= R1MAX && NG0 * 16 + 112 <= WIN && 3 * NG0 >= NPAIR * NE * 32 && NE <= 20 && 2 * NPAIR < 16 && NPAIR * NE * 64 <= DROW, "gates");
__device__ __forceinline__ int gate_g(int k) { return (k < NG0 ? OFF_H1 : OFF_G) + k * 16; }
__device__ __forceinline__ int gate_h(int k) { return (k < NG0 ? OFF_H1 + 0x20000 : OFF_G + GH) + k * 16; }
__device__ __forceinline__ uint2 out_row(int row, const float4& o, const float4& add, const uint2& mv) {
    const float* w = reinterpret_cast<const float*>(smem + OFF_WSM);
    const float unit = *reinterpret_cast<const float*>(smem + W_UNIT), K = 8388608.f + ZERO;
    const uint2 ac = reinterpret_cast<const uint2*>(smem + OFF_ACC)[row];
    const uint32_t* g = reinterpret_cast<const uint32_t*>(smem + gate_g(row >> 1)) + (row & 1), *h = reinterpret_cast<const uint32_t*>(smem + gate_h(row >> 1)) + (row & 1);
    const uint32_t c0 = ac.x + BIAS, c1 = ac.y + BIAS;
    const float a[4] = {fmaf(__uint_as_float(__byte_perm(c0, 0x4b00u, 0x5410)) - K, unit, o.x), fmaf(__uint_as_float(__byte_perm(c0, 0x4b00u, 0x5432)) - K, unit, o.y),
                        fmaf(__uint_as_float(__byte_perm(c1, 0x4b00u, 0x5410)) - K, unit, o.z), fmaf(__uint_as_float(__byte_perm(c1, 0x4b00u, 0x5432)) - K, unit, o.w)};
    float sd[4], uu[4];
#pragma unroll
    for (int k = 0; k < 4; k++) sd[k] = fmaf(a[3], w[12 + k], fmaf(a[2], w[8 + k], fmaf(a[1], w[4 + k], a[0] * w[k])));
    const uint32_t a01 = hmul_bf2(pack_bf2(sd[0] + add.x, sd[1] + add.y), g[0]), a23 = hmul_bf2(pack_bf2(sd[2] + add.z, sd[3] + add.w), g[2]);
#pragma unroll
    for (int k = 0; k < 4; k++) uu[k] = fmaf(bf_hi(a23), w[28 + k], fmaf(bf_lo(a23), w[24 + k], fmaf(bf_hi(a01), w[20 + k], bf_lo(a01) * w[16 + k])));
    return make_uint2(hadd_bf2(mv.x, hmul_bf2(pack_bf2(uu[0], uu[1]), h[0])), hadd_bf2(mv.y, hmul_bf2(pack_bf2(uu[2], uu[3]), h[2])));
}
__device__ __forceinline__ void mma16(float (&c)[4], const uint32_t (&a)[4], uint32_t b0, uint32_t b1) {
    asm volatile("mma.sync.aligned.m16n8k16.row.col.f32.bf16.bf16.f32 {%0,%1,%2,%3}, {%4,%5,%6,%7}, {%8,%9}, {%0,%1,%2,%3};"
                 : "+f"(c[0]), "+f"(c[1]), "+f"(c[2]), "+f"(c[3]) : "r"(a[0]), "r"(a[1]), "r"(a[2]), "r"(a[3]), "r"(b0), "r"(b1));
}
__device__ __forceinline__ void finish_rows(const Params& p, uint32_t sb, bool s1) {
    int tid;
    bool wet = false;
    {
        asm volatile("mov.u32 %0, %%tid.x;" : "=r"(tid));
        const int lane = tid & 31;
        if (s1) mbar_wait(sb + B_INIT, 0); else if (lane == 0) mbar_arrive(sb + B_TFREE);
#pragma unroll 1
        for (bool own = s1;; own = false, wet = true) {
            asm volatile("mov.u32 %0, %%tid.x;" : "=r"(tid));
            uint32_t item = tid >> 5;
            if (!own) item = tid & 31 ? 0u : atoms_add<W_ITEM>(sb, 1u);
            item = __reduce_max_sync(0xffffffffu, item);
            if (item >= 3 * NS1) break;
            const int kb = item / NS1 * NG0 + item % NS1 * 8, q = (lds32(sb + W_ROLE) * p.R2 >> 1) + kb + (tid >> 2 & 7) + (tid & 3) * NS1 * 8;
            uint32_t ds[NTILE / 4];
#pragma unroll
            for (int j = 0; j < NTILE / 4; j++) ds[j] = ld_in(reinterpret_cast<const uint32_t*>(p.dist) + min(q + j * NS1 * 32, (p.E >> 1) - 1));
            const uint2 wc = lds64<OFF_WG>(sb + (tid & 31) * 8);
            const uint32_t wb = wc.x, cen = wc.y;
            TKZ(4, (ds[0] ^ ds[1] ^ ds[2] ^ ds[3] ^ wb ^ cen))
            uint2 v[NTILE];
#pragma unroll
            for (int i = 0; i < NTILE; i++) {
                const uint32_t x = __shfl_sync(0xffffffffu, ds[i >> 2], i & 3, 4);
                uint32_t rb[2];
#pragma unroll
                for (int u = 0; u < 2; u++) {
                    const uint32_t df = hsub_bf2(__byte_perm(x, 0u, u ? 0x3232 : 0x1010), cen);
                    const uint32_t ar = hmul_bf2(hmul_bf2(df, df), 0xc120c120u);
                    rb[u] = pack_bf2(exp_fast(bf_lo(ar)), exp_fast(bf_hi(ar)));
                }
                float c[4];
                asm volatile("mma.sync.aligned.m16n8k8.row.col.f32.bf16.bf16.f32 {%0,%1,%2,%3}, {%4,%5}, {%6}, {%7,%7,%7,%7};"
                             : "=f"(c[0]), "=f"(c[1]), "=f"(c[2]), "=f"(c[3]) : "r"(rb[0]), "r"(rb[1]), "r"(wb), "f"(0.f));
                v[i] = make_uint2(pack_bf2(c[0], c[1]), pack_bf2(c[2], c[3]));
            }
            TKZ(5, (v[15].x ^ v[9].y))
            if (own) bar_sync(BAR_H1, (NS1 + 1) * 32); else mbar_wait(sb + B_TFREE, 0);
            asm volatile("mov.u32 %0, %%tid.x;" : "=r"(tid));
            const int k0 = kb + (tid >> 2 & 7);
            const uint32_t a = sb + (tid & 2 ? gate_h(k0) : gate_g(k0)) + (tid & 1) * 8;
#pragma unroll
            for (int i = 0; i < NTILE; i++) if (i < NTILE - 1 || k0 + i * NS1 * 8 < R2MAX / 2) sts64(a + i * NS1 * 8 * 16, v[i].x, v[i].y);
            static_assert(2 * NG0 + (NTILE - 1) * NS1 * 8 <= R2MAX / 2, "gates");
            TKY(1)
        }
    }
    asm volatile("mov.u32 %0, %%tid.x;" : "=r"(tid));
    const int role = lds32(sb + W_ROLE), row0 = role * p.R2, np = min(p.R2, p.E - row0) >> 1, lane = tid & 31;
    uint4 wd = make_uint4(0u, 0u, 0u, 0u), wu = wd;
    if ((lane & 3) == lane >> 3) { wd = lds128(sb + OFF_WB + (lane & 4) * 8); wu = lds128(sb + OFF_WB + 16 + (lane & 4) * 8); }
    const uint32_t wb[8] = {wd.x, wd.y, wd.z, wd.w, wu.x, wu.y, wu.z, wu.w};
    const uint32_t k0 = (lds32(sb + W_UNIT) >> 16) * 0x10001u + 0x03800380u;
    uint8_t* dirty = g_dirty + role * DROW + tid * 2;
    auto flags = [&](uint32_t on) {
        uint32_t f[NPAIR], m = 0;
#pragma unroll
        for (int i = 0; i < NPAIR; i++) asm volatile("{ .reg .pred q; setp.ne.u32 q, %2, 0; mov.u32 %0, 0; @q ld.relaxed.gpu.global.u16 %0, [%1]; }" : "=r"(f[i]) : "l"(dirty + i * NE * 64), "r"(on) : "memory");
#pragma unroll
        for (int i = 0; i < NPAIR; i++) m |= ((f[i] | f[i] >> 7) & 3u) << 2 * i;
        return m;
    };
    auto row_of = [&](int j) { return 2 * tid + (j >> 1) * NE * 64 + (j & 1); };
    uint32_t kept, left = 0, bad = 0, at;
#pragma unroll 1
    for (;; wet = true) {
        if (wet) mbar_wait(sb + B_FLAG, 0);
        TKY(2)
        kept = flags(wet);
        TKZ(3, kept)
        const uint32_t q = sb + OFF_LIST + (tid >> 5) * (LCAP * 16) + (tid < 320 ? 0 : GH - 10 * LCAP * 16), cnt = __popc(kept);
        uint32_t n = 0;
        at = q;
#pragma unroll
        for (int i = 0; i < 4; i++) {
            const uint32_t b = __ballot_sync(0xffffffffu, cnt >> i & 1u);
            n += __popc(b) << i;
            at += __popc(b & ((1u << lane) - 1u)) << (4 + i);
        }
        if (n || !wet) {
            if (n > LCAP) { sts32(sb + W_WRAP, 1u); kept = 0; }
            else {
                uint32_t to = at;
                uint32_t m = kept;
#pragma unroll 1
                do {
                    if (m) sts32(to, row_of(__ffs(m) - 1));
                    m &= m - 1; to += 16;
                } while (m);
                __syncwarp();
                to = q + lane * 16;
#pragma unroll 1
                do {
                    const bool on = to < q + n * 16;
                    float4 o = make_float4(0.f, 0.f, 0.f, 0.f);
                    asm volatile("{ .reg .pred q; setp.ne.u32 q, %5, 0; @q ld.relaxed.gpu.global.v4.f32 {%0,%1,%2,%3}, [%4]; }"
                                 : "+f"(o.x), "+f"(o.y), "+f"(o.z), "+f"(o.w) : "l"(&g_ovf[role * RPAD + lds32(to)]), "r"((uint32_t)on) : "memory");
                    const float4* w = reinterpret_cast<const float4*>(smem + OFF_WSM);
                    const uint4 v = make_uint4(__float_as_uint(fmaf(o.w, w[3].x, fmaf(o.z, w[2].x, fmaf(o.y, w[1].x, o.x * w[0].x)))),
                                               __float_as_uint(fmaf(o.w, w[3].y, fmaf(o.z, w[2].y, fmaf(o.y, w[1].y, o.x * w[0].y)))),
                                               __float_as_uint(fmaf(o.w, w[3].z, fmaf(o.z, w[2].z, fmaf(o.y, w[1].z, o.x * w[0].z)))),
                                               __float_as_uint(fmaf(o.w, w[3].w, fmaf(o.z, w[2].w, fmaf(o.y, w[1].w, o.x * w[0].w)))));
                    if (on) sts128<0>(to, v);
                    to += 512;
                } while (to < q + n * 16);
            }
        }
        TKY(6)
        if (wet) {
            mbar_wait(sb + B_ROWS, 0);
            TKX(5)
            bar_sync(BAR_ACC, (NE + NC) * 32);
        }
        const int lim = wet ? np : 0;
        uint32_t from = at, bit = wet ? 1u : 1u << (2 * NPAIR - 2);
        uint4* out = reinterpret_cast<uint4*>(p.out + row0) + tid;
#pragma unroll 1
        for (int k = tid; bit < 1u << 2 * NPAIR; k += NE * 32, bit *= 4, out += NE * 32) {
            const uint4 ac = lds128(sb + OFF_ACC + k * 16), g = lds128(sb + gate_g(k)), h = lds128(sb + gate_h(k));
            const uint4 mv = lds128(sb + (row0 * 8 & 127) + k * 16 + (k < NG0 ? 0 : k < 2 * NG0 ? 0x10000 - NG0 * 16 : 0x30000 - NG0 * 32));
            const uint32_t u[4] = {ac.x + BIAS, ac.z + BIAS, ac.y + BIAS, ac.w + BIAS};
            uint32_t a[4];
            float c[4] = {0.f, 0.f, 0.f, 0.f}, d[4] = {0.f, 0.f, 0.f, 0.f};
#pragma unroll
            for (int j = 0; j < 2; j++)
                asm volatile("{ .reg .pred q; setp.ne.u32 q, %5, 0; @q ld.shared.v2.f32 {%0,%1}, [%4]; @q ld.shared.v2.f32 {%2,%3}, [%4+8]; @q add.u32 %4, %4, 16; }"
                             : "+f"(c[2 * j]), "+f"(c[2 * j + 1]), "+f"(d[2 * j]), "+f"(d[2 * j + 1]), "+r"(from) : "r"(kept & bit << j) : "memory");
#pragma unroll
            for (int j = 0; j < 4; j++) a[j] = hsub_bf2(and_or<0x007f007fu>(u[j] >> 9, k0 + 0x04800480u), k0 + 0x04c004c0u);
            mma16(c, a, wb[0], wb[1]); mma16(d, a, wb[2], wb[3]);
#pragma unroll
            for (int j = 0; j < 4; j++) a[j] = and_or<0x007f007fu>(u[j] >> 2, k0 + 0x01000100u);
            mma16(c, a, wb[0], wb[1]); mma16(d, a, wb[2], wb[3]);
#pragma unroll
            for (int j = 0; j < 4; j++) a[j] = and_or<0x00030003u>(u[j], k0);
            mma16(c, a, wb[0], wb[1]); mma16(d, a, wb[2], wb[3]);
            a[0] = hmul_bf2(pack_bf2(c[0], c[1]), g.x); a[1] = hmul_bf2(pack_bf2(c[2], c[3]), g.y);
            a[2] = hmul_bf2(pack_bf2(d[0], d[1]), g.z); a[3] = hmul_bf2(pack_bf2(d[2], d[3]), g.w);
#pragma unroll
            for (int j = 0; j < 4; j++) c[j] = d[j] = 0.f;
            mma16(c, a, wb[4], wb[5]); mma16(d, a, wb[6], wb[7]);
            if (k < lim) {
                *out = make_uint4(hadd_bf2(mv.x, hmul_bf2(pack_bf2(c[0], c[1]), h.x)), hadd_bf2(mv.y, hmul_bf2(pack_bf2(d[0], d[1]), h.z)),
                                  hadd_bf2(mv.z, hmul_bf2(pack_bf2(c[2], c[3]), h.y)), hadd_bf2(mv.w, hmul_bf2(pack_bf2(d[2], d[3]), h.w)));
                if (c[0] != c[0] || c[2] != c[2]) bad |= 3u * bit;
            }
        }
        if (wet) break;
    }
    const bool wrap = lds32(sb + W_WRAP);
    if (RARE(wrap)) { left = flags(1u); kept = 0; }
#pragma unroll 1
    for (uint32_t m = left | bad; RARE(m); m &= m - 1) {
        const int j = __ffs(m) - 1, row = row_of(j);
        uint4 v = make_uint4(0u, 0u, 0u, 0u);
        if (kept >> j & 1u) v = lds128(at + __popc(kept & ((1u << j) - 1u)) * 16);
        p.out[row0 + row] = out_row(row, take(&g_ovf[role * RPAD + row], left >> j & 1u),
                                    make_float4(__uint_as_float(v.x), __uint_as_float(v.y), __uint_as_float(v.z), __uint_as_float(v.w)), p.m[row0 + row]);
        if (wrap) g_dirty[role * DROW + row] = 0;
    }
}

template <int HOP> __device__ __forceinline__ uint2 null_rec(int lane, uint32_t R) {
    if (HOP == 1) return make_uint2(0x800000u | H<1>::tag(R), (OFF_CNT1 - OFF_M) / 8);
    return make_uint2(0x08000800u | lane << 28, 0x0fff0000u | H<2>::tag(R));
}
template <int HOP> __device__ __forceinline__ void fill(uint32_t win, int ct, uint32_t R) {
    const uint2 v = null_rec<HOP>(ct, R);
#pragma unroll
    for (int i = 0; i < WIN / (NC * 512); i++) sts128<0>(win + ct * 16 + i * NC * 512, make_uint4(v.x, v.y, v.x, v.y));
}
template <int HOP> __device__ __forceinline__ void reset(uint32_t win, int lane, uint32_t R) {
    const uint2 v = null_rec<HOP>(lane, R);
    const uint32_t a = win + lane * 32 + H<HOP>::mark(R, lane >> 2) * 8;
#pragma unroll
    for (int i = 0; i < 16; i++) sts64(a + i * 1024, v.x, v.y);
    if (lane < 16) sts64(a + 16384, v.x, v.y);
}
__device__ __forceinline__ bool elect() {
    uint32_t q; asm volatile("{ .reg .pred q; elect.sync _|q, 0xffffffff; selp.u32 %0, 1, 0, q; }" : "=r"(q)); return q;
}
__device__ __forceinline__ const unsigned char* mk_ptr(uint32_t lo, uint32_t hi) { return reinterpret_cast<const unsigned char*>((uint64_t)hi << 32 | lo); }
__device__ __forceinline__ void bulk_store(uint32_t lo, uint32_t hi, uint32_t src, uint32_t n) {
    asm volatile("cp.async.bulk.global.shared::cta.bulk_group [%0], [%1], %2;" ::"l"(mk_ptr(lo, hi)), "r"(src), "r"(n) : "memory");
}
template <int HOP>
__device__ __forceinline__ void manager(const Params& p, uint32_t sb, int lane, int role, uint32_t base) {
    typedef H<HOP> h;
    constexpr int V = h::NBIN / 32, PB = h::S * 8;
    const int RT = p.rounds + HOP - 1, lo = HOP == 1 && role >= NG ? NG : 0, hi = lo + h::NBIN;
    const int w = (role - lo) / (HOP * J), j = (role - lo - w * HOP * J) / HOP;
    const Ring rg(p.ring, __reduce_or_sync(0xffffffffu, lds32(sb + W_PAR)), 2 * w + HOP - 1);
    const uint32_t side = lds32(sb + W_SIDE), dhi = rg.main >> 32, mhi = rg.mid >> 32;
    const uint32_t c0 = HOP == 2 ? role & 1 : 0, up = (HOP == 1 && lo) ^ rg.par ^ c0;
    uint32_t dA = ((uint32_t)rg.main + src_off(j) + (c0 << 16) + (up ? 4096 : 12288)) ^ slot_off(base % 3);
    uint32_t dM = ((uint32_t)rg.mid + src_off(j) + c0 * 1024) ^ slot_off(base % 3);
    const int a0 = max(64, lo), b1 = min(68, hi);
    int n0 = (min(NHI, hi) - a0) * PB, a1 = (max(NLO, lo) - lo) * PB;
    const unsigned char* cr = reinterpret_cast<const unsigned char*>(rg.main) + MISC + ((side ^ rg.par) << 12);
    const unsigned char* cr0 = cr + cred_off(lo + lane * V), *cr1 = cr + cred_off(lo + 32 * V + min(lane, V - 1));
    const uint32_t ca0 = sb + h::CNT + lane * V * 4, ca1 = sb + h::CNT + (32 * V + min(lane, V + NDUM)) * 4;
    const uint32_t rot0 = (lane * V & 7) * 16, rot1 = lane * 16;
    uint32_t st = slot_steps(base);
    uint32_t init = h::init(base), prim = sb + h::STG + (HOP == 1 ? h::win(base) : 0u);
    uint32_t cs[5] = {0, 0, 0, 0, 0};
    auto sample = [&]() {
        if (V == 2) asm volatile("ld.relaxed.gpu.global.v2.u32 {%0,%1}, [%2];" : "=r"(cs[0]), "=r"(cs[1]) : "l"(cr0) : "memory");
        else asm volatile("ld.relaxed.gpu.global.v4.u32 {%0,%1,%2,%3}, [%4];" : "=r"(cs[0]), "=r"(cs[1]), "=r"(cs[2]), "=r"(cs[3]) : "l"(cr0) : "memory");
        cs[V] = ld_rlx32(reinterpret_cast<const uint32_t*>(cr1));
    };
    uint32_t low[5] = {rot0, rot0 + 16, rot0 + 32, rot0 + 48, rot1};
    TK_DECL
#pragma unroll 1
    for (int r = 0;; r++) {
        const uint32_t R = base + r, ninit = h::init(R + 1), done = prim;
        TK(5)
        mbar_wait(sb + B_FULL + (HOP - 1) * 8, r & 1);
        TK(0)
        if (HOP == 2) sample();
        uint32_t c[5];
        if (V == 2) asm volatile("ld.shared.v2.u32 {%0,%1}, [%2];" : "=r"(c[0]), "=r"(c[1]) : "r"(ca0) : "memory");
        else asm volatile("ld.shared.v4.u32 {%0,%1,%2,%3}, [%4];" : "=r"(c[0]), "=r"(c[1]), "=r"(c[2]), "=r"(c[3]) : "r"(ca0) : "memory");
        c[V] = lds32(ca1);
        uint32_t nc[5];
#pragma unroll
        for (int k = 0; k <= V; k++) {
            const uint32_t rot = k < V ? rot0 + k * 16 : rot1, z = ninit + (HOP == 1 ? rot : low[k]);
            if (HOP == 2) low[k] = min((max((int)(c[k] - low[k] - init - h::CAP * h::INC), 0) >> h::SH) * 128u + low[k], rot + BOXN * 128u);
            nc[k] = min(max(c[k] + (ninit - init - h::S * h::INC), z), (HOP == 1 ? z : ninit + low[k]) + (h::CAP - h::S) * h::INC);
        }
        if (V == 2) sts64(ca0, nc[0], nc[1]); else sts128<0>(ca0, make_uint4(nc[0], nc[1], nc[2], nc[3]));
        sts32(ca1, lane < V ? nc[V] : lane < V + NDUM ? DUMMY : r);
        __syncwarp();
        if (lane == 0) mbar_arrive(sb + B_OPEN + (HOP - 1) * 8);
        TK(1)
        TK(2)
        asm volatile("fence.proxy.async.shared::cta;" ::: "memory");
        TK(6)
        if (r >= D) {
            int it = 0;
            while (true) {
                uint32_t bad = 0;
#pragma unroll
                for (int k = 0; k <= V; k++) bad |= cs[k] - (R - D + 1);
                if (!__any_sync(0xffffffffu, bad >> 20)) break;
                if (++it > SPIN_LIMIT) __trap();
                if (it > 1) __nanosleep(100);
                sample();
            }
        }
        TK(3)
        if (elect()) {
            const uint32_t dB = (HOP == 1 ? dA ^ 0x10000u : dA) + (up ? 8192 : -8192), sm = prim + (lo ? 2 * PB : 0);
            bulk_store(dA, dhi, sm, 8192);
            bulk_store(dB, dhi, HOP == 1 ? sm + 8192 : prim + 68 * PB, 8192);
            if (n0 > 0) bulk_store(dM + (a0 - 64) * PB, mhi, prim + (a0 - lo) * PB, n0);
            if (a1 < (b1 - lo) * PB) bulk_store((dM ^ 4096u) + (uint32_t)((lo - NLO) * PB + a1), mhi, prim + a1, (b1 - lo) * PB - a1);
            asm volatile("cp.async.bulk.commit_group;" ::: "memory");
            if (r != RT - 1) asm volatile("cp.async.bulk.wait_group.read 0;" ::: "memory");
        }
        __syncwarp();
        TK(4)
        prim = HOP == 1 ? prim ^ 0x20000u : prim >= sb + 0x30000u ? sb : prim + (prim - sb) + 0x10000u;
        if (r == RT - 1) break;
        reset<HOP>(done, lane, R + HOP + 1);
        if (HOP == 1) {
            __syncwarp();
            if (lane == 0) mbar_arrive(sb + B_FREE);
        }
        if (RARE(r == D - 1 || r == RT - D - 1)) {
            uint32_t n = NHI, m = NLO;
            if (HOP == 1 && r == RT - D - 1 && lane < 2) {
                const int row0 = role * p.R2, nr = min(p.R2, p.E - row0) & ~7;
                const uint64_t a = lane ? reinterpret_cast<uint64_t>(p.dist + row0) + 15 & ~15ull : reinterpret_cast<uint64_t>(p.m + row0);
                if (nr > 8) asm volatile("cp.async.bulk.prefetch.L2.global [%0], %1;" ::"l"(a), "r"(lane ? nr * 2 - 16 : nr * 8) : "memory");
            }
            if (r < RT - D - 1) {
                int it = 0;
                while (true) {
                    n = ld_rlx32(reinterpret_cast<const uint32_t*>(p.ring + M_CNT + (side << 12)));
                    if ((n & 0xffffu) + (n >> 16) == NB) break;
                    if (++it > SPIN_LIMIT) __trap();
                }
                m = n = min(max(__reduce_or_sync(0xffffffffu, n) & 0xffffu, (uint32_t)NLO), (uint32_t)NHI);
            }
            n0 = (min((int)n, hi) - a0) * PB;
            a1 = (max((int)m, lo) - lo) * PB;
        }
        if (HOP == 2 && RARE(r == RT - LATE)) fence_gpu();
        if (HOP == 1) sample();
        slot_next(dA, st); slot_next(dM, st);
        st = slot_rot(st);
        init = ninit;
    }
    TK_OUT
}

template <int HOP> struct Reader {
    uint32_t lo, hi, st, line;
    uint32_t* cred;
    __device__ __forceinline__ void init(const Params& p, uint32_t sb, int w, int lane, int role, uint32_t base) {
        constexpr int PB = H<HOP>::S * 8;
        const int first = HOP == 1 ? (role >= NG ? NG : 0) + w * J : w * 2 * J;
        const Ring rg(p.ring, lds32(sb + W_PAR), 2 * w + HOP - 1);
        const uint32_t side = lds32(sb + W_SIDE);
        const bool mid = side ? role < 68 : role >= 64;
        const uint32_t i = role - (side ? (mid ? NLO : 68) : (mid ? 64 : 0));
        const uint32_t c = HOP == 1 ? i >> 5 : lane >> 3 & 1, in = (HOP == 1 ? (i & 31) * PB + (lane & 15) * 16 : i * PB + (lane & 7) * 16) + (lane >> 4) * src_off(3);
        lo = (in + (mid ? ((uint32_t)rg.mid ^ side << 12) + c * 1024 : (uint32_t)rg.main + (c << 16) + (side ^ rg.par ^ c ? 4096 : 12288))) ^ slot_off(base % 3);
        hi = __reduce_or_sync(0xffffffffu, (uint32_t)((mid ? rg.mid : rg.main) >> 32));
        st = slot_steps(base);
        line = opaque((HOP == 1 ? 2 * (role % NG) + (lane >> 3 & 1) : role) + (lane & 1) * 2);
        const bool both = first >= NLO && first < NHI;
        cred = lane < 1 + both ? reinterpret_cast<uint32_t*>(rg.main + MISC + (((both ? lane : first >= NG) ^ rg.par) << 12) + cred_off(role)) : nullptr;
    }
    template <int K> __device__ __forceinline__ void load1(uint2 (&v)[J]) const {
        asm volatile("ld.relaxed.gpu.global.v4.u32 {%0,%1,%2,%3}, [%4+%5];" : "=r"(v[2 * K].x), "=r"(v[2 * K].y), "=r"(v[2 * K + 1].x), "=r"(v[2 * K + 1].y)
                     : "l"(mk_ptr(lo, hi)), "n"(src_off(K)) : "memory");
    }
    static __device__ __forceinline__ uint32_t word(const uint2& v) { return HOP == 1 ? v.x : v.y; }
    template <int K> __device__ __forceinline__ void again(uint2 (&v)[J], uint32_t want, uint32_t m0, uint32_t m1, uint32_t grp) const {
        if (__ballot_sync(0xffffffffu, ((word(v[2 * K]) ^ want) & m0) | ((word(v[2 * K + 1]) ^ want) & m1)) & grp) load1<K>(v);
    }
    __device__ __forceinline__ void load(uint2 (&rec)[J]) const { load1<0>(rec); load1<1>(rec); load1<2>(rec); }
    __device__ __forceinline__ void check(uint2 (&rec)[J], uint32_t R, uint32_t ns, int lane TK_ARG) {
        const uint32_t want = H<HOP>::tag(R), mk = H<HOP>::mark(R, line);
        const uint32_t m0 = mk == 0 ? H<HOP>::TAG : 0u, m1 = mk == 1 ? H<HOP>::TAG : 0u;
        int it = 0;
        while (true) {
            uint32_t b0 = 0, b1 = 0;
#pragma unroll
            for (int j = 0; j < J; j += 2) { b0 |= word(rec[j]) ^ want; b1 |= word(rec[j + 1]) ^ want; }
            if (!__any_sync(0xffffffffu, (b0 & m0) | (b1 & m1))) break;
            if (++it > SPIN_LIMIT) __trap();
            __nanosleep(ns);
            TK_CNT(7)
            const uint32_t grp = 0xffu << (lane & 24u);
            again<0>(rec, want, m0, m1, grp); again<1>(rec, want, m0, m1, grp); again<2>(rec, want, m0, m1, grp);
        }
        if (cred) st_rlx32(cred, R + 1);
        __syncwarp();
        slot_next(lo, st);
        st = slot_rot(st);
    }
    __device__ __forceinline__ void finish() const { if (cred) st_rlx32(cred, 0u); }
};

__device__ __forceinline__ uint32_t probe(unsigned char* a, uint32_t zero) {
    *reinterpret_cast<uint4*>(a) = make_uint4(0u, 0u, 0u, 0u);
    *reinterpret_cast<uint4*>(a + 16) = make_uint4(0u, 0u, 0u, 0u);
    uint32_t best = ~0u, v = threadIdx.x, prev = 0;
#pragma unroll
    for (int t = 0; t <= NPROBE + 1; t++) {
        uint32_t now;
        if (t <= NPROBE) asm volatile("atom.relaxed.gpu.global.add.u32 %0, [%1], 1;" : "=r"(v) : "l"(a + (v & zero)) : "memory");
        else asm volatile("red.relaxed.gpu.global.add.u32 [%0], 1;" ::"l"(a + (v & zero)) : "memory");
        asm volatile("mov.u32 %0, %%clock;" : "=r"(now) :: "memory");
        if (t > 1) best = min(best, now - prev);
        prev = now;
    }
    return best;
}
template <bool B> struct BoolC { static constexpr bool value = B; };

__device__ __forceinline__ void stage1(const Params& p, uint32_t sb, const int pos0, int lane, const bool half) {
    typedef H<1> h;
    constexpr int NP = 4;
    static_assert(NPR == NS1 * NP * 32 - NP * 16, "tiles");
    const int RT = p.rounds;
    uint32_t ff = *reinterpret_cast<const uint16_t*>(p.ang_freq) * 0x10001u;
    auto pair_of = [&](int r, int pos) {
        const int q = r < RT - 1 ? (r * NB + blockIdx.x) * NPR + pos : (RT - 1) * NB * NPR + blockIdx.x * p.lastn + pos;
        return pos < (r < RT - 1 ? NPR : r == RT - 1 ? p.lastn : 0) && q < p.T2 ? q : -1;
    };
    uint2 vi[NP], vo[NP]; uint32_t va[NP];
    auto load_edge = [&](int r) {
#pragma unroll
        for (int u = 0; u < NP; u++) {
            const int q = max(pair_of(r, pos0 + u * 32), 0);
            vi[u] = ld_in(p.idx_in + q); vo[u] = ld_in(p.idx_out + q); va[u] = ld_in(p.angle + q);
        }
    };
    if (p.full) {
#pragma unroll
        for (int u = 0; u < NP; u += 2) {
            const int k = ((blockIdx.x * NPR + pos0 + lane) >> 1) + (!u ? 0 : half ? 0x40000000 : 32);
            tex2(p.ta, k, va[u], va[u + 1]); tex4(p.to, k, vo[u], vo[u + 1]); tex4(p.ti, k, vi[u], vi[u + 1]);
        }
    } else load_edge(0);
    if (blockIdx.x == 0 && pos0 == 0 && (p.T & 1)) {
        const int t = p.T - 1;
        slow_triplet(p, reinterpret_cast<const uint32_t*>(p.idx_in)[t], reinterpret_cast<const uint32_t*>(p.idx_out)[t],
                     bf16r(cos_bf(hmul_bf2(reinterpret_cast<const uint16_t*>(p.angle)[t], ff) & 0xffffu)));
    }
    ff = __reduce_or_sync(0xffffffffu, ff);
    bar_sync(BAR_S1, (NS1 + NC) * 32);
    uint32_t R = __reduce_or_sync(0xffffffffu, lds32(sb + W_BASE) & 31u);
    TK_DECL
    auto step = [&](const int r, const int qn, auto edge) {
        constexpr bool EDGE = decltype(edge)::value;
        uint32_t cc[NP], big = 0;
#pragma unroll
        for (int u = 0; u < NP; u++) {
            va[u] = hmul_bf2(va[u], ff);
            cc[u] = pack_bf2(__cosf(bf_lo(va[u])), __cosf(bf_hi(va[u])));
            big |= hmul_bf2(va[u], 0x3d003d00u);
        }
        if (RARE(big & 0x40004000u)) {
#pragma unroll 1
            for (int u = 0; u < NP; u++) {
                const uint32_t a = pick(u, va);
                float c0 = cos_bf(a & 0xffffu), c1 = cos_bf(a >> 16);
                if ((c0 != c0 || c1 != c1) && (EDGE ? pair_of(r, pos0 + u * 32) >= 0 : !half || u < 2)) {
                    const uint2 i2 = pick(u, vi), o2 = pick(u, vo);
                    if (c0 != c0) slow_triplet(p, i2.x, o2.x, c0);
                    if (c1 != c1) slow_triplet(p, i2.y, o2.y, c1);
                }
                const uint32_t v = pack_bf2(c0 != c0 ? 0.f : c0, c1 != c1 ? 0.f : c1);
#pragma unroll
                for (int k = 0; k < NP; k++) if (k == u) cc[k] = v;
            }
        }
        uint32_t bin[2 * NP], x[2 * NP], y[2 * NP];
        uint32_t dep = 0;
        auto loads = [&]() {
            const int q = qn + (dep & p.zero);
#pragma unroll
            for (int u = 0; u < NP; u += 2) {
                const int k = !u ? q : q + (half ? 0x40000000 : 32);
                tex2(p.ta, k, va[u], va[u + 1]); tex4(p.to, k, vo[u], vo[u + 1]); tex4(p.ti, k, vi[u], vi[u + 1]);
            }
        };
#pragma unroll
        for (int j = 0; j < 2 * NP; j++) {
            const uint32_t ii = j & 1 ? vi[j >> 1].y : vi[j >> 1].x, oo = j & 1 ? vo[j >> 1].y : vo[j >> 1].x;
            bin[j] = imul(ii, p.i1);
            y[j] = __byte_perm(ifma(bin[j], p.k1, ii), cc[j >> 1], j & 1 ? 0x7610 : 0x5410);
            const uint32_t bo = imul(oo, p.i2);
            x[j] = __byte_perm(ifma(bo, p.k2, imul(oo, 8.f)), bo, 0x0514);
            dep |= x[j] | y[j];
            if (EDGE && pair_of(r, pos0 + (j >> 1) * 32) < 0) bin[j] = NG + (lane & (NDUM - 1));
        }
        if (!EDGE) loads();
        else if (r < RT - 1) load_edge(r + 1);
        const uint32_t init = h::init(R), lim = init + ((EDGE && r == RT - 1 ? h::S : h::CAP) << h::SH);
        TKS(0)
        mbar_wait(sb + B_OPEN, ~R & 1);
        TKS(1)
        bool freed = false;
        uint32_t over = 0;
#pragma unroll
        for (int g = 0; g < 2 * NP; g += NP) if (!g || EDGE || !half) {
            constexpr int G = NP;
            uint32_t ret[G];
            int mx = 0;
#pragma unroll
            for (int j = 0; j < G; j++) ret[j] = atoms_add<h::CNT>(sb + imul(bin[g + j], 4.f), h::INC);
#pragma unroll
            for (int j = 0; j < G; j++) mx = j ? max(mx, (int)ret[j]) : (int)ret[j];
            if (!freed && __any_sync(0xffffffffu, mx >= (int)(init + 0x10000u))) { TKS(2) mbar_wait(sb + B_FREE, ~R & 1); freed = true; TKS(3) }
            TKS(2)
#pragma unroll
            for (int j = 0; j < G; j++) {
                x[g + j] = and_or<h::TAG>(ret[j], x[g + j]);
                put_rec<h::STG>(ret[j], lim, sb + and_or<0x20000u | h::PM>(ret[j], imul(bin[g + j], 256.f)), x[g + j], y[g + j]);
            }
            if (RARE(mx >= (int)lim)) {
#pragma unroll
                for (int j = 0; j < G; j++) if ((int)ret[j] >= (int)lim) over |= 1u << (g + j);
            }
        }
        __syncwarp();
        if (elect()) mbar_arrive(sb + B_FULL);
        R++;
        TKS(4)
#pragma unroll 1
        while (RARE(over)) {
            TK_CNT(7)
            const int j = __ffs(over) - 1;
            over &= over - 1;
            slow_rec1(p, pick(j, x), pick(j, y), pick(j, bin));
        }
        __syncwarp();
    };
#pragma unroll 1
    for (int q = opaque(((NB + blockIdx.x) * NPR + pos0 + lane) >> 1), r = 1; r < p.full; r++, q += NB * NPR / 2) step(r - 1, q, BoolC<false>());
#pragma unroll 1
    for (int r = max(p.full - 1, 0); r < RT; r++) step(r, 0, BoolC<true>());
    TK_OUT
}

__device__ __forceinline__ void stage2(const Params& p, uint32_t sb, int w, int lane, int role, uint32_t base1, uint32_t base) {
    typedef H<2> h;
    const int RT = p.rounds + 1;
    Reader<1> rd;
    rd.init(p, sb, w, lane, role, base1 + 3);
    uint2 rec[J];
#pragma unroll
    for (int j = 0; j < J; j++) rec[j] = null_rec<1>(lane, base1);
    uint32_t kb = sb + 0x10000u, am = 0x10000u | h::PM;
    const float unit = __uint_as_float(__reduce_or_sync(0xffffffffu, lds32(sb + W_UNIT)));
    TK_DECL
#pragma unroll 1
    for (int r = 0; r < RT; r++) {
        rd.check(rec, base1 + r, POLL_NS, lane TK_PASS);
        if (RARE(r == 1)) bar_sync(BAR_TABLE, 2 * NC * 32);
        const uint32_t want = H<1>::tag(base1 + r);
        TKS(0)
        uint2 mv[J];
#pragma unroll
        for (int j = 0; j < J; j++) {
            mv[j] = make_uint2(0u, 0u);
            const uint32_t a = sb + imul(rec[j].y & 0xffffu, 8.f);
            if (!xor_and<0x8e0000u>(rec[j].x, want)) mv[j] = lds64<OFF_M>(a);
        }
        uint32_t fl = 0;
#pragma unroll
        for (int j = 0; j < J; j++) fl |= mv[j].y;
        if (RARE(fl & 0x40000000u)) {
#pragma unroll 1
            for (int j = 0; j < J; j++) {
                const uint2 v = pick(j, mv), w = pick(j, rec);
                if ((v.y & 0x40000000u) && !((w.x ^ want) & 0x8e0000u)) {
                    if (v.x & 0x40000000u) slow_rec1(p, w.x, w.y, lds32(sb + W_ROLE) % NG);
                    else {
                        const float c = bf_hi(w.y), s = __uint_as_float(lds32(sb + W_UNIT)) * 1024.f;
                        side_add(w.x & 0xffu, __byte_perm(w.x, 0u, 0x4413) >> 3, c * (bf_lo(v.x) * s), c * (bf_hi(v.x) * s),
                                 c * (bf_lo(v.y) * s), c * (bf_hi(v.y & 0xbfffffffu) * s));
                    }
                }
            }
#pragma unroll
            for (int j = 0; j < J; j++) if (mv[j].y & 0x40000000u) rec[j].x = 0x800000u;
        }
        uint32_t w0[J], w1[J], bin[J], ret[J];
#pragma unroll
        for (int j = 0; j < J; j++) {
            const float c = bf_hi(rec[j].y), MG = 8194.0f;
            const uint32_t x = rec[j].x;
            const float v[4] = {bf_lo(mv[j].x), bf_hi(mv[j].x), bf_lo(mv[j].y), bf_hi(mv[j].y)};
            w0[j] = and_or<0xf000f000u>(x, __byte_perm(__float_as_uint(fmaf(c, v[0], MG)), __float_as_uint(fmaf(c, v[1], MG)), 0x5410));
            w1[j] = and_or<0xf000f000u>(x << 4, __byte_perm(__float_as_uint(fmaf(c, v[2], MG)), __float_as_uint(fmaf(c, v[3], MG)), 0x5410));
            bin[j] = min(xor_and<0x8e00ffu>(x, want), NB + (lane & (NDUM - 1)));
        }
        const uint32_t lim = h::init(base + r) + (r == RT - 1 ? 0x10000u : 0x20000u);
        rd.load(rec);
        TKS(1)
        mbar_wait(sb + B_OPEN + 8, (r - 1) & 1);
        TKS(2)
#pragma unroll
        for (int j = 0; j < J; j++) ret[j] = atoms_add<h::CNT>(sb + imul(bin[j], 4.f), h::INC);
        uint32_t mx = 0;
#pragma unroll
        for (int j = 0; j < J; j++) {
            w1[j] = and_or<h::TAG>(ret[j], w1[j]);
            put_rec<0>(ret[j], lim, and_xor(ret[j], am, bin[j] * 128 + kb), w0[j], w1[j]);
            mx = __viaddmax_u32(ret[j], 0u - DUMMY, mx);
        }
        __syncwarp();
        if (lane == 0) mbar_arrive(sb + B_FULL + 8);
        TKS(3)
        if (RARE(mx >= lim - DUMMY)) {
            uint32_t over = 0;
#pragma unroll
            for (int j = 0; j < J; j++) if (ret[j] - DUMMY >= lim - DUMMY) over |= 1u << j;
#pragma unroll 1
            do {
                const int j = __ffs(over) - 1;
                over &= over - 1;
                const uint32_t b = pick(j, bin), v = pick(j, ret) - lim, e = v >> h::SH, at = ((v - e * h::INC - (b & 7u) * 16u - h::CAP * 8) >> 7) + e;
                if (max(at, e) < BOXN && r < RT - LATE) g_box[(b * NB + role) * BOX + at] = make_uint2(pick(j, w0), pick(j, w1) | h::TAG);
                else slow_rec2(p, pick(j, w0), pick(j, w1), b, unit);
            } while (over);
        }
        __syncwarp();
        am = am >= 0x30000u ? 0x10000u | h::PM : am + 0x10000u;
        kb ^= am & 0x30000u;
        TKS(4)
    }
    rd.finish();
    TK_OUT
}

__device__ __forceinline__ void add_recs(uint32_t sb, int lane, const uint2 (&rec)[J], uint32_t want) {
    const uint32_t t = 0u - (lane & 1u), k = (t & 1u << 26) - (want >> 4);
    uint32_t o0[J], o1[J], g = 0;
#pragma unroll
    for (int j = 0; j < J; j++) {
        o0[j] = 0; o1[j] = 0;
        if (xor_and<0x7fffffffu>(rec[j].y, want) < 0x0ffc0000u) {
            const uint32_t a = aux_of(rec[j].x, rec[j].y, k);
            const uint32_t v0 = (rec[j].x & 0x0fff0fffu) - 0x08000800u, v1 = (rec[j].y & 0x0fff0fffu) - 0x08000800u;
            o0[j] = atoms_add<OFF_ACC>(sb + a, mux(v0, v1, t));
            o1[j] = atoms_add<OFF_ACC>(sb + (a ^ 4u), mux(v1, v0, t));
        }
    }
#pragma unroll
    for (int j = 0; j < J; j++) g |= o0[j] | o1[j];
    if (RARE(__any_sync(0xffffffffu, g & 0x80008000u))) {
#pragma unroll 1
        for (int j = 0; j < J; j++) {
            const uint2 w = pick(j, rec);
            const uint32_t aux = aux_of(w.x, w.y), p0 = pick(j, o0), p1 = pick(j, o1);
            const float2 a = acc_fix(t ? p1 : p0, w.x & 0x0fff0fffu), b = acc_fix(t ? p0 : p1, w.y & 0x0fff0fffu);
            const float unit = __uint_as_float(lds32(sb + W_UNIT));
            if (xor_and<0x7fffffffu>(w.y, want) < 0x0ffc0000u && (a.x != 0.f || a.y != 0.f || b.x != 0.f || b.y != 0.f)) {
                side_add(lds32(sb + W_ROLE), aux >> 3, a.x * unit, a.y * unit, b.x * unit, b.y * unit);
                sts32(sb + W_WRAP, 1u);
            }
            __syncwarp();
        }
    }
}
__device__ __forceinline__ void stage3(const Params& p, uint32_t sb, int w, int lane, int role, uint32_t base) {
    const int RT = p.rounds + 1;
    Reader<2> rd;
    rd.init(p, sb, w, lane, role, base);
    uint2 rec[J];
    TK_DECL
#pragma unroll 1
    for (int r = 0; r < RT; r++) {
        rd.load(rec);
        rd.check(rec, base + r, r < RT - 2 ? POLL_NS3 : 100, lane TK_PASS);
        RTS((r & 127) == 41 && w == 0, 1 + (r >> 7))
        TK(0)
        add_recs(sb, lane, rec, H<2>::tag(base + r));
        TK(1)
        if (RARE((uint32_t)(r - (RT - LATE + 1)) < 2u)) {
            static_assert(BOX == 32, "box");
            float4* box = reinterpret_cast<float4*>(g_box) + (lds32(sb + W_ROLE) * NB + (w * 2 + r - (RT - LATE + 1)) * J) * (BOX / 2) + lane;
            TKY(0)
#pragma unroll
            for (int j = 0; j < J / 2; j++) {
                const float4 v = ld_rlx128f(box + j * 32);
                rec[2 * j] = make_uint2(__float_as_uint(v.x), __float_as_uint(v.y)); rec[2 * j + 1] = make_uint2(__float_as_uint(v.z), __float_as_uint(v.w));
            }
#pragma unroll
            for (int j = 0; j < J / 2; j++) if (rec[2 * j].x) box[j * 32] = make_float4(0.f, 0.f, 0.f, 0.f);
            add_recs(sb, lane, rec, H<2>::TAG);
            TKY(1)
        }
    }
    rd.finish();
    TK_OUT
}

__device__ __forceinline__ uint32_t row_max(uint32_t x, uint32_t y) {
    const uint32_t mx = __vmaxu2(x & 0x7fff7fffu, y & 0x7fff7fffu);
    return max(mx & 0xffffu, mx >> 16);
}
__device__ __forceinline__ uint32_t amax2(uint32_t a, uint32_t b) {
    uint32_t r; asm("max.NaN.xorsign.abs.bf16x2 %0, %1, %2;" : "=r"(r) : "r"(a), "r"(b)); return r;
}
constexpr int NTAB = 9, TABC = 2 * NC * 32 * 16;
__device__ __forceinline__ void load_piece(const Params& p, uint32_t sb, int role, int i) {
    const int r0 = (role >= NG ? role - NG : role) * p.R1, n = max(min(min(p.R1, p.E - r0) * 8 - i * TABC, TABC), 0);
    asm volatile("mbarrier.arrive.expect_tx.shared::cta.b64 _, [%0], %1;" ::"r"(sb + B_TAB + i * 8), "r"(n) : "memory");
    if (n) asm volatile("cp.async.bulk.shared::cluster.global.mbarrier::complete_tx::bytes [%0], [%1], %2, [%3];"
                        ::"r"(sb + OFF_M + i * TABC), "l"(p.m + r0 + i * (TABC / 8)), "r"(n), "r"(sb + B_TAB + i * 8) : "memory");
}
static_assert(NTAB * TABC >= R1MAX * 8 && NTAB * TABC - TABC / 2 <= R1MAX * 8, "table");
constexpr int EWIN = 5;

__global__ void __launch_bounds__(NTHR, 1) fused_kernel(const Params p) {
    const int tid = threadIdx.x, lane = tid & 31;
    const int hw = __reduce_max_sync(0xffffffffu, tid >> 5);
    const uint32_t sb = __reduce_or_sync(0xffffffffu, (uint32_t)__cvta_generic_to_shared(smem));
    TKX(0)
    RTS(tid == 0, 0)
    uint32_t cta;
    asm volatile("mov.u32 %0, %%ctaid.x;" : "=r"(cta));
    if (hw != W_M1 && hw != W_M2) {
        const int job = hw < W_M1 ? hw : hw - 1;
        if (lane == 0 && job < 2 * NPAGE + 2)
            sts32(sb + OFF_PROBE + job * 4, probe(p.ring + (size_t)max(job / 2 - 1, 0) * PAGE + PROBE + (cta & 31) * 128 + (cta >> 5 & 3) * 16384 + (cta >> 7 << 20) +
                                                  ((job & 1) << 12 ^ (job < 2 ? 0x3000 : 0)), p.zero));
        if (job < 4) bar_arrive(BAR_SIDE, 5 * 32); else bar_arrive(BAR_PROBE, 27 * 32);
        TKX(1)
    }
    if (hw < NS1) {
        stage1(p, sb, hw * 128 + lane, lane, hw == NS1 - 1);
    } else if (hw == W_M1) {
        const uint32_t epoch = ld_rlx32(reinterpret_cast<const uint32_t*>(p.ring + M_BASE)) ^ 33u;
        if (lane == 0) {
            if (sb & 255u) __trap();
            mbar_init(sb + B_FULL, NS1); mbar_init(sb + B_OPEN, 1); mbar_init(sb + B_FREE, 1); mbar_init(sb + B_TFREE, NC); mbar_init(sb + B_FLAG, 32); mbar_init(sb + B_INIT, 1); sts32(sb + W_ITEM, NS1);
            for (int i = 0; i < NTAB; i++) mbar_init(sb + B_TAB + i * 8, 1);
            asm volatile("fence.proxy.async.shared::cta;" ::: "memory");
        }
        const uint32_t base = __reduce_or_sync(0xffffffffu, epoch) & 31u;
        if (lane == 0) { sts32(sb + W_BASE, epoch); sts64(sb + W_NLIST, 0u, 0u); }
        if (lane == 0 && (base & 1u)) { mbar_arrive(sb + B_OPEN); mbar_arrive(sb + B_FREE); }
        bar_arrive(BAR_BASE, (NC + 1) * 32);
        TKY(5)
        bar_sync(BAR_SIDE, 5 * 32);
        TKY(6)
        {
            const uint2 la = lds64<OFF_PROBE>(sb), lb = lds64<OFF_PROBE + 8>(sb);
            const uint32_t side = min(la.y, lb.y) < min(la.x, lb.x);
            uint32_t v = 0;
            if (lane == 0) {
                asm volatile("atom.relaxed.gpu.global.add.u32 %0, [%1], %2;" : "=r"(v) : "l"(p.ring + M_CNT), "r"(side ? 0x10000u : 1u) : "memory");
                asm volatile("red.relaxed.gpu.global.add.u32 [%0], %1;" ::"l"(p.ring + M_CNT + 4096), "r"(side ? 0x10000u : 1u) : "memory");
            }
            bar_sync(BAR_PROBE, 27 * 32);
            const uint2 l = lds64<OFF_PROBE + 8>(sb + min(lane, NPAGE - 1) * 8);
            const uint32_t mine = (__ballot_sync(0xffffffffu, (l.y < l.x) != side) & ~1u) | 0x80000000u;
            if (lane == 0) {
                uint32_t par;
                asm volatile("atom.relaxed.gpu.global.cas.b32 %0, [%1], 0, %2;" : "=r"(par) : "l"(p.ring + M_PAR), "r"(mine) : "memory");
                const uint32_t role = side ? NB - 1 - (v >> 16) : v & 0xffffu;
#pragma unroll 1
                for (int i = 0; i < AHEAD; i++) load_piece(p, sb, role, i);
                sts32(sb + W_ROLE, role); sts32(sb + W_SIDE, role < NLO ? 0u : role >= NHI ? 1u : side);
                sts32(sb + W_END, (epoch | 1023u) + 1u + (base + p.rounds) % 24u + ((epoch >> 5 & 31u) + p.rounds + 1) % 24u * 32u);
                sts32(sb + W_PAR, par ? par : mine);
            }
            TKX(2)
        }
        bar_arrive(BAR_PAR, (2 * NC + 2) * 32);
        manager<1>(p, sb, opaque(lane), __reduce_max_sync(0xffffffffu, lds32(sb + W_ROLE)), base);
        asm volatile("cp.async.bulk.wait_group 0;" ::: "memory");
        bar_arrive(BAR_H1, (NS1 + 1) * 32);
        TKX(4)
        {
            const int role = lds32(sb + W_ROLE);
#pragma unroll 1
            for (int i = lane * 16; i < DROW; i += NPF * 512) {
                float4 f[NPF];
#pragma unroll
                for (int u = 0; u < NPF; u++) f[u] = ld_rlx128f(reinterpret_cast<const float4*>(g_dirty + role * DROW + i + u * 512));
#pragma unroll
                for (int u = 0; u < NPF; u++) {
                    if (__float_as_uint(f[u].x) | __float_as_uint(f[u].y)) prefetch_l2(g_ovf + role * RPAD + i + u * 512);
                    if (__float_as_uint(f[u].z) | __float_as_uint(f[u].w)) prefetch_l2(g_ovf + role * RPAD + i + u * 512 + 8);
                }
            }
        }
        bar_sync(BAR_DONE, (NE + 1) * 32);
        TKY(0)
        const uint32_t flag = lds32(sb + W_END) >> 10 & 0xffffu;
        if (lane < 2) {
            fence_gpu();
            asm volatile("st.relaxed.gpu.global.u16 [%0], %1;" ::"l"(p.ring + M_FLAG + lane * 4096 + blockIdx.x * 2), "h"((uint16_t)flag) : "memory");
        }
        TKY(1)
        __syncwarp();
        bar_arrive(BAR_ROWS, 64);
        wait_flags(p, sb, lane, flag * 0x10001u);
        TKX(5)
        mbar_arrive(sb + B_FLAG);
        if (blockIdx.x == 0) {
            if (lane == 0) *reinterpret_cast<uint32_t*>(p.ring + M_BASE) = lds32(sb + W_END) ^ 33u;
            if (lane < 3) *reinterpret_cast<uint32_t*>(p.ring + (lane & 2 ? M_PAR : M_CNT + (lane & 1) * 4096)) = 0;
        }
    } else if (hw == W_M2) {
        uint2 sm[16];
#pragma unroll
        for (int i = 0; i < 8; i++) ld_in4(p.m + 2 * min((i * 8 + (lane >> 2)) * (p.E >> 7) + (lane & 3), (p.E >> 1) - 1), sm[2 * i], sm[2 * i + 1]);
        const float wd = __bfloat162float(lane & 16 ? p.w_up[lane & 15] : p.w_down[lane & 15]);
        const uint16_t* wg = reinterpret_cast<const uint16_t*>(lane & 16 ? p.w_rbf : p.w_sbf) + (lane & 3) * 8 + (lane >> 2 & 3);
        const uint16_t* cp = reinterpret_cast<const uint16_t*>(p.centers) + (lane & 3) * 2;
        const uint32_t w0 = __ldg(wg), w1 = __ldg(wg + 4), c0 = __ldg(cp), c1 = __ldg(cp + 1);
        if (lane == 0) { mbar_init(sb + B_FULL + 8, NC); mbar_init(sb + B_OPEN + 8, 1); mbar_init(sb + B_ROWS, 1); }
        sts128<OFF_HIST>(sb + lane * 16, make_uint4(0u, 0u, 0u, 0u)); sts128<OFF_HIST + 512>(sb + lane * 16, make_uint4(0u, 0u, 0u, 0u));
        __syncwarp();
#pragma unroll
        for (int i = 0; i < 16; i++) atoms_add<OFF_HIST>(sb + (row_max(sm[i].x, sm[i].y) >> 7) * 4, 1u);
        __syncwarp();
        uint32_t best = 0;
#pragma unroll 1
        for (int e = 11 + lane; e <= 230; e += 32) {
            uint32_t c = 0;
#pragma unroll
            for (int i = 0; i < EWIN; i++) c += lds32(sb + OFF_HIST + (e - i) * 4);
            best = max(best, c << 8 | (255 - e));
        }
        const uint32_t e = 255 - (__reduce_max_sync(0xffffffffu, best) & 255u);
        if (lane == 0) { sts32(sb + W_EXP, e); sts32(sb + W_UNIT, (e - 10) << 23); }
        reinterpret_cast<float*>(smem + OFF_WSM)[lane] = wd;
        const int wi = (lane & 4) * 4 + (lane & 1) * 8 + (lane & 2) + (lane >> 3 & 1);
        const uint32_t fr = __byte_perm(__float_as_uint(__shfl_sync(0xffffffffu, wd, wi)), __float_as_uint(__shfl_sync(0xffffffffu, wd, wi + 4)), 0x7632);
        if (lane < 16) sts32(sb + OFF_WB + lane * 4, fr);
        sts64(sb + OFF_WG + lane * 8, w0 | w1 << 16, c0 | c1 << 16);
        TKY(5)
        bar_sync(BAR_PAR, (2 * NC + 2) * 32);
        if (lane == 0) mbar_arrive(sb + B_INIT);
        manager<2>(p, sb, opaque(lane), __reduce_max_sync(0xffffffffu, lds32(sb + W_ROLE)), __reduce_or_sync(0xffffffffu, lds32(sb + W_BASE)) >> 5 & 31u);
        TKX(4)
        asm volatile("cp.async.bulk.wait_group.read 0;" ::: "memory");
        bar_sync(BAR_ROWS, 64);
        if (lane == 0) {
            const int row0 = lds32(sb + W_ROLE) * p.R2, np = min(p.R2, p.E - row0) >> 1, off = row0 * 8 & 127;
            asm volatile("mbarrier.arrive.expect_tx.shared::cta.b64 _, [%0], %1;" ::"r"(sb + B_ROWS), "r"(max(np, 0) * 16 + (max(np, 0) + NG0 - 1) / NG0 * off) : "memory");
#pragma unroll 1
            for (int k = 0; k < np; k += NG0)
                asm volatile("cp.async.bulk.shared::cluster.global.mbarrier::complete_tx::bytes [%0], [%1], %2, [%3];"
                             ::"r"(sb + H<2>::win(k / NG0)), "l"(p.m + (row0 - off / 8 + 2 * k)), "r"(min(np - k, NG0) * 16 + off), "r"(sb + B_ROWS) : "memory");
        }
        asm volatile("cp.async.bulk.wait_group 0;" ::: "memory");
    } else {
        const int w = __reduce_max_sync(0xffffffffu, hw < W_M1 ? hw - NS1 : hw - W_M1 - 1), ct = w * 32 + lane;
        if (hw < W_M1) {
            bar_sync(BAR_BASE, (NC + 1) * 32);
            const uint32_t b1 = lds32(sb + W_BASE) & 31u, b2 = lds32(sb + W_BASE) >> 5 & 31u;
            if (ct < NG + NDUM) sts32(sb + OFF_CNT1 + ct * 4, ct < NG ? H<1>::init(b1) + (ct & 7) * 16 : DUMMY);
            if (ct <= NB + NDUM) sts32(sb + OFF_CNT2 + ct * 4, ct < NB ? H<2>::init(b2) + (ct & 7) * 16 : DUMMY);
            fill<1>(sb + OFF_H1 + H<1>::win(b1), ct, b1); fill<1>(sb + OFF_H1 + H<1>::win(b1 + 1), ct, b1 + 1);
            bar_arrive(BAR_S1, (NS1 + NC) * 32);
#pragma unroll
            for (int i = 0; i < 3; i++) fill<2>(sb + H<2>::win(i), ct, b2 + i);
        }
        bar_sync(BAR_PAR, (2 * NC + 2) * 32);
        TKY(4)
        const int role = __reduce_max_sync(0xffffffffu, lds32(sb + W_ROLE));
        const uint32_t epoch = __reduce_or_sync(0xffffffffu, lds32(sb + W_BASE));
        if (hw < W_M1) {
            for (int i = ct; i < R2MAX / 2; i += NC * 32) reinterpret_cast<uint4*>(smem + OFF_ACC)[i] = make_uint4(0x40004000u, 0x40004000u, 0x40004000u, 0x40004000u);
            mbar_wait(sb + B_TAB + KDRY * 8, 0);
            stage2(p, sb, w, opaque(lane), role, (epoch & 31u) - 1u, epoch >> 5 & 31u);
        } else {
            const int e = lds32(sb + W_EXP);
            const uint32_t sc = (uint32_t)(254 - e) * 0x800080u, top = (e << 7 | 0x807fu) * 0x10001u;
            auto conv = [&](uint32_t& x, uint32_t& y) {
                const uint32_t mx = row_max(x, y);
                const int d = e - (int)(mx >> 7);
                x = hmul_bf2(x, sc); y = hmul_bf2(y, sc);
                if (d >= EWIN) y |= 0x40000000u;
                if (d < 0 || (d >= EWIN && e > 127)) { x = 0x40000000u; y = x; }
                if (mx == 0) { x = 0; y = 0; }
            };
#pragma unroll 1
            for (int i = 0; i < NTAB; i++) {
                mbar_wait(sb + B_TAB + i * 8, 0);
                if (ct == 0 && i < NTAB - AHEAD) load_piece(p, sb, role, i + AHEAD);
                const uint32_t t = sb + OFF_M + i * TABC + ct * 16, t1 = t + TABC / 2 < sb + OFF_M + R1MAX * 8 ? t + TABC / 2 : t;
                uint4 v[2] = {lds128(t), lds128(t1)};
                uint32_t ok = ~0u;
#pragma unroll
                for (int u = 0; u < 2; u++) {
                    const uint32_t a = amax2(v[u].x, v[u].y), b = amax2(v[u].z, v[u].w), mx = amax2(__byte_perm(a, b, 0x5410), __byte_perm(a, b, 0x7632)) & 0x7fff7fffu;
                    ok &= (top - mx) ^ (top - EWIN * 0x800080u - mx);
                }
                if (RARE(~ok & 0x80008000u)) {
#pragma unroll 1
                    for (int u = 0; u < 4; u++) {
                        conv(v[0].x, v[0].y);
                        const uint2 f = make_uint2(v[0].x, v[0].y);
                        v[0] = make_uint4(v[0].z, v[0].w, v[1].x, v[1].y); v[1] = make_uint4(v[1].z, v[1].w, f.x, f.y);
                    }
                } else {
#pragma unroll
                    for (int u = 0; u < 2; u++) v[u] = make_uint4(hmul_bf2(v[u].x, sc), hmul_bf2(v[u].y, sc), hmul_bf2(v[u].z, sc), hmul_bf2(v[u].w, sc));
                }
                sts128<0>(t, v[0]); sts128<0>(t1, v[1]);
                __syncwarp();
            }
            TKX(3)
            bar_sync(BAR_TABLE, 2 * NC * 32);
            stage3(p, sb, w, opaque(lane), role, epoch >> 5 & 31u);
            TKX(4)
            bar_sync(BAR_ACC, (NE + NC) * 32);
            if (!lds32(sb + W_WRAP)) {
                int i;
                asm volatile("mov.u32 %0, %%tid.x;" : "=r"(i));
                const int ro = lds32(sb + W_ROLE);
#pragma unroll 1
                for (i -= (W_M1 + 1) * 32; i < DROW / 16; i += NC * 32) {
                    float4* f = reinterpret_cast<float4*>(g_dirty + ro * DROW) + i;
                    const float4 v = ld_rlx128f(f);
                    uint32_t m = __float_as_uint(v.x) | __float_as_uint(v.y) << 1 | __float_as_uint(v.z) << 2 | __float_as_uint(v.w) << 3;
                    if (m) *f = make_float4(0.f, 0.f, 0.f, 0.f);
#pragma unroll 1
                    for (; m; m &= m - 1) {
                        const int b = __ffs(m) - 1;
                        g_ovf[ro * RPAD + i * 16 + (b & 3) * 4 + (b >> 3)] = make_float4(0.f, 0.f, 0.f, 0.f);
                    }
                }
            }
        }
    }
    if (hw < W_M1) {
        bar_arrive(BAR_DONE, (NE + 1) * 32);
        __syncwarp();
        TKX(4)
        finish_rows(p, sb, hw < NS1);
    }
}

__global__ void fb_scatter(const uint2* __restrict__ m, const int* __restrict__ idx_in, const int* __restrict__ idx_out,
                           const uint16_t* __restrict__ angle, const __nv_bfloat16* __restrict__ ang_freq, int T, int e0, int e1) {
    const uint32_t fb = *reinterpret_cast<const uint16_t*>(ang_freq);
    for (long long t = blockIdx.x * (long long)blockDim.x + threadIdx.x; t < T; t += (long long)gridDim.x * blockDim.x) {
        int o = idx_out[t];
        if (o < e0 || o >= e1) continue;
        float c = bf16r(cos_bf(hmul_bf2(angle[t], fb) & 0xffffu));
        uint2 v = __ldg(m + idx_in[t]);
        red4(&g_ovf[o - e0], c * bf_lo(v.x), c * bf_hi(v.x), c * bf_lo(v.y), c * bf_hi(v.y));
    }
}
__global__ void fb_final(const Params p, int e0, int e1) {
    int e = e0 + blockIdx.x * blockDim.x + threadIdx.x;
    if (e >= e1) return;
    float4 a4 = g_ovf[e - e0];
    g_ovf[e - e0] = make_float4(0.f, 0.f, 0.f, 0.f);
    float a[4] = {a4.x, a4.y, a4.z, a4.w};
    float d = __bfloat162float(p.dist[e]);
    float g[4] = {0, 0, 0, 0}, h[4] = {0, 0, 0, 0};
    for (int r = 0; r < 8; r++) {
        float df = bf16r(d - __bfloat162float(p.centers[r]));
        float rb = bf16r(expf(bf16r(-10.0f * bf16r(df * df))));
        for (int k = 0; k < 4; k++) {
            g[k] += rb * __bfloat162float(p.w_sbf[r * 4 + k]);
            h[k] += rb * __bfloat162float(p.w_rbf[r * 4 + k]);
        }
    }
    float ag[4];
    for (int k = 0; k < 4; k++) {
        float s = 0.f;
        for (int j = 0; j < 4; j++) s += a[j] * __bfloat162float(p.w_down[j * 4 + k]);
        ag[k] = bf16r(s * g[k]);
    }
    uint2 mv = p.m[e];
    float mm[4] = {bf_lo(mv.x), bf_hi(mv.x), bf_lo(mv.y), bf_hi(mv.y)};
    __nv_bfloat16 o[4];
    for (int k = 0; k < 4; k++) {
        float u = 0.f;
        for (int j = 0; j < 4; j++) u += ag[j] * __bfloat162float(p.w_up[j * 4 + k]);
        o[k] = __float2bfloat16_rn(mm[k] + bf16r(bf16r(u) * bf16r(h[k])));
    }
    p.out[e] = *reinterpret_cast<uint2*>(o);
}

}

static cudaTextureObject_t make_tex(const void* ptr, size_t bytes, int words) {
    cudaResourceDesc rd = {}; cudaTextureDesc td = {};
    rd.resType = cudaResourceTypeLinear; rd.res.linear.devPtr = const_cast<void*>(ptr); rd.res.linear.sizeInBytes = bytes;
    rd.res.linear.desc = cudaCreateChannelDesc(32, words > 1 ? 32 : 0, words > 2 ? 32 : 0, words > 2 ? 32 : 0, cudaChannelFormatKindUnsigned);
    td.readMode = cudaReadModeElementType;
    cudaTextureObject_t t = 0;
    if (cudaCreateTextureObject(&t, &rd, &td, nullptr) != cudaSuccess) { t = 0; (void)cudaGetLastError(); }
    return t;
}

extern "C" void kernel_launch(void* const* d_in, const int* in_sizes, int n_in, void* d_out, int out_size) {
    typedef const __nv_bfloat16* B;
    Params p;
    p.m = (const uint2*)d_in[0]; p.idx_in = (const uint2*)d_in[1]; p.idx_out = (const uint2*)d_in[2]; p.dist = (B)d_in[3];
    p.angle = (const uint32_t*)d_in[4]; p.centers = (B)d_in[5]; p.ang_freq = (B)d_in[6]; p.w_rbf = (B)d_in[7]; p.w_sbf = (B)d_in[8];
    p.w_down = (B)d_in[9]; p.w_up = (B)d_in[10]; p.out = (uint2*)d_out;
    p.E = in_sizes[3]; p.T = in_sizes[1]; p.T2 = p.T >> 1; p.zero = 0;
    p.R1 = p.R2 = p.rounds = p.lastn = p.full = 0; p.i1 = p.i2 = p.k1 = p.k2 = 0.f;
    static int ok = -1;
    static unsigned char* ring = nullptr;
    if (ok < 0) {
        void* ra = nullptr;
        cudaGetSymbolAddress(&ra, g_ring);
        ring = reinterpret_cast<unsigned char*>(((uintptr_t)ra + PAGE - 1) & ~(uintptr_t)(PAGE - 1));
        int dev = 0, sms = 0, occ = 0;
        cudaGetDevice(&dev);
        cudaDeviceGetAttribute(&sms, cudaDevAttrMultiProcessorCount, dev);
        cudaError_t e = cudaFuncSetAttribute(fused_kernel, cudaFuncAttributeMaxDynamicSharedMemorySize, SMEM_BYTES);
        if (e == cudaSuccess) e = cudaOccupancyMaxActiveBlocksPerMultiprocessor(&occ, fused_kernel, NTHR, SMEM_BYTES);
        ok = (e == cudaSuccess && occ >= 1 && sms >= NB) ? 1 : 0;
        (void)cudaGetLastError();
    }
    p.ring = ring;
    static cudaTextureObject_t tx[3];
    static const void* of[3];
    static int of_t = -1;
    if (of[0] != d_in[1] || of[1] != d_in[2] || of[2] != d_in[4] || of_t != p.T) {
        tx[0] = make_tex(p.idx_in, (size_t)(p.T >> 2) * 16, 4); tx[1] = make_tex(p.idx_out, (size_t)(p.T >> 2) * 16, 4); tx[2] = make_tex(p.angle, (size_t)(p.T >> 2) * 8, 2);
        of[0] = d_in[1]; of[1] = d_in[2]; of[2] = d_in[4]; of_t = p.T;
    }
    p.ti = tx[0]; p.to = tx[1]; p.ta = tx[2];
    const bool fused = ok == 1 && p.E <= EMAX && p.E >= 2 * NB && p.E % 2 == 0 && p.T >= 2;
    if (fused) {
        p.R1 = ((p.E + NG - 1) / NG + 1) & ~1;
        if (p.R1 > 1024) p.R1 = (p.R1 + 15) & ~15;
        p.R2 = ((p.E + NB - 1) / NB + 1) & ~1;
        p.i1 = nextafterf(1.f / p.R1, 2.f); p.i2 = nextafterf(1.f / p.R2, 2.f); p.k1 = -(float)p.R1; p.k2 = -8.f * p.R2;
        const int per = NB * NPR;
        int full = p.T2 / per, rest = p.T2 - full * per;
        p.full = p.ti && p.to && p.ta ? full : 0;
        p.lastn = (rest + NB - 1) / NB;
        if (p.lastn > NPR / 2) { full++; p.lastn = 0; }
        if (full < D) { full = D; p.lastn = 0; }
        p.rounds = full + 1;
        fused_kernel<<<NB, NTHR, SMEM_BYTES>>>(p);
    } else {
        for (int e0 = 0; e0 < p.E; e0 += EMAX) {
            int e1 = p.E - e0 < EMAX ? p.E : e0 + EMAX;
            fb_scatter<<<1056, 256>>>(p.m, (const int*)d_in[1], (const int*)d_in[2], (const uint16_t*)d_in[4], p.ang_freq, p.T, e0, e1);
            fb_final<<<(e1 - e0 + 255) / 256, 256>>>(p, e0, e1);
        }
    }
}
```
